```python
import torch

def _softmax(x, axis=-1):
    return torch.softmax(x, dim=axis)
def _gelu(x):
    return torch.nn.functional.gelu(x, approximate="tanh")
def _silu(x):
    return torch.nn.functional.silu(x)
def _sigmoid(x):
    return torch.sigmoid(x)
def _layernorm(x, axis=-1, eps=1e-5):
    m = x.mean(dim=axis, keepdim=True)
    v = x.var(dim=axis, keepdim=True, unbiased=False)
    return (x - m) / torch.sqrt(v + eps)
def _scatter_add(tgt, idx, src, axis=0):
    return tgt.clone().index_add_(axis, idx, src)
def _segment_sum(src, seg, n):
    out = torch.zeros((n,) + src.shape[1:], dtype=src.dtype)
    return out.index_add_(0, seg, src)
def _pad(x, pw):
    flat = tuple(v for pair in reversed(pw) for v in pair)
    return torch.nn.functional.pad(x, flat)

kernel_name = 'sequential_preLN__spectral_fnet__moe_arch_mod__prompt'

def setup_inputs():

    _w = (lambda a: (lambda t: t.to(torch.bfloat16) if t.is_floating_point() else t)(torch.as_tensor(a)))
    def _A_setup():
        B, S, D = 1, 2048, 1024
        ns = torch.arange(S)[:, None] * torch.arange(S)[None, :]
        nd = torch.arange(D)[:, None] * torch.arange(D)[None, :]
        Ws_re = torch.cos(-2.0 * torch.pi * ns / S).to(float)
        Ws_im = torch.sin(-2.0 * torch.pi * ns / S).to(float)
        Wd_re = torch.cos(-2.0 * torch.pi * nd / D).to(float)
        Wd_im = torch.sin(-2.0 * torch.pi * nd / D).to(float)
        return {
            "x": _w((lambda *s: torch.randn(*s, dtype=torch.bfloat16) * 0.05)(B, S, D)),
            "dft_seq_re": _w(Ws_re),
            "dft_seq_im": _w(Ws_im),
            "dft_hid_re": _w(Wd_re),
            "dft_hid_im": _w(Wd_im),
        }
    _A_in = _A_setup()

    def _B_setup():
        B, S, D, F, C = 1, 2048, 1024, 3584, 1
        return {
            "x": _w((lambda *s: torch.randn(*s, dtype=torch.bfloat16) * 0.05)(B, S, D)),
            "w_r": _w((lambda *s: torch.randn(*s, dtype=torch.bfloat16) * 1.6)(D)),
            "w_gate": _w((lambda *s: torch.randn(*s, dtype=torch.bfloat16) * 0.4)(D, F)),
            "w_up": _w((lambda *s: torch.randn(*s, dtype=torch.bfloat16) * 0.4)(D, F)),
            "w_down": _w((lambda *s: torch.randn(*s, dtype=torch.bfloat16) * 0.4)(F, D)),
        }
    _B_in = _B_setup()

    return {
        "A_x": _A_in["x"],
        "A_dft_seq_re": _A_in["dft_seq_re"],
        "A_dft_seq_im": _A_in["dft_seq_im"],
        "A_dft_hid_re": _A_in["dft_hid_re"],
        "A_dft_hid_im": _A_in["dft_hid_im"],
        "B_x": _B_in["x"],
        "B_w_r": _B_in["w_r"],
        "B_w_gate": _B_in["w_gate"],
        "B_w_up": _B_in["w_up"],
        "B_w_down": _B_in["w_down"],
    }

def reference(A_x, A_dft_seq_re, A_dft_seq_im, A_dft_hid_re, A_dft_hid_im, B_x, B_w_r, B_w_gate, B_w_up, B_w_down):
    def _A_ref(x, dft_seq_re, dft_seq_im, dft_hid_re, dft_hid_im):
        a = torch.einsum("bsd,ed->bse", x, dft_hid_re)
        b = torch.einsum("bsd,ed->bse", x, dft_hid_im)
        y = torch.einsum("ts,bse->bte", dft_seq_re, a) - torch.einsum("ts,bse->bte", dft_seq_im, b)
        return y

    def _B_ref(x, w_r, w_gate, w_up, w_down):
        B, S, D = x.shape
        C = 1
        r = x @ w_r
        idx = torch.argsort(-r, axis=-1)[:, :C]
        idx_e = (lambda x, n, axis: torch.repeat_interleave(x, n, dim=axis))(idx.reshape(B, C, 1), D, axis=2)
        x_sel = (lambda x, i, axis: torch.take_along_dim(x, i, dim=axis))(x, idx_e, axis=1)
        g = _silu(x_sel @ w_gate)
        u = x_sel @ w_up
        y = (g * u) @ w_down
        r_sel = _sigmoid((lambda x, i, axis: torch.take_along_dim(x, i, dim=axis))(r, idx, axis=1))
        y = y * r_sel.reshape(B, C, 1)
        b_off = (torch.arange(B) * S).reshape(B, 1)
        flat_idx = (idx + b_off).reshape(B * C)
        zero = (x * 0.0).reshape(B * S, D)
        upd = _scatter_add(zero, flat_idx, y.reshape(B * C, D), axis=0)
        return x + upd.reshape(B, S, D)

    x = A_x
    h = x + _A_ref(_layernorm(x, axis=-1), A_dft_seq_re, A_dft_seq_im, A_dft_hid_re, A_dft_hid_im)
    h2 = h + _B_ref(_layernorm(h, axis=-1), B_w_r, B_w_gate, B_w_up, B_w_down)
    return h2
```

```cpp
#include <cuda.h>
#include <cuda_runtime.h>
#include <cuda_bf16.h>
#include <stdint.h>
#include <type_traits>

typedef __nv_bfloat16 bf16;

constexpr int NGRID = 132, NTHR = 384;
#define SIGMA(tau, i) (((tau) + (i)) & 7)
constexpr int A_BYTES = 128 * 64 * 2;
constexpr int B_BYTES = 256 * 64 * 2;
constexpr int ST_BYTES = A_BYTES + B_BYTES;
constexpr int OFF_AUX = 4 * ST_BYTES;
constexpr int OFF_BAR = OFF_AUX + 32768;
constexpr int OFF_XS = OFF_BAR + 256;
constexpr int OFF_WR = OFF_XS + 2048;
constexpr int OFF_REM = OFF_WR + 256;
constexpr int OFF_INFO = OFF_REM + 256;
constexpr int SMEM_TOTAL = OFF_INFO + 256;
constexpr int INFO_WSUM = OFF_INFO, INFO_TAG = OFF_INFO + 4, INFO_KEY = OFF_INFO + 8, INFO_CAND = OFF_INFO + 16, INFO_ONES = OFF_INFO + 48, INFO_DS = OFF_INFO + 64, INFO_DS2 = OFF_INFO + 192;
constexpr int OFF_RS = OFF_XS;
constexpr int OFF_WC = OFF_AUX;
constexpr int OFF_EXA = OFF_AUX + 4096;
constexpr int OFF_EXB = OFF_AUX + 6144;
constexpr int OFF_RECV = A_BYTES;
__host__ __device__ constexpr int off_y(int w) { return w * ST_BYTES; }
constexpr int NSRC = 112;
enum { B_FULL = 0, B_EMPTY = 4, B_EP = 8, B_AW = 16, B_STAT = 24, B_WC = 25, B_CD = 26, B_ALL = 27, B_INFO = 28, B_PEER = 29, B_XCH = 30, B_GUX = (OFF_INFO + 128 - OFF_BAR) / 8 };
enum { NB_TURN0 = 1, NB_TURN1 = 2, NB_BOTH = 3, NB_AUX = 4, NB_H = 5 };

struct Scratch;
struct Params {
  CUtensorMap tmD0, tmD1, tmX, tmW0, tmW1, tmAbS, tmAbL, tmG, tmU, tmDn;
  const bf16* x; const bf16* Dre; const bf16* Dim; const bf16* wr; const bf16* wdown; const bf16* wgate; const bf16* wup; const bf16* Wre; const bf16* Wim;
  bf16* out; Scratch* sc;
};

__device__ __align__(1024) bf16 g_abT[2048 * 2048];
struct Scratch {
  alignas(128) uint4 xz[2048];
  alignas(128) uint2 dsum[2048];
  alignas(128) uint32_t abflag[128 * 2 * 32];
  alignas(128) uint32_t abdone[128 * 32];
  alignas(128) uint2 u[4 * 512];
  alignas(128) uint2 cl[128 * 16];
  alignas(128) uint4 cpart[4 * 16 * 512];
  alignas(128) uint2 ch[4 * 128 * 16];
  alignas(128) uint2 rdone[128];
  alignas(128) uint2 sel[4 * 1024];
  alignas(128) uint2 selkey[4 * 128 * 16];
  alignas(128) uint4 ypart[4 * NSRC * 64];
  alignas(128) uint4 hstat[16 * 8 * 128];
  alignas(128) uint2 key[128];
  alignas(128) uint2 hrow[128 * 512];
  alignas(128) uint2 fpart[8 * 1024];
  alignas(128) uint32_t epoch;
};
__device__ Scratch g_sc;

#define SPIN_LIMIT (1u << 17)
#define PF1_K 6
#define PF2_K 24
#define UNIT_PACE 1500
#define POLL_E 3
#define PFMODE 0
#define XPF_K 36
#define XS_DELAY 600
#define U_CLK 4400
#define XROW_PF 0
#define DROW_PF 0
#define Z_CLK 9500
#define CH_CLK 29000
#define CP_DELAY 2500
#define SEL_CLK 30000
#define YPART_DELAY 14000
__device__ __forceinline__ uint32_t smem_u32(const void* p) { return (uint32_t)__cvta_generic_to_shared(p); }
__device__ __forceinline__ uint32_t clk32() { uint32_t c; asm volatile("mov.u32 %0, %%clock;" : "=r"(c)); return c; }
__device__ __forceinline__ uint32_t zero_here() { uint64_t c; asm volatile("mov.u64 %0, %%clock64;" : "=l"(c) :: "memory"); return (uint32_t)(c >> 32) & threadIdx.y; }
__device__ __forceinline__ uint32_t uniform_zero_here() { uint32_t c; asm volatile("mov.u32 %0, %%clock;" : "=r"(c) :: "memory"); return c & blockIdx.y; }
__device__ __forceinline__ void wait_clk(uint32_t t0, uint32_t dt) {
#pragma unroll 1
  while (clk32() - t0 < dt) __nanosleep(100);
}
__device__ __forceinline__ void mbar_init(uint32_t bar, uint32_t cnt) { asm volatile("mbarrier.init.shared::cta.b64 [%0], %1;" :: "r"(bar), "r"(cnt) : "memory"); }
__device__ __forceinline__ void mbar_expect_tx(uint32_t bar, uint32_t bytes) { asm volatile("mbarrier.arrive.expect_tx.shared::cta.b64 _, [%0], %1;" :: "r"(bar), "r"(bytes) : "memory"); }
__device__ __forceinline__ void mbar_arrive(uint32_t bar) { asm volatile("mbarrier.arrive.shared::cta.b64 _, [%0];" :: "r"(bar) : "memory"); }
__device__ __forceinline__ void mbar_arrive_remote(uint32_t cluster_addr) { asm volatile("mbarrier.arrive.shared::cluster.b64 _, [%0];" :: "r"(cluster_addr) : "memory"); }
__device__ __forceinline__ void mbar_wait(uint32_t bar, uint32_t parity) {
  asm volatile("{\n.reg .pred p;\n.reg .u32 n;\n"
               "mbarrier.try_wait.parity.shared::cta.b64 p, [%0], %1;\n@p bra DONE;\nmov.u32 n, 0;\n"
               "LOOP:\nmbarrier.try_wait.parity.shared::cta.b64 p, [%0], %1;\nadd.u32 n, n, 1;\nsetp.ge.or.u32 p, n, 0x20000, p;\n@!p bra LOOP;\n"
               "DONE:\n}\n" :: "r"(bar), "r"(parity) : "memory");
}
__device__ __forceinline__ bool mbar_test(uint32_t bar, uint32_t parity) {
  uint32_t ok;
  asm volatile("{\n.reg .pred p;\nmbarrier.test_wait.parity.shared::cta.b64 p, [%1], %2;\nselp.u32 %0, 1, 0, p;\n}\n" : "=r"(ok) : "r"(bar), "r"(parity) : "memory");
  return ok != 0;
}
__device__ __forceinline__ void tma_load_2d(uint32_t dst, const CUtensorMap* tm, uint32_t bar, int c0, int c1) {
  asm volatile("cp.async.bulk.tensor.2d.shared::cluster.global.mbarrier::complete_tx::bytes [%0], [%1, {%3, %4}], [%2];"
    :: "r"(dst), "l"(tm), "r"(bar), "r"(c0), "r"(c1) : "memory");
}
__device__ __forceinline__ void tma_load_2d_hint(uint32_t dst, const CUtensorMap* tm, uint32_t bar, int c0, int c1, uint64_t pol) {
  asm volatile("cp.async.bulk.tensor.2d.shared::cluster.global.mbarrier::complete_tx::bytes.L2::cache_hint [%0], [%1, {%3, %4}], [%2], %5;"
    :: "r"(dst), "l"(tm), "r"(bar), "r"(c0), "r"(c1), "l"(pol) : "memory");
}
__device__ __forceinline__ uint64_t policy_evict_first() { uint64_t p; asm volatile("createpolicy.fractional.L2::evict_first.b64 %0, 1.0;" : "=l"(p)); return p; }
__device__ __forceinline__ void tma_store_2d(const CUtensorMap* tm, uint32_t src, int c0, int c1) {
  asm volatile("cp.async.bulk.tensor.2d.global.shared::cta.bulk_group [%0, {%2, %3}], [%1];" :: "l"(tm), "r"(src), "r"(c0), "r"(c1) : "memory");
}
__device__ __forceinline__ void bulk_load(uint32_t dst, const void* src, uint32_t bytes, uint32_t bar) {
  asm volatile("cp.async.bulk.shared::cluster.global.mbarrier::complete_tx::bytes [%0], [%1], %2, [%3];" :: "r"(dst), "l"(src), "r"(bytes), "r"(bar) : "memory");
}
__device__ __forceinline__ void prefetch_l2(const void* p) { asm volatile("prefetch.global.L2 [%0];" :: "l"(p)); }
__device__ __forceinline__ void bulk_commit() { asm volatile("cp.async.bulk.commit_group;" ::: "memory"); }
__device__ __forceinline__ void bulk_wait_all() { asm volatile("cp.async.bulk.wait_group 0;" ::: "memory"); }
__device__ __forceinline__ void fence_async_smem() { asm volatile("fence.proxy.async.shared::cta;" ::: "memory"); }
__device__ __forceinline__ void wgmma_fence() { asm volatile("wgmma.fence.sync.aligned;" ::: "memory"); }
__device__ __forceinline__ void wgmma_commit() { asm volatile("wgmma.commit_group.sync.aligned;" ::: "memory"); }
template<int N> __device__ __forceinline__ void wgmma_wait() { asm volatile("wgmma.wait_group.sync.aligned %0;" :: "n"(N) : "memory"); }
__device__ __forceinline__ void bar_sync(int id, int n) { asm volatile("bar.sync %0, %1;" :: "r"(id), "r"(n) : "memory"); }
__device__ __forceinline__ void bar_arrive(int id, int n) { asm volatile("bar.arrive %0, %1;" :: "r"(id), "r"(n) : "memory"); }
__device__ __forceinline__ void cluster_wait() { asm volatile("barrier.cluster.wait.aligned;" ::: "memory"); }
template<int R> __device__ __forceinline__ void reg_inc() { asm volatile("setmaxnreg.inc.sync.aligned.u32 %0;" :: "n"(R)); }
template<int R> __device__ __forceinline__ void reg_dec() { asm volatile("setmaxnreg.dec.sync.aligned.u32 %0;" :: "n"(R)); }
__device__ __forceinline__ bool elect_one() {
  uint32_t p;
  asm volatile("{\n.reg .pred q;\nelect.sync _|q, 0xffffffff;\nselp.u32 %0, 1, 0, q;\n}\n" : "=r"(p));
  return p != 0;
}
__device__ __forceinline__ uint32_t mapa(uint32_t addr, uint32_t cta) { uint32_t r; asm volatile("mapa.shared::cluster.u32 %0, %1, %2;" : "=r"(r) : "r"(addr), "r"(cta)); return r; }
__device__ __forceinline__ void st_async_v4(uint32_t addr, uint32_t bar, uint32_t a, uint32_t b, uint32_t c, uint32_t d) {
  asm volatile("st.async.weak.shared::cluster.mbarrier::complete_tx::bytes.v4.b32 [%0], {%2, %3, %4, %5}, [%1];" :: "r"(addr), "r"(bar), "r"(a), "r"(b), "r"(c), "r"(d) : "memory");
}
__device__ __forceinline__ void st_async_b32(uint32_t addr, uint32_t bar, uint32_t a) {
  asm volatile("st.async.weak.shared::cluster.mbarrier::complete_tx::bytes.b32 [%0], %2, [%1];" :: "r"(addr), "r"(bar), "r"(a) : "memory");
}
__device__ __forceinline__ void stsm_x4(uint32_t addr, uint32_t a, uint32_t b, uint32_t c, uint32_t d) {
  asm volatile("stmatrix.sync.aligned.m8n8.x4.shared.b16 [%0], {%1, %2, %3, %4};" :: "r"(addr), "r"(a), "r"(b), "r"(c), "r"(d) : "memory");
}
__device__ __forceinline__ void stsm_x4_t(uint32_t addr, uint32_t a, uint32_t b, uint32_t c, uint32_t d) {
  asm volatile("stmatrix.sync.aligned.m8n8.x4.trans.shared.b16 [%0], {%1, %2, %3, %4};" :: "r"(addr), "r"(a), "r"(b), "r"(c), "r"(d) : "memory");
}
__device__ __forceinline__ uint4 lds128(uint32_t addr) { uint4 v; asm volatile("ld.shared.v4.b32 {%0, %1, %2, %3}, [%4];" : "=r"(v.x), "=r"(v.y), "=r"(v.z), "=r"(v.w) : "r"(addr) : "memory"); return v; }
extern __shared__ __align__(1024) uint8_t smem_raw[];
template<class T> __device__ __forceinline__ T& SM(int off) { return *reinterpret_cast<T*>(smem_raw + off); }
__device__ __forceinline__ uint4 ldg_nc128(const void* p) { uint4 v; asm volatile("ld.global.nc.v4.b32 {%0, %1, %2, %3}, [%4];" : "=r"(v.x), "=r"(v.y), "=r"(v.z), "=r"(v.w) : "l"(p)); return v; }
__device__ __forceinline__ uint4 ldg128(const void* p) { uint4 v; asm volatile("ld.global.L1::no_allocate.v4.b32 {%0, %1, %2, %3}, [%4];" : "=r"(v.x), "=r"(v.y), "=r"(v.z), "=r"(v.w) : "l"(p) : "memory"); return v; }
__device__ __forceinline__ void pkt_st128(void* p, uint32_t a, uint32_t b, uint32_t c, uint32_t d) {
  asm volatile("{\n.reg .b128 v;\n.reg .b64 lo, hi;\nmov.b64 lo, {%1, %2};\nmov.b64 hi, {%3, %4};\nmov.b128 v, {lo, hi};\nst.relaxed.gpu.global.b128 [%0], v;\n}\n"
    :: "l"(p), "r"(a), "r"(b), "r"(c), "r"(d) : "memory");
}
__device__ __forceinline__ uint4 pkt_ld128(const void* p) {
  uint4 r;
  asm volatile("{\n.reg .b128 v;\n.reg .b64 lo, hi;\nld.relaxed.gpu.global.b128 v, [%4];\nmov.b128 {lo, hi}, v;\nmov.b64 {%0, %1}, lo;\nmov.b64 {%2, %3}, hi;\n}\n"
    : "=r"(r.x), "=r"(r.y), "=r"(r.z), "=r"(r.w) : "l"(p) : "memory");
  return r;
}
__device__ __forceinline__ void pkt_st64(void* p, uint32_t a, uint32_t b) {
  asm volatile("{\n.reg .b64 v;\nmov.b64 v, {%1, %2};\nst.relaxed.gpu.global.b64 [%0], v;\n}\n" :: "l"(p), "r"(a), "r"(b) : "memory");
}
__device__ __forceinline__ uint2 pkt_ld64(const void* p) {
  uint2 r;
  asm volatile("{\n.reg .b64 v;\nld.relaxed.gpu.global.b64 v, [%2];\nmov.b64 {%0, %1}, v;\n}\n" : "=r"(r.x), "=r"(r.y) : "l"(p) : "memory");
  return r;
}
__device__ __forceinline__ void pkt_clear128(void* p) { pkt_st128(p, 0, 0, 0, 0); }
__device__ __forceinline__ uint32_t ld_relaxed32(const void* p) { uint32_t v; asm volatile("ld.relaxed.gpu.global.b32 %0, [%1];" : "=r"(v) : "l"(p) : "memory"); return v; }
__device__ __forceinline__ uint32_t ld_acquire32(const void* p) { uint32_t v; asm volatile("ld.acquire.gpu.global.b32 %0, [%1];" : "=r"(v) : "l"(p) : "memory"); return v; }
__device__ __forceinline__ void st_relaxed32(void* p, uint32_t v) { asm volatile("st.relaxed.gpu.global.b32 [%0], %1;" :: "l"(p), "r"(v) : "memory"); }
__device__ __forceinline__ uint32_t poll64(const void* p, uint32_t tag, int ns) {
  uint2 v; uint32_t n = 0;
#pragma unroll 1
  while (true) {
    v = pkt_ld64(p);
    if (v.y == tag || ++n > SPIN_LIMIT) break;
    __nanosleep(ns);
  }
  return v.x;
}
__device__ __forceinline__ uint32_t poll64_warp(const void* p, uint32_t tag, int ns) {
  uint2 v; uint32_t n = 0;
#pragma unroll 1
  while (true) {
    v = pkt_ld64(p);
    if (__all_sync(0xffffffffu, v.y == tag) || ++n > SPIN_LIMIT) break;
    __nanosleep(ns);
  }
  return v.x;
}
__device__ __forceinline__ uint32_t code_of(uint32_t tag) { return tag % 3u + 1u; }
__device__ __forceinline__ uint32_t with_bit(uint32_t v, uint32_t bit) { return (v & ~1u) | (bit & 1u); }
__device__ __forceinline__ uint32_t with_bit(float v, uint32_t bit) { return with_bit(__float_as_uint(v), bit); }
__device__ __forceinline__ void chk(uint32_t& bad, uint32_t a, uint32_t want) { bad |= a ^ want; asm("" : "+r"(bad)); }
__device__ __forceinline__ void chk_code(uint32_t& bad, const uint4& v, uint32_t c0, uint32_t c1) { chk(bad, v.x, c0); chk(bad, v.y, c1); chk(bad, v.z, c0); chk(bad, v.w, c1); }
__device__ __forceinline__ void poll_code(const void* p, uint32_t c0, uint32_t c1, int ns) {
  uint32_t n = 0;
#pragma unroll 1
  while (true) {
    const uint2 v = pkt_ld64(p);
    if (!(((v.x ^ c0) | (v.y ^ c1)) & 1) || ++n > SPIN_LIMIT) break;
    __nanosleep(ns);
  }
}
__device__ __forceinline__ uint32_t pack_bf16(float lo, float hi) { uint32_t r; asm("cvt.rn.bf16x2.f32 %0, %1, %2;" : "=r"(r) : "f"(hi), "f"(lo)); return r; }
__device__ __forceinline__ float bf_lo(uint32_t v) { return __uint_as_float(v << 16); }
__device__ __forceinline__ float bf_hi(uint32_t v) { return __uint_as_float(v & 0xFFFF0000u); }
__device__ __forceinline__ float bf16r(float x) { return __uint_as_float(pack_bf16(0.f, x)); }
__device__ __forceinline__ void st_bf16(bf16* p, float x) { *reinterpret_cast<uint16_t*>(p) = (uint16_t)pack_bf16(x, 0.f); }
__device__ __forceinline__ float fast_rcp(float x) { float r; asm("rcp.approx.f32 %0, %1;" : "=f"(r) : "f"(x)); return r; }
__device__ __forceinline__ float ldbf(const bf16* p) { return __bfloat162float(*p); }
__device__ __forceinline__ uint32_t badd2(uint32_t a, uint32_t b) { uint32_t r; asm("add.rn.bf16x2 %0, %1, %2;" : "=r"(r) : "r"(a), "r"(b)); return r; }
__device__ __forceinline__ uint32_t bfma2(uint32_t a, uint32_t b, uint32_t c) { uint32_t r; asm("fma.rn.bf16x2 %0, %1, %2, %3;" : "=r"(r) : "r"(a), "r"(b), "r"(c)); return r; }
__device__ __forceinline__ float warp_sum(float v) {
#pragma unroll
  for (int o = 16; o > 0; o >>= 1) v += __shfl_xor_sync(0xffffffffu, v, o);
  return v;
}
template<int N> __device__ __forceinline__ void fold(float* v, int o, int lane) {
  const bool up = lane & o;
#pragma unroll
  for (int i = 0; i < N / 2; i++) {
    const float keep = up ? v[N / 2 + i] : v[i], send = up ? v[i] : v[N / 2 + i];
    v[i] = keep + __shfl_xor_sync(0xffffffffu, send, o);
  }
}
__device__ __forceinline__ uint32_t make_key(float r_bf, int row) {
  const uint32_t u = __float_as_uint(r_bf);
  return (((u & 0x80000000u) ? ~u : (u | 0x80000000u)) & 0xFFFF0000u) | (0xFFFFu - (uint32_t)row);
}
__device__ __forceinline__ int key_row(uint32_t key) { return (0xFFFF - (int)(key & 0xFFFFu)) & 2047; }
__device__ __forceinline__ float key_val(uint32_t key) { const uint32_t o = key & 0xFFFF0000u; return __uint_as_float((o & 0x80000000u) ? (o & 0x7FFFFFFFu) : (~o & 0xFFFF0000u)); }
__device__ __forceinline__ float ref_sd(float var) { float r; asm("sqrt.approx.f32 %0, %1;" : "=f"(r) : "f"(bf16r(bf16r(var) + 1e-5f))); return bf16r(r); }
__device__ __forceinline__ uint64_t make_desc(uint32_t addr) { return (uint64_t)((addr & 0x3FFFF) >> 4) | ((uint64_t)64 << 32) | ((uint64_t)1 << 62); }
__device__ __forceinline__ uint64_t make_desc_noswz(uint32_t addr) { return (uint64_t)((addr & 0x3FFFF) >> 4) | ((uint64_t)8 << 32); }
#define ACC8(d, o) "+f"(d[o]), "+f"(d[o + 1]), "+f"(d[o + 2]), "+f"(d[o + 3]), "+f"(d[o + 4]), "+f"(d[o + 5]), "+f"(d[o + 6]), "+f"(d[o + 7])
#define ACC64(d, o) ACC8(d, o), ACC8(d, o + 8), ACC8(d, o + 16), ACC8(d, o + 24), ACC8(d, o + 32), ACC8(d, o + 40), ACC8(d, o + 48), ACC8(d, o + 56)
#define REGS64 "%0, %1, %2, %3, %4, %5, %6, %7, %8, %9, %10, %11, %12, %13, %14, %15, %16, %17, %18, %19, %20, %21, %22, %23, %24, %25, %26, %27, %28, %29, %30, %31, " \
    "%32, %33, %34, %35, %36, %37, %38, %39, %40, %41, %42, %43, %44, %45, %46, %47, %48, %49, %50, %51, %52, %53, %54, %55, %56, %57, %58, %59, %60, %61, %62, %63"
#define REGS128 REGS64 ", %64, %65, %66, %67, %68, %69, %70, %71, %72, %73, %74, %75, %76, %77, %78, %79, %80, %81, %82, %83, %84, %85, %86, %87, %88, %89, %90, %91, %92, %93, %94, %95, " \
    "%96, %97, %98, %99, %100, %101, %102, %103, %104, %105, %106, %107, %108, %109, %110, %111, %112, %113, %114, %115, %116, %117, %118, %119, %120, %121, %122, %123, %124, %125, %126, %127"
__device__ __forceinline__ void wgmma_n256(float (&d)[128], uint64_t da, uint64_t db) {
  asm volatile("wgmma.mma_async.sync.aligned.m64n256k16.f32.bf16.bf16 {" REGS128 "}, %128, %129, 1, 1, 1, 0, 0;\n"
    : ACC64(d, 0), ACC64(d, 64) : "l"(da), "l"(db));
}
#define OUT8(d, o) "=f"(d[o]), "=f"(d[o + 1]), "=f"(d[o + 2]), "=f"(d[o + 3]), "=f"(d[o + 4]), "=f"(d[o + 5]), "=f"(d[o + 6]), "=f"(d[o + 7])
#define OUT64(d, o) OUT8(d, o), OUT8(d, o + 8), OUT8(d, o + 16), OUT8(d, o + 24), OUT8(d, o + 32), OUT8(d, o + 40), OUT8(d, o + 48), OUT8(d, o + 56)
__device__ __forceinline__ void wgmma_n256_rs_init(float (&d)[128], const uint32_t* a, uint64_t db) {
  asm volatile("wgmma.mma_async.sync.aligned.m64n256k16.f32.bf16.bf16 {" REGS128 "}, {%128, %129, %130, %131}, %132, 0, 1, 1, 0;\n"
    : OUT64(d, 0), OUT64(d, 64) : "r"(a[0]), "r"(a[1]), "r"(a[2]), "r"(a[3]), "l"(db));
}
template<int ACCUM> __device__ __forceinline__ void wgmma_n256_rs(float (&d)[128], const uint32_t* a, uint64_t db) {
  asm volatile("wgmma.mma_async.sync.aligned.m64n256k16.f32.bf16.bf16 {" REGS128 "}, {%128, %129, %130, %131}, %132, %133, 1, 1, 0;\n"
    : ACC64(d, 0), ACC64(d, 64) : "r"(a[0]), "r"(a[1]), "r"(a[2]), "r"(a[3]), "l"(db), "n"(ACCUM));
}
template<int ACCUM> __device__ __forceinline__ void wgmma_n8_rs(float (&d)[4], const uint32_t* a, uint64_t db) {
  asm volatile("wgmma.mma_async.sync.aligned.m64n8k16.f32.bf16.bf16 {%0, %1, %2, %3}, {%4, %5, %6, %7}, %8, %9, 1, 1, 0;\n"
    : "+f"(d[0]), "+f"(d[1]), "+f"(d[2]), "+f"(d[3]) : "r"(a[0]), "r"(a[1]), "r"(a[2]), "r"(a[3]), "l"(db), "n"(ACCUM));
}
__device__ __forceinline__ void wgmma_n8(float (&d)[4], uint64_t da, uint64_t db) {
  asm volatile("wgmma.mma_async.sync.aligned.m64n8k16.f32.bf16.bf16 {%0, %1, %2, %3}, %4, %5, 1, 1, 1, 0, 0;\n"
    : "+f"(d[0]), "+f"(d[1]), "+f"(d[2]), "+f"(d[3]) : "l"(da), "l"(db));
}
__device__ __forceinline__ void wgmma_n128(float (&d)[64], uint64_t da, uint64_t db) {
  asm volatile("wgmma.mma_async.sync.aligned.m64n128k16.f32.bf16.bf16 {" REGS64 "}, %64, %65, 1, 1, 1, 0, 0;\n" : ACC64(d, 0) : "l"(da), "l"(db));
}
template<int N> __device__ __forceinline__ void fence_regs(float (&d)[N]) {
#pragma unroll
  for (int i = 0; i < N; i++) asm volatile("" : "+f"(d[i]) :: "memory");
}
__device__ __forceinline__ void mma16816(float (&c)[4], uint32_t a0, uint32_t a1, uint32_t a2, uint32_t a3, uint32_t b0, uint32_t b1) {
  asm volatile("mma.sync.aligned.m16n8k16.row.col.f32.bf16.bf16.f32 {%0, %1, %2, %3}, {%4, %5, %6, %7}, {%8, %9}, {%0, %1, %2, %3};"
               : "+f"(c[0]), "+f"(c[1]), "+f"(c[2]), "+f"(c[3]) : "r"(a0), "r"(a1), "r"(a2), "r"(a3), "r"(b0), "r"(b1));
}
__device__ __forceinline__ void fma8(float* acc, const uint4& v, float x) {
  acc[0] = fmaf(bf_lo(v.x), x, acc[0]); acc[1] = fmaf(bf_hi(v.x), x, acc[1]); acc[2] = fmaf(bf_lo(v.y), x, acc[2]); acc[3] = fmaf(bf_hi(v.y), x, acc[3]);
  acc[4] = fmaf(bf_lo(v.z), x, acc[4]); acc[5] = fmaf(bf_hi(v.z), x, acc[5]); acc[6] = fmaf(bf_lo(v.w), x, acc[6]); acc[7] = fmaf(bf_hi(v.w), x, acc[7]);
}
__device__ __forceinline__ float swiglu(float g, float u) {
  g = bf16r(g); u = bf16r(u);
  return bf16r(bf16r(g * fast_rcp(1.f + __expf(-g))) * u);
}

#define CT(slot) do {} while (0)
#define TIM(slot) do {} while (0)

constexpr int H_BUF0 = 0, H_BUF1 = 16384, H_RED = 32768, H_KEYS = H_RED + 1024, H_ROW = H_KEYS + 1024, H_ACT = H_ROW + 8192, H_PART = H_ACT + 4096;
__device__ __forceinline__ void hsync() { bar_sync(NB_H, 256); }
template<int N> __device__ __forceinline__ void block_sum(float (&v)[N], int warp, int lane) {
#pragma unroll
  for (int i = 0; i < N; i++) v[i] = warp_sum(v[i]);
  hsync();
  if (lane == 0) {
#pragma unroll
    for (int i = 0; i < N; i++) SM<float>(H_RED + (i * 8 + warp) * 4) = v[i];
  }
  hsync();
#pragma unroll
  for (int i = 0; i < N; i++) {
    const float4 a = SM<float4>(H_RED + i * 32), b = SM<float4>(H_RED + i * 32 + 16);
    v[i] = ((a.x + a.y) + (a.z + a.w)) + ((b.x + b.y) + (b.z + b.w));
  }
}
__device__ __forceinline__ void fft_first(int j, float2 v0, float2 v1, float2 v2, float2 v3) {
  const float2 a = make_float2(v0.x + v2.x, v0.y + v2.y), b = make_float2(v0.x - v2.x, v0.y - v2.y);
  const float2 c = make_float2(v1.x + v3.x, v1.y + v3.y), d = make_float2(v1.y - v3.y, v3.x - v1.x);
  SM<float4>(H_BUF1 + j * 32) = make_float4(a.x + c.x, a.y + c.y, b.x + d.x, b.y + d.y);
  SM<float4>(H_BUF1 + j * 32 + 16) = make_float4(a.x - c.x, a.y - c.y, b.x - d.x, b.y - d.y);
}
template<int NB> __device__ __forceinline__ void fft_passes(int tid) {
  constexpr int q = 256 * NB;
#pragma unroll 1
  for (int ps = 1; ps < 5; ps++) {
    const int ns = 1 << (2 * ps), k = tid & (ns - 1);
    float s1, c1;
    __sincosf(-1.57079632679f * __fdividef((float)k, (float)ns), &s1, &c1);
    const float c2 = c1 * c1 - s1 * s1, s2 = 2.f * c1 * s1, c3 = c1 * c2 - s1 * s2, s3 = c1 * s2 + s1 * c2;
    hsync();
#pragma unroll
    for (int i = 0; i < NB; i++) {
      const int j = tid + 256 * i;
      const float2* in = &SM<float2>((ps & 1) ? H_BUF1 : H_BUF0);
      float2* o = &SM<float2>((ps & 1) ? H_BUF0 : H_BUF1) + (j - k) * 4 + k;
      const float2 v0 = in[j], x1 = in[j + q], x2 = in[j + 2 * q], x3 = in[j + 3 * q];
      const float2 v1 = make_float2(x1.x * c1 - x1.y * s1, x1.x * s1 + x1.y * c1);
      const float2 v2 = make_float2(x2.x * c2 - x2.y * s2, x2.x * s2 + x2.y * c2);
      const float2 v3 = make_float2(x3.x * c3 - x3.y * s3, x3.x * s3 + x3.y * c3);
      const float2 a = make_float2(v0.x + v2.x, v0.y + v2.y), b = make_float2(v0.x - v2.x, v0.y - v2.y);
      const float2 c = make_float2(v1.x + v3.x, v1.y + v3.y), d = make_float2(v1.y - v3.y, v3.x - v1.x);
      o[0] = make_float2(a.x + c.x, a.y + c.y); o[ns] = make_float2(b.x + d.x, b.y + d.y);
      o[2 * ns] = make_float2(a.x - c.x, a.y - c.y); o[3 * ns] = make_float2(b.x - d.x, b.y - d.y);
    }
  }
  hsync();
}
template<int NR> __device__ __forceinline__ void ln_rows(const float (&h)[NR][4], float (&hn)[NR][4], int warp, int lane) {
  float s[NR], q[NR];
#pragma unroll
  for (int i = 0; i < NR; i++) s[i] = (h[i][0] + h[i][1]) + (h[i][2] + h[i][3]);
  block_sum(s, warp, lane);
#pragma unroll
  for (int i = 0; i < NR; i++) {
    s[i] *= 1.f / 1024.f; q[i] = 0.f;
#pragma unroll
    for (int z = 0; z < 4; z++) q[i] = fmaf(h[i][z] - s[i], h[i][z] - s[i], q[i]);
  }
  block_sum(q, warp, lane);
#pragma unroll
  for (int i = 0; i < NR; i++) {
    const float mb = bf16r(s[i]), inv = fast_rcp(ref_sd(q[i] * (1.f / 1024.f)));
#pragma unroll
    for (int z = 0; z < 4; z++) hn[i][z] = bf16r(bf16r(h[i][z] - mb) * inv);
  }
}
__device__ __forceinline__ float routed_out(float h, float hn, float y, float r) {
  const float sig = bf16r(fast_rcp(1.f + __expf(-r)));
  return h + bf16r(hn + bf16r(bf16r(y) * sig));
}

__device__ __forceinline__ void helper_cta(const Params& p, const int hi, const uint32_t t_entry) {
  const int tid = threadIdx.x, warp = tid >> 5, lane = tid & 31;
  const float w0 = ldbf(p.wr + tid), w1 = ldbf(p.wr + tid + 256), w2 = ldbf(p.wr + tid + 512), w3 = ldbf(p.wr + tid + 768), wf = ldbf(p.wr);
  const uint32_t tag = ld_relaxed32(&p.sc->epoch) + 1;
  pkt_clear128(&p.sc->u[hi * 512 + tid * 2]);
  if (tid == 0 && w0 != 123.f) TIM(12);
  fft_first(tid, make_float2(w0, 0.f), make_float2(w1, 0.f), make_float2(w2, 0.f), make_float2(w3, 0.f));
  fft_passes<1>(tid);
  const uint32_t c0 = code_of(tag), c1 = c0 >> 1;
  {
    const float off = wf - SM<float>(H_BUF1) * (1.f / 1024.f);
    const float4 v = SM<float4>(H_BUF1 + tid * 32), u = SM<float4>(H_BUF1 + tid * 32 + 16);
    pkt_st128(&p.sc->u[hi * 512 + tid * 2], with_bit(pack_bf16((tid ? v.x : 0.f) - off, v.z - off), c0), with_bit(pack_bf16(v.y, v.w), c1),
              with_bit(pack_bf16(u.x - off, u.z - off), c0), with_bit(pack_bf16(u.y, u.w), c1));
    pkt_clear128(&p.sc->sel[hi * 1024 + tid * 2]); pkt_clear128(&p.sc->sel[hi * 1024 + 512 + tid * 2]);
    if (tid < 128) { pkt_clear128(&p.sc->selkey[(hi * 128 + tid) * 16]); pkt_clear128(&p.sc->selkey[(hi * 128 + tid) * 16 + 2]); }
    else if (tid >= 192) pkt_clear128(&p.sc->cl[(hi * 32 + ((tid - 192) >> 1)) * 16 + (tid & 1) * 2]);
    hsync();
  }
  if (tid == 0) TIM(0);
  {
    float tw[8];
#pragma unroll
    for (int i = 0; i < 4; i++) __sincosf((float)(tid + 256 * i) * (-6.28318530718f / 2048.f), &tw[2 * i], &tw[2 * i + 1]);
    wait_clk(t_entry, Z_CLK);
    uint2 z[8]; uint32_t n = 0;
#pragma unroll 1
    while (true) {
      uint32_t bad = 0;
#pragma unroll
      for (int i = 0; i < 8; i++) z[i] = pkt_ld64(reinterpret_cast<const uint2*>(&p.sc->xz[tid + 256 * i]) + 1);
#pragma unroll
      for (int i = 0; i < 8; i++) chk(bad, z[i].y, tag);
      if (!bad || ++n > SPIN_LIMIT) break;
      __nanosleep(150);
    }
#pragma unroll
    for (int i = 0; i < 2; i++)
      fft_first(tid + 256 * i, make_float2(bf_lo(z[i].x), bf_hi(z[i].x)), make_float2(bf_lo(z[i + 2].x), bf_hi(z[i + 2].x)),
                make_float2(bf_lo(z[i + 4].x), bf_hi(z[i + 4].x)), make_float2(bf_lo(z[i + 6].x), bf_hi(z[i + 6].x)));
    if (tid == 0) TIM(7);
    fft_passes<2>(tid);
    if (tid == 0) TIM(1);
    uint32_t k8[8];
#pragma unroll
    for (int i = 0; i < 4; i++) {
      const int k = tid + 256 * i;
      const float2 v0 = SM<float2>(H_BUF1 + k * 8), v1 = SM<float2>(H_BUF1 + (k + 1024) * 8);
      const float w = v1.x * tw[2 * i + 1] - v1.y * tw[2 * i];
      const uint32_t a = __float_as_uint(v0.x + w), b = __float_as_uint(v0.x - w);
      k8[2 * i] = (((a & 0x80000000u) ? ~a : (a | 0x80000000u)) & ~2047u) | k;
      k8[2 * i + 1] = (((b & 0x80000000u) ? ~b : (b | 0x80000000u)) & ~2047u) | (k + 1024);
    }
    uint32_t lim = 0xFFFFFFFFu;
#pragma unroll 1
    for (int r = 0; r < 4; r++) {
      uint32_t mx = 0;
#pragma unroll
      for (int i = 0; i < 8; i++) mx = max(mx, k8[i] <= lim ? k8[i] : 0u);
      mx = __reduce_max_sync(0xffffffffu, mx);
      if (lane == 0) SM<uint32_t>(H_KEYS + (warp * 4 + r) * 4) = mx;
      lim = mx - 1;
    }
    hsync();
    if (tid < 32) {
      const uint32_t me = SM<uint32_t>(H_KEYS + tid * 4);
      int rank = 0;
#pragma unroll
      for (int i = 0; i < 8; i++) { const uint4 o = SM<uint4>(H_KEYS + i * 16); rank += (o.x > me) + (o.y > me) + (o.z > me) + (o.w > me); }
      if (rank < 8) SM<uint16_t>(H_KEYS + 256 + rank * 2) = me & 2047u;
    }
    hsync();
    if (tid >= 128) pkt_st64(&p.sc->cl[(hi * 32 + ((tid - 128) >> 2)) * 16 + (tid & 3)], SM<uint32_t>(H_KEYS + 256 + (tid & 3) * 4), tag);
  }
  const uint32_t cpair = SM<uint32_t>(H_KEYS + 256 + hi * 4);
  const int ca = cpair & 0xFFFF, cb = cpair >> 16;
  if (tid < 128) prefetch_l2(((tid & 32) ? p.Wim : p.Wre) + (size_t)((tid & 64) ? cb : ca) * 2048 + lane * 64);
  if (tid == 0) TIM(2);
  {
    const int e0 = (tid >> 2) * 16 + (tid & 3) * 2;
    const uint32_t wa = *reinterpret_cast<const uint32_t*>(p.wr + e0), wb = *reinterpret_cast<const uint32_t*>(p.wr + e0 + 8);
    wait_clk(t_entry, CH_CLK);
    uint4 va, vb; uint32_t n = 0;
#pragma unroll 1
    while (true) {
      const uint2* src = &p.sc->ch[(hi * 128 + (tid >> 1)) * 16 + (tid & 1) * 2];
      va = pkt_ld128(src); vb = pkt_ld128(src + 4);
      if ((va.y == tag && va.w == tag && vb.y == tag && vb.w == tag) || ++n > SPIN_LIMIT) break;
      __nanosleep(150);
    }
    if (tid == 0) TIM(3);
    const float h[2][4] = {{bf_lo(va.x), bf_hi(va.x), bf_lo(va.z), bf_hi(va.z)}, {bf_lo(vb.x), bf_hi(vb.x), bf_lo(vb.z), bf_hi(vb.z)}};
    float hn[2][4], r[2];
    ln_rows<2>(h, hn, warp, lane);
    if (tid == 0) TIM(13);
#pragma unroll
    for (int i = 0; i < 2; i++) r[i] = (hn[i][0] * bf_lo(wa) + hn[i][1] * bf_lo(wb)) + (hn[i][2] * bf_hi(wa) + hn[i][3] * bf_hi(wb));
    block_sum(r, warp, lane);
    const uint32_t ka = make_key(bf16r(r[0]), ca), kb = make_key(bf16r(r[1]), cb), mine = max(ka, kb);
    const bool s2 = kb > ka;
    pkt_st128(&p.sc->sel[hi * 1024 + tid * 2], s2 ? pack_bf16(hn[1][0], hn[1][1]) : pack_bf16(hn[0][0], hn[0][1]), tag, s2 ? pack_bf16(hn[1][2], hn[1][3]) : pack_bf16(hn[0][2], hn[0][3]), tag);
    pkt_st128(&p.sc->sel[hi * 1024 + 512 + tid * 2], s2 ? vb.x : va.x, tag, s2 ? vb.z : va.z, tag);
    if (tid < 128) pkt_st64(&p.sc->selkey[(hi * 128 + tid) * 16], mine, tag);
    if (tid == 0) TIM(14);
  }
}

__device__ __forceinline__ void slow_path(const Params& p, int grp, int eps, uint32_t tag, uint32_t key, int win) {
  const int tid = threadIdx.x, warp = tid >> 5, lane = tid & 31;
  uint32_t best = __reduce_max_sync(0xffffffffu, poll64(&p.sc->key[tid & 127], tag, 200));
  if (lane == 0) SM<uint32_t>(H_KEYS + warp * 4) = best;
  hsync();
  { const uint4 b4 = SM<uint4>(H_KEYS); best = max(max(b4.x, b4.y), max(b4.z, b4.w)); }
  const int tw = key_row(best), col = eps * 128 + (tid & 127);
  if ((tw >> 7) != grp) return;
  if (tid < 128) {
    const int pos = (col >> 4) * 8 + (col & 7);
    const uint32_t a = poll64(&p.sc->sel[win * 1024 + 512 + pos], tag, 100), b = poll64(&p.sc->sel[win * 1024 + pos], tag, 100);
    poll64(&p.sc->rdone[col >> 3], tag, 100);
    st_bf16(p.out + key_row(key) * 1024 + col, (col & 8) ? bf_hi(a) + bf_hi(b) : bf_lo(a) + bf_lo(b));
  }
  const uint32_t h0 = poll64(&p.sc->hrow[(tw >> 4) * 512 + 2 * tid], tag, 100), h1 = poll64(&p.sc->hrow[(tw >> 4) * 512 + 2 * tid + 1], tag, 100);
  float h[1][4] = {{bf_lo(h0), bf_hi(h0), bf_lo(h1), bf_hi(h1)}}, hn[1][4];
  ln_rows<1>(h, hn, warp, lane);
  SM<float4>(H_ROW + tid * 16) = make_float4(hn[0][0], hn[0][1], hn[0][2], hn[0][3]);
  SM<float4>(H_ROW + 4096 + tid * 16) = make_float4(h[0][0], h[0][1], h[0][2], h[0][3]);
  hsync();
  if (tid < 224) {
    const int part = tid / 56;
    const bf16* wp = ((part & 1) ? p.wup : p.wgate) + (part >> 1) * 512 * 3584 + eps * 448 + (tid - part * 56) * 8;
    float acc[8] = {0.f, 0.f, 0.f, 0.f, 0.f, 0.f, 0.f, 0.f};
#pragma unroll 8
    for (int d = 0; d < 512; d++) fma8(acc, ldg_nc128(wp + d * 3584), SM<float>(H_ROW + ((part >> 1) * 512 + d) * 4));
#pragma unroll
    for (int i = 0; i < 8; i++) SM<float>(H_PART + (tid * 8 + i) * 4) = acc[i];
  }
  hsync();
#pragma unroll 1
  for (int f = tid; f < 448; f += 256)
    SM<float>(H_ACT + f * 4) = swiglu(SM<float>(H_PART + f * 4) + SM<float>(H_PART + (896 + f) * 4), SM<float>(H_PART + (448 + f) * 4) + SM<float>(H_PART + (1344 + f) * 4));
  hsync();
  {
    const int fh = tid >> 7;
    const bf16* wp = p.wdown + (eps * 448 + fh * 224) * 1024 + (tid & 127) * 8;
    float acc[8] = {0.f, 0.f, 0.f, 0.f, 0.f, 0.f, 0.f, 0.f};
#pragma unroll 8
    for (int f = 0; f < 224; f++) fma8(acc, ldg_nc128(wp + f * 1024), SM<float>(H_ACT + (fh * 224 + f) * 4));
#pragma unroll
    for (int i = 0; i < 8; i++) SM<float>(H_PART + (tid * 8 + i) * 4) = acc[i];
  }
  hsync();
#pragma unroll 1
  for (int e = tid; e < 1024; e += 256) pkt_st64(&p.sc->fpart[eps * 1024 + e], __float_as_uint(SM<float>(H_PART + e * 4) + SM<float>(H_PART + (1024 + e) * 4)), tag);
  if (tid < 128) {
    float y = 0.f;
#pragma unroll 1
    for (int q = 0; q < 8; q++) y += __uint_as_float(poll64(&p.sc->fpart[q * 1024 + col], tag, 200));
    st_bf16(p.out + tw * 1024 + col, routed_out(SM<float>(H_ROW + 4096 + col * 4), SM<float>(H_ROW + col * 4), y, key_val(best)));
  }
}

template<int MAP>
__global__ void __cluster_dims__(2, 1, 1) __launch_bounds__(NTHR, 1)
fnet_moe_kernel(const __grid_constant__ Params p) {
  const uint32_t t_entry = clk32();
  uint32_t smid;
  asm("mov.u32 %0, %%smid;" : "=r"(smid));
  const int tpc = smid >> 1, m = blockIdx.x & 1;
  if (MAP == 1 ? tpc >= 64 : (tpc >> 1) == 30) {
    if (threadIdx.x < 256) helper_cta(p, (tpc & 1) * 2 + m, t_entry);
    return;
  }
  const uint32_t sb = smem_u32(smem_raw);
  const int tid = threadIdx.x, warp = __shfl_sync(0xffffffffu, tid >> 5, 0), lane = tid & 31;
  const int e7 = ((tpc - 32) * 37) >> 8;
  const int tau = MAP == 1 || tpc < 32 ? (tpc & 7) : (tpc < 60 ? tpc - 31 - 7 * e7 : 0);
  const int eps = MAP == 1 || tpc < 32 ? (tpc >> 3) : (tpc < 60 ? 4 + e7 : tpc - 58);
  const int cid = tau * 16 + eps * 2 + m;
  const int grp = tau * 2 + m;
  auto BAR = [&](int i) { return sb + OFF_BAR + 8 * i; };
  const CUtensorMap* tmD = m ? &p.tmD1 : &p.tmD0;
#define LOAD_STREAM(d, tm, bar, c0, c1) tma_load_2d_hint(d, tm, bar, c0, c1, pol_ef)
#define LOAD_W tma_load_2d
#define LOAD_D tma_load_2d
#define LOAD_X tma_load_2d
#define LOAD_F LOAD_STREAM

  uint32_t tag = 0;
  uint4 wq = make_uint4(0, 0, 0, 0);
  if (warp >= 8) { tag = ld_relaxed32(&p.sc->epoch) + 1; wq = ldg128(p.wr + (tid & 127) * 8); }
  if (warp == 4) {
    if (elect_one()) {
      const uint64_t pol_ef = policy_evict_first();
#pragma unroll
      for (int k = 0; k < 4; k++) mbar_init(BAR(B_FULL + k), 1);
      asm volatile("fence.mbarrier_init.release.cluster;" ::: "memory");
#pragma unroll
      for (int k = 0; k < 4; k++) {
        mbar_expect_tx(BAR(B_FULL + k), ST_BYTES);
        tma_load_2d(sb + k * ST_BYTES + A_BYTES, &p.tmX, BAR(B_FULL + k), k * 64, tau * 256);
        LOAD_D(sb + k * ST_BYTES, tmD, BAR(B_FULL + k), k * 64, eps * 128);
        TIM(k);
      }
    }
  } else if (warp == 9) {
    if (elect_one()) {
#pragma unroll
      for (int s = 0; s < 4; s++) mbar_init(BAR(B_EMPTY + s), 1);
#pragma unroll
      for (int s = 0; s < 8; s++) { mbar_init(BAR(B_EP + s), 4); mbar_init(BAR(B_AW + s), 1); }
      mbar_init(BAR(B_STAT), 4); mbar_init(BAR(B_WC), 1); mbar_init(BAR(B_CD), 2);
      mbar_init(BAR(B_ALL), 1); mbar_init(BAR(B_INFO), 1); mbar_init(BAR(B_PEER), 1);
      mbar_init(BAR(B_XCH), 1); mbar_init(BAR(B_XCH + 1), 1); mbar_init(BAR(B_GUX), 1);
      asm volatile("fence.mbarrier_init.release.cluster;" ::: "memory");
      mbar_expect_tx(BAR(B_XCH), 16384); mbar_expect_tx(BAR(B_XCH + 1), 16384); mbar_expect_tx(BAR(B_GUX), 256);
    }
  }
  __syncthreads();
  asm volatile("barrier.cluster.arrive.relaxed.aligned;" ::: "memory");
  cluster_wait();
  const int abrow = m * 1024 + eps * 128;
  const bool ffn = eps > 0;
  const int fc = (tau * 7 + eps - 1) * 64, src = (fc >> 5) + m;

  if (warp >= 8) {
    reg_dec<72>();
    const int a = warp - 8;
    int lane, j;
    auto fresh_ids = [&]() { uint32_t l; asm volatile("mov.u32 %0, %%laneid;" : "=r"(l)); lane = l; j = a * 32 + l; };
    fresh_ids();
    const uint32_t buf = sb + OFF_AUX + a * 8192, bar0 = BAR(B_AW + 2 * a);
    if (a == 0 && lane < 16) pkt_clear128(&p.sc->xz[cid * 16 + lane]);
    if (lane < 2) pkt_clear128(&p.sc->dsum[cid * 16 + a * 4 + lane * 2]);
    if (a == 3 && lane < 24) pkt_clear128(lane < 16 ? &p.sc->abflag[cid * 64 + lane * 4] : &p.sc->abdone[cid * 32 + (lane - 16) * 4]);
    {
      const float s = warp_sum(((bf_lo(wq.x) + bf_hi(wq.x)) + (bf_lo(wq.y) + bf_hi(wq.y))) + ((bf_lo(wq.z) + bf_hi(wq.z)) + (bf_lo(wq.w) + bf_hi(wq.w))));
      if ((j >> 4) == eps) SM<uint4>(OFF_WR + (j & 15) * 16) = wq;
      if (lane == 0) { SM<float>(INFO_DS + a * 4) = s; SM<uint32_t>(INFO_ONES + a * 4) = 0x3F803F80u; }
    }
    const uint32_t c0 = code_of(tag), c1 = c0 >> 1;
    const bf16* xrows = p.x + (cid * 16 + a * 4) * 1024;
    const bf16* drows = (cid < 64 ? p.Dre : p.Dim) + ((cid & 63) * 16 + a * 4) * 1024;
    if (XROW_PF) {
      wait_clk(t_entry, XROW_PF);
      prefetch_l2(xrows + lane * 64); prefetch_l2(xrows + 2048 + lane * 64);
    }
    fresh_ids();
    {
      wait_clk(t_entry, U_CLK);
      uint4 u[8]; uint32_t n = 0;
#pragma unroll 1
      while (true) {
        uint32_t bad = 0;
#pragma unroll
        for (int q = 0; q < 8; q++) u[q] = pkt_ld128(&p.sc->u[a * 512 + ((q >> 1) * 32 + lane) * 4 + (q & 1) * 2]);
        if (n == 0 && lane < 2) { mbar_expect_tx(bar0 + lane * 8, 4096); bulk_load(buf + lane * 4096, xrows + lane * 2048, 4096, bar0 + lane * 8); }
#pragma unroll
        for (int q = 0; q < 8; q++) chk_code(bad, u[q], c0, c1);
        if (!__any_sync(0xffffffffu, bad & 1) || ++n > SPIN_LIMIT) break;
        __nanosleep(200);
      }
      if (j == 0) TIM(96);
      if (DROW_PF) { prefetch_l2(drows + lane * 64); prefetch_l2(drows + 2048 + lane * 64); }
#pragma unroll 1
      for (int r2 = 0; r2 < 2; r2++) {
        float v8[8];
        mbar_wait(bar0 + r2 * 8, 0);
        if (lane == 0) TIM(140 + r2 * 4 + a);
#pragma unroll
        for (int r = 0; r < 2; r++) {
          float s0 = 0.f, s1 = 0.f, q0 = 0.f, q1 = 0.f;
          uint32_t zr = 0, zi = 0;
#pragma unroll
          for (int q = 0; q < 4; q++) {
            const uint4 v = lds128(buf + r2 * 4096 + r * 2048 + (q * 32 + lane) * 16);
            const uint32_t ww[4] = {v.x, v.y, v.z, v.w};
#pragma unroll
            for (int z = 0; z < 4; z++) {
              const float lo = bf_lo(ww[z]), hi = bf_hi(ww[z]);
              s0 += lo; s1 += hi; q0 = fmaf(lo, lo, q0); q1 = fmaf(hi, hi, q1);
            }
            zr = bfma2(v.x, u[2 * q].x, zr); zi = bfma2(v.x, u[2 * q].y, zi); zr = bfma2(v.y, u[2 * q].z, zr); zi = bfma2(v.y, u[2 * q].w, zi);
            zr = bfma2(v.z, u[2 * q + 1].x, zr); zi = bfma2(v.z, u[2 * q + 1].y, zi); zr = bfma2(v.w, u[2 * q + 1].z, zr); zi = bfma2(v.w, u[2 * q + 1].w, zi);
          }
          v8[4 * r] = s0 + s1; v8[4 * r + 1] = q0 + q1; v8[4 * r + 2] = bf_lo(zr) + bf_hi(zr); v8[4 * r + 3] = bf_lo(zi) + bf_hi(zi);
        }
        fold<8>(v8, 16, lane);
        if (lane == 0) { mbar_expect_tx(bar0 + r2 * 8, 4096); bulk_load(buf + r2 * 4096, drows + r2 * 2048, 4096, bar0 + r2 * 8); }
        fold<4>(v8, 8, lane); fold<2>(v8, 4, lane);
        v8[0] += __shfl_xor_sync(0xffffffffu, v8[0], 2);
        v8[0] += __shfl_xor_sync(0xffffffffu, v8[0], 1);
        SM<float>(OFF_REM + a * 64 + r2 * 32 + (lane >> 2) * 4) = v8[0];
        if (lane == 0) TIM(148 + r2 * 4 + a);
      }
    }
    bar_sync(NB_AUX, 128);
    fresh_ids();
    if (a == 0 && lane < 16) {
      const float4 v = SM<float4>(OFF_REM + lane * 16);
      const float mean = v.x * (1.f / 1024.f), rs = fast_rcp(ref_sd(fmaxf(v.y * (1.f / 1024.f) - mean * mean, 0.f)));
      pkt_st128(&p.sc->xz[cid * 16 + lane], __float_as_uint(bf16r(mean)) | (tag & 0xFFFFu), __float_as_uint(rs), pack_bf16(v.z * rs, v.w * rs), tag);
    }
    if (j == 32) { const float4 v = SM<float4>(INFO_DS); SM<float2>(INFO_WSUM) = make_float2((v.x + v.y) + (v.z + v.w), __uint_as_float(tag)); }
    if (j == 0) TIM(98);
#pragma unroll 1
    for (int r2 = 0; r2 < 2; r2++) {
      mbar_wait(bar0 + r2 * 8, 1);
      uint4 dv[8];
#pragma unroll
      for (int q = 0; q < 8; q++) dv[q] = lds128(buf + r2 * 4096 + (lane >> 4) * 2048 + q * 256 + (lane & 15) * 16);
      float s0 = __uint_as_float(zero_here()), s1 = 0.f;
#pragma unroll
      for (int q = 0; q < 8; q++) {
        const uint4 v = dv[q];
        s0 += (bf_lo(v.x) + bf_lo(v.y)) + (bf_lo(v.z) + bf_lo(v.w)); s1 += (bf_hi(v.x) + bf_hi(v.y)) + (bf_hi(v.z) + bf_hi(v.w));
      }
      s0 += s1;
#pragma unroll
      for (int o = 8; o > 0; o >>= 1) s0 += __shfl_xor_sync(0xffffffffu, s0, o);
      SM<float>(INFO_DS2 + (a * 4 + r2 * 2 + (lane >> 4)) * 4) = s0;
    }
    bar_sync(NB_AUX, 128);
    if (a == 1 && lane < 16) pkt_st64(&p.sc->dsum[cid * 16 + lane], SM<uint32_t>(INFO_DS2 + lane * 4), tag);
    if (j == 0) TIM(99);
    uint4* cpart = &p.sc->cpart[grp * 512 + eps * 64];
    pkt_clear128(cpart + (j >> 5) * 8192 + lane); pkt_clear128(cpart + (j >> 5) * 8192 + 32 + lane);
    if (a == 3) pkt_st64(&p.sc->ch[((lane >> 3) * 128 + cid) * 16 + (lane & 7)], 0, 0);
    {
      wait_clk(clk32(), XS_DELAY);
      uint2 v0, v1, cs; uint32_t n = 0;
      const uint32_t t16 = tag & 0xFFFFu;
#pragma unroll 1
      while (true) {
        v0 = pkt_ld64(&p.sc->xz[tau * 256 + j]); v1 = pkt_ld64(&p.sc->xz[tau * 256 + 128 + j]); cs = pkt_ld64(&p.sc->dsum[m * 1024 + eps * 128 + j]);
        if (__all_sync(0xffffffffu, (v0.x & 0xFFFFu) == t16 && (v1.x & 0xFFFFu) == t16 && cs.y == tag) || ++n > SPIN_LIMIT) break;
        __nanosleep(200);
      }
      const int ro = OFF_RS + ((j & 7) >> 1) * 272 + (j >> 3) * 8 + (j & 1) * 4;
      SM<uint32_t>(ro) = v0.y ^ (m << 31); SM<uint32_t>(ro + 128) = v1.y ^ (m << 31);
      const uint32_t n0 = (v0.x >> 16) ^ 0x8000u, n1 = (v1.x >> 16) ^ 0x8000u;
      SM<uint4>(OFF_EXB + j * 16) = make_uint4(n0 | (n0 << 16), n0, 0, 0);
      SM<uint4>(OFF_EXB + 2048 + j * 16) = make_uint4(n1 | (n1 << 16), n1, 0, 0);
      const float c = 0.5f * __uint_as_float(cs.x), hi = bf16r(c), mid = bf16r(c - hi), lo = bf16r((c - hi) - mid);
      SM<uint4>(OFF_EXA + j * 16) = make_uint4((__float_as_uint(hi) >> 16) | __float_as_uint(mid), __float_as_uint(lo) >> 16, 0, 0);
      fence_async_smem();
      __syncwarp();
      if (lane == 0) mbar_arrive(BAR(B_STAT));
    }
    if (j == 0) TIM(100);
    {
      if (a == 3) {
        const uint32_t cl = poll64_warp(&p.sc->cl[cid * 16 + (lane & 3)], tag, 100);
        if (lane == 0) TIM(101);
        const bf16* wm = (m ? p.Wim : p.Wre) + tau * 256 + lane * 8;
        uint4 v[8];
#pragma unroll
        for (int i = 0; i < 8; i++) v[i] = ldg128(wm + ((__shfl_sync(0xffffffffu, cl, i >> 1) >> ((i & 1) * 16)) & 2047) * 2048);
        const int pos = cid * 4 + (lane & 3);
        const bf16* xc = p.x + ((__shfl_sync(0xffffffffu, cl, lane >> 3) >> ((lane & 4) * 4)) & 2047) * 1024 + (pos >> 3) * 16 + (pos & 7);
        const float x0 = ldbf(xc), x1 = ldbf(xc + 8);
        if (lane < 4) SM<uint32_t>(INFO_CAND + lane * 4) = cl;
#pragma unroll
        for (int i = 0; i < 8; i++) SM<uint4>(OFF_WC + (lane >> 3) * 1024 + i * 128 + (((lane & 7) ^ i) << 4)) = v[i];
        fence_async_smem();
        __syncwarp();
        if (lane == 0) { mbar_arrive(BAR(B_WC)); TIM(102); }
        mbar_wait(BAR(B_CD), 0);
        wait_clk(clk32(), CP_DELAY);
        uint32_t n = 0;
#pragma unroll 1
        while (true) {
          uint32_t bad = 0;
#pragma unroll
          for (int i = 0; i < 8; i++) v[i] = pkt_ld128(&p.sc->cpart[((lane >> 3) * 16 + 2 * i + ((lane >> 2) & 1)) * 512 + pos]);
#pragma unroll
          for (int i = 0; i < 8; i++) chk_code(bad, v[i], c0, c1);
          if (!__any_sync(0xffffffffu, bad & 1) || ++n > SPIN_LIMIT) break;
          __nanosleep(200);
        }
        float y[4] = {0.f, 0.f, 0.f, 0.f};
#pragma unroll
        for (int i = 0; i < 8; i++) { y[0] += __uint_as_float(v[i].x); y[2] += __uint_as_float(v[i].y); y[1] += __uint_as_float(v[i].z); y[3] += __uint_as_float(v[i].w); }
#pragma unroll
        for (int i = 0; i < 4; i++) y[i] = bf16r(y[i]);
        __syncwarp();
        fold<4>(y, 4, lane);
        pkt_st64(&p.sc->ch[((lane >> 3) * 128 + cid) * 16 + (lane & 7)], pack_bf16(x0 + bf16r(y[0]), x1 + bf16r(y[1])), tag);
        if (lane == 0) TIM(119);
      }
      if (a < 2) {
        if (elect_one()) {
#pragma unroll 1
          for (int i = 0; i < 4; i++) {
            const int w = i >> 1, c = 2 * a + ((i ^ a) & 1);
            mbar_wait(BAR(B_EP + w * 4 + c), 0);
            TIM(64 + a * 8 + i);
            fence_async_smem();
            tma_store_2d(&p.tmAbS, sb + c * ST_BYTES + w * 8192, tau * 256 + c * 64, abrow + w * 64);
          }
          bulk_commit();
          bulk_wait_all();
          TIM(68 + a * 8);
          asm volatile("fence.proxy.async.global;" ::: "memory");
          asm volatile("fence.acq_rel.gpu;" ::: "memory");
          TIM(69 + a * 8);
        }
        __syncwarp();
        if (lane < 9) st_relaxed32(lane == 8 ? &p.sc->abflag[(cid * 2 + a) * 32] : &p.sc->abdone[((cid & 15) + lane * 16) * 32 + tau * 2 + a], tag);
        if (elect_one()) {
          uint32_t n = 0;
#pragma unroll 1
          while (ld_acquire32(&p.sc->abflag[(((cid + 16) & 127) * 2 + a) * 32]) != tag && ++n < SPIN_LIMIT) {}
          asm volatile("fence.proxy.async.global;" ::: "memory");
#pragma unroll 1
          for (int c = 2 * a; c < 2 * a + 2; c++) {
            mbar_wait(BAR(c < 3 ? B_FULL + c : B_EMPTY + 3), 0);
            tma_load_2d(sb + c * ST_BYTES, &p.tmAbL, BAR(B_FULL + c), SIGMA(tau, 1) * 256 + c * 64, abrow);
            TIM(130 + c);
          }
        }
        __syncwarp();
      } else if (a == 2) {
        uint32_t done = 0, n = 0;
        mbar_wait(BAR(B_EMPTY + POLL_E), 0);
#pragma unroll 1
        for (int c = 0; c < 5; c++) {
          const uint32_t need = c < 4 ? 3u << (2 * SIGMA(tau, 2)) : 0xFFFFu;
#pragma unroll 1
          while ((done & need) != need && ++n < SPIN_LIMIT) done = __ballot_sync(0xffffffffu, ld_acquire32(&p.sc->abdone[cid * 32 + (lane & 15)]) == tag);
          if (elect_one()) {
            TIM(80 + c);
            asm volatile("fence.proxy.async.global;" ::: "memory");
            if (c < 4) {
              mbar_wait(BAR(B_EMPTY + c), 1);
              tma_load_2d(sb + c * ST_BYTES, &p.tmAbL, BAR(B_FULL + c), SIGMA(tau, 2) * 256 + c * 64, abrow);
            } else mbar_arrive(BAR(B_ALL));
          }
          __syncwarp();
        }
      }
    }
    if (ffn) { pkt_clear128(&p.sc->ypart[(a * NSRC + src) * 64 + lane * 2]); pkt_clear128(&p.sc->ypart[(a * NSRC + src) * 64 + lane * 2 + 1]); }
    mbar_wait(BAR(B_CD), 0);
    const uint64_t pol_ef = policy_evict_first();
    auto load_unit = [&](int v) {
      if (elect_one()) {
        const uint32_t dst = buf + (v & 1) * 4096, bar = bar0 + (v & 1) * 8;
        mbar_expect_tx(bar, 4096);
        if (v < 8) {
          LOAD_F(dst, &p.tmG, bar, fc, m * 512 + (a * 8 + v) * 16);
          LOAD_F(dst + 2048, &p.tmU, bar, fc, m * 512 + (a * 8 + v) * 16);
        } else LOAD_F(dst, &p.tmDn, bar, a * 256, src * 32 + (v - 8) * 8);
      }
    };
    wait_clk(t_entry, SEL_CLK);
    if (ffn) { load_unit(0); load_unit(1); }
    {
      if (a == 3) {
        const uint32_t kk = poll64_warp(&p.sc->selkey[((lane & 3) * 128 + cid) * 16], tag, 100), key = __reduce_max_sync(0xffffffffu, kk);
        const int win = __ffs(__ballot_sync(0xffffffffu, kk == key)) - 1;
        if (lane == 0) SM<uint2>(INFO_KEY) = make_uint2(key, win);
      }
      bar_sync(NB_AUX, 128);
      const uint2* sel = &p.sc->sel[SM<uint32_t>(INFO_KEY + 4) * 1024];
      uint4 v; uint32_t n = 0;
#pragma unroll 1
      while (true) {
        v = pkt_ld128(sel + m * 256 + 2 * j);
        if (__all_sync(0xffffffffu, v.y == tag && v.w == tag) || ++n > SPIN_LIMIT) break;
        __nanosleep(100);
      }
      const int d = (j >> 2) * 16 + (j & 3) * 2;
      SM<float2>(OFF_XS + d * 4) = make_float2(bf_lo(v.x), bf_lo(v.z));
      SM<float2>(OFF_XS + (d + 8) * 4) = make_float2(bf_hi(v.x), bf_hi(v.z));
    }
    pkt_clear128(&p.sc->hstat[(grp * 8 + eps) * 128 + j]);
    bar_sync(NB_AUX, 128);
    if (j == 0) {
      mbar_arrive(BAR(B_INFO)); TIM(103);
      if (cid == 0) st_relaxed32(&p.sc->epoch, tag);
    }
    const uint32_t t2 = clk32();
    fresh_ids();
    if (!ffn) {
      wait_clk(t2, YPART_DELAY);
    } else {
      const int r = lane >> 3;
      float acc[16];
#pragma unroll
      for (int i = 0; i < 16; i++) acc[i] = 0.f;
#pragma unroll 1
      for (int v = 0; v < 8; v++) {
        mbar_wait(bar0 + (v & 1) * 8, (v >> 1) & 1);
        const float4 xv = SM<float4>(OFF_XS + ((a * 8 + v) * 16 + r * 4) * 4);
        const uint32_t wa = buf + (v & 1) * 4096 + r * 512 + (lane & 7) * 16;
        uint4 wv[8];
#pragma unroll
        for (int i = 0; i < 8; i++) wv[i] = lds128(wa + (i >> 2) * 2048 + (i & 3) * 128);
        acc[0] += __uint_as_float(zero_here());
        fma8(acc, wv[0], xv.x); fma8(acc, wv[1], xv.y); fma8(acc, wv[2], xv.z); fma8(acc, wv[3], xv.w);
        fma8(acc + 8, wv[4], xv.x); fma8(acc + 8, wv[5], xv.y); fma8(acc + 8, wv[6], xv.z); fma8(acc + 8, wv[7], xv.w);
        fence_regs(acc);
        __syncwarp();
        wait_clk(t2, v * UNIT_PACE);
        load_unit(v + 2);
        if (j == 0) TIM(104 + v);
      }
      fold<16>(acc, 16, lane); fold<8>(acc, 8, lane);
      bar_sync(NB_AUX, 128);
      SM<float4>(OFF_XS + (a * 128 + (r >> 1) * 64 + (lane & 7) * 8 + (r & 1) * 4) * 4) = make_float4(acc[0], acc[1], acc[2], acc[3]);
      bar_sync(NB_AUX, 128);
      auto psum = [&](int i) { return (SM<float>(OFF_XS + i * 4) + SM<float>(OFF_XS + (128 + i) * 4)) + (SM<float>(OFF_XS + (256 + i) * 4) + SM<float>(OFF_XS + (384 + i) * 4)); };
      if (a < 2) st_async_b32(mapa(sb + OFF_REM + j * 4, m ^ 1), mapa(BAR(B_GUX), m ^ 1), __float_as_uint(psum(a * 64 + (m ^ 1) * 32 + lane)));
      const float og = psum(m * 32 + lane), ou = psum(64 + m * 32 + lane);
      mbar_wait(BAR(B_GUX), 0);
      const float rg = SM<float>(OFF_REM + lane * 4), ru = SM<float>(OFF_REM + 128 + lane * 4);
      const float act = swiglu(m ? rg + og : og + rg, m ? ru + ou : ou + ru);
      if (j == 0) TIM(112);
      float y[8] = {0.f, 0.f, 0.f, 0.f, 0.f, 0.f, 0.f, 0.f};
#pragma unroll 1
      for (int v = 8; v < 12; v++) {
        mbar_wait(bar0 + (v & 1) * 8, (v >> 1) & 1);
        uint4 wv[8];
#pragma unroll
        for (int i = 0; i < 8; i++) wv[i] = lds128(buf + (v & 1) * 4096 + i * 512 + lane * 16);
        y[0] += __uint_as_float(zero_here());
#pragma unroll
        for (int i = 0; i < 8; i++) fma8(y, wv[i], __shfl_sync(0xffffffffu, act, (v - 8) * 8 + i));
        fence_regs(y);
        __syncwarp();
        if (v < 10) load_unit(v + 2);
        if (j == 0) TIM(105 + v);
      }
      fresh_ids();
      uint4* ypart = &p.sc->ypart[(a * NSRC + src) * 64 + lane * 2];
      pkt_st128(ypart, with_bit(y[0], c0), with_bit(y[1], c1), with_bit(y[2], c0), with_bit(y[3], c1));
      pkt_st128(ypart + 1, with_bit(y[4], c0), with_bit(y[5], c1), with_bit(y[6], c0), with_bit(y[7], c1));
      __nanosleep(400);
    }
    {
      float y[8] = {0.f, 0.f, 0.f, 0.f, 0.f, 0.f, 0.f, 0.f};
      uint32_t hh = 0;
      if (j >= NSRC) hh = poll64(&p.sc->sel[SM<uint32_t>(INFO_KEY + 4) * 1024 + (j & 8) * 64 + (cid >> 1) * 8 + (j & 7)], tag, 100);
      if (j < NSRC) {
        const uint4* yp = &p.sc->ypart[((cid >> 5) * NSRC + j) * 64 + (cid & 31) * 2];
        uint4 va, vb; uint32_t n = 0;
#pragma unroll 1
        while (true) {
          uint32_t bad = 0;
          va = pkt_ld128(yp); vb = pkt_ld128(yp + 1);
          chk_code(bad, va, c0, c1); chk_code(bad, vb, c0, c1);
          if (!(bad & 1) || ++n > SPIN_LIMIT) break;
          __nanosleep(300);
        }
        y[0] = __uint_as_float(va.x); y[1] = __uint_as_float(va.y); y[2] = __uint_as_float(va.z); y[3] = __uint_as_float(va.w);
        y[4] = __uint_as_float(vb.x); y[5] = __uint_as_float(vb.y); y[6] = __uint_as_float(vb.z); y[7] = __uint_as_float(vb.w);
      }
      __syncwarp();
      fold<8>(y, 16, lane); fold<4>(y, 8, lane); fold<2>(y, 4, lane);
      y[0] += __shfl_xor_sync(0xffffffffu, y[0], 2);
      y[0] += __shfl_xor_sync(0xffffffffu, y[0], 1);
      SM<float>(OFF_AUX + a * 8192 + (lane >> 2) * 4) = y[0];
      const float hn = m ? bf_hi(hh) : bf_lo(hh), h = __shfl_down_sync(0xffffffffu, hn, 8);
      bar_sync(NB_AUX, 128);
      if ((j >> 3) == 14) {
        const uint32_t key = SM<uint32_t>(INFO_KEY);
        const int o = OFF_AUX + (j & 7) * 4;
        const float ys = (SM<float>(o) + SM<float>(o + 8192)) + (SM<float>(o + 16384) + SM<float>(o + 24576));
        st_bf16(p.out + key_row(key) * 1024 + cid * 8 + (j & 7), routed_out(h, hn, ys, key_val(key)));
        if (j == 112) TIM(118);
        __threadfence();
        __syncwarp(0xFF0000);
        if (j == 112) pkt_st64(&p.sc->rdone[cid], 0, tag);
      }
    }
  } else {
    reg_inc<216>();
    const int w = warp >> 2, wi = warp & 3, t = tid & 127;
    const int turn_me = NB_TURN0 + w, turn_other = NB_TURN1 - w;
    uint64_t dA, dB;
    auto new_desc = [&]() { const uint32_t z = sb + uniform_zero_here(); dA = make_desc(z + w * 8192); dB = make_desc(z + A_BYTES); };
    constexpr int SL = ST_BYTES >> 4;
    float acc[128];
#pragma unroll
    for (int i = 0; i < 128; i++) acc[i] = 0.f;
    if (w == 1) bar_arrive(NB_TURN0, 256);
    auto full = [&](int k) { mbar_wait(BAR(B_FULL + (k & 3)), (k >> 2) & 1); CT(64 + k); };
    const uint64_t pol_ef = policy_evict_first();
    const CUtensorMap* tmW = m ? &p.tmW1 : &p.tmW0;
    auto refill_g1 = [&](int k) {
      if (warp == 4) {
        if (elect_one()) {
          const int s = k & 3;
          TIM(k + 4);
          mbar_expect_tx(BAR(B_FULL + s), ST_BYTES);
          LOAD_X(sb + s * ST_BYTES + A_BYTES, &p.tmX, BAR(B_FULL + s), (k + 4) * 64, tau * 256);
          LOAD_D(sb + s * ST_BYTES, tmD, BAR(B_FULL + s), (k + 4) * 64, eps * 128);
        }
        __syncwarp();
      }
    };
    auto refill_g2 = [&](int k, int mode) {
      if (warp == 4) {
        if (elect_one()) {
          const int s = k & 3, s0 = (tau * 256 + (k - 12) * 64) & 2047;
          TIM(k + 4);
          mbar_expect_tx(BAR(B_FULL + s), mode ? ST_BYTES : B_BYTES);
          if (mode == 1) mbar_arrive(BAR(B_EMPTY + s));
          LOAD_W(sb + s * ST_BYTES + A_BYTES, tmW, BAR(B_FULL + s), s0, grp * 128);
          LOAD_W(sb + s * ST_BYTES + A_BYTES + 16384, tmW, BAR(B_FULL + s), s0, (grp ^ 1) * 128);
          if (mode == 2) tma_load_2d(sb + s * ST_BYTES, &p.tmAbL, BAR(B_FULL + s), s0, abrow);
        }
        __syncwarp();
      }
    };
    auto mma_ss = [&](int k) {
#pragma unroll
      for (int kk = 0; kk < 4; kk++) wgmma_n256(acc, dA + (k & 3) * SL + kk * 2, dB + (k & 3) * SL + kk * 2);
    };
    auto prefetch_ffn = [&](int k) {
      const int v = (k < 16 ? k - PF1_K : k - PF2_K + 14 - PF1_K) >> 1;
      if (k >= PF1_K && (k < 16 || k >= PF2_K) && v < 12 && (warp >> 1) == (k & 1)) {
        if (PFMODE == 0 && v < 8) { if (ffn) prefetch_l2(((lane & 16) ? p.wup : p.wgate) + (m * 512 + (wi * 8 + v) * 16 + (lane & 15)) * 3584 + fc); }
        else if (v < 8) { if (t < 112) prefetch_l2((t < 56 ? p.wgate + t * 64 : p.wup + (t - 56) * 64) + (tau * 128 + v * 16 + (cid & 15)) * 3584); }
        else if (ffn) prefetch_l2(p.wdown + (src * 32 + (v - 8) * 8) * 1024 + t * 64);
      }
    };
    auto kstep = [&](int k) {
      full(k);
      bar_sync(turn_me, 256);
      wgmma_fence();
      mma_ss(k);
      wgmma_commit();
      bar_arrive(turn_other, 256);
    };

#pragma unroll 1
    for (int k4 = 0; k4 < 12; k4 += 4) {
      new_desc();
#pragma unroll
      for (int s = 0; s < 4; s++) { kstep(k4 | s); prefetch_ffn(k4 | s); wgmma_wait<0>(); refill_g1(k4 | s); }
    }
    uint32_t R[64];
    auto load_rs = [&](auto gi) {
      const uint32_t rsa = sb + OFF_RS + (lane & 3) * 272;
#pragma unroll
      for (int i = 4 * decltype(gi)::value; i < 4 * decltype(gi)::value + 4; i++) { const uint4 v = lds128(rsa + i * 16); R[4 * i] = v.x; R[4 * i + 1] = v.y; R[4 * i + 2] = v.z; R[4 * i + 3] = v.w; }
    };
    new_desc();
    kstep(12);
    prefetch_ffn(12);
    mbar_wait(BAR(B_STAT), 0);
    CT(1);
    load_rs(std::integral_constant<int, 0>());
    wgmma_wait<0>(); refill_g2(12, 0);
    load_rs(std::integral_constant<int, 1>());
    auto mma_h = [&](float (&d)[64], int s, int half) {
#pragma unroll
      for (int kk = 0; kk < 4; kk++) wgmma_n128(d, dA + s * SL + kk * 2, dB + s * SL + half * 1024 + kk * 2);
    };
    const int rho = 16 * wi + (lane & 15);
    const uint32_t arow = sb + w * 8192 + rho * 128;
    auto convert = [&](auto cc, float (&d)[64]) {
      const float z = __uint_as_float(zero_here());
#pragma unroll
      for (int jj = 8 * decltype(cc)::value; jj < 8 * decltype(cc)::value + 8; jj++) {
        const float r0 = __uint_as_float(R[2 * jj]), r1 = __uint_as_float(R[2 * jj + 1]);
        const float* ac = &d[4 * (jj & 15)];
        R[2 * jj] = pack_bf16(fmaf(ac[0], r0, z), fmaf(ac[1], r1, z));
        R[2 * jj + 1] = pack_bf16(fmaf(ac[2], r0, z), fmaf(ac[3], r1, z));
      }
    };
    auto put = [&](auto cc) {
      constexpr int c = decltype(cc)::value;
#pragma unroll
      for (int jj = 8 * c; jj < 8 * c + 8; jj += 2)
        stsm_x4(arow + c * ST_BYTES + ((((jj & 7) + (lane >> 4)) ^ (rho & 7)) << 4), R[2 * jj], R[2 * jj + 1], R[2 * jj + 2], R[2 * jj + 3]);
      __syncwarp();
      if (lane == 0) mbar_arrive(BAR(B_EP + w * 4 + c));
    };
    {
      float lo[64], hi[64];
      fence_regs(acc);
#pragma unroll
      for (int i = 0; i < 64; i++) asm volatile("mov.b32 %0, %1;" : "=f"(lo[i]) : "f"(acc[i]));
#pragma unroll
      for (int i = 0; i < 64; i++) asm volatile("mov.b32 %0, %1;" : "=f"(hi[i]) : "f"(acc[64 + i]));
      const uint64_t dEA = make_desc_noswz(sb + OFF_EXA + w * 1024), dEB = make_desc_noswz(sb + OFF_EXB);
      full(13); full(14);
      bar_sync(turn_me, 256);
      wgmma_fence();
      mma_h(lo, 1, 0); mma_h(lo, 2, 0);
      wgmma_commit();
      bar_arrive(turn_other, 256);
      prefetch_ffn(13);
      load_rs(std::integral_constant<int, 3>());
      new_desc();
      full(15);
      bar_sync(turn_me, 256);
      wgmma_fence();
      mma_h(lo, 3, 0);
      wgmma_n128(lo, dEA, dEB);
      wgmma_commit();
      mma_h(hi, 1, 1);
      wgmma_commit();
      bar_arrive(turn_other, 256);
      wgmma_wait<1>();
      fence_regs(lo);
      CT(15);
      convert(std::integral_constant<int, 0>(), lo); put(std::integral_constant<int, 0>());
      load_rs(std::integral_constant<int, 2>());
      convert(std::integral_constant<int, 1>(), lo);
      wgmma_wait<0>(); refill_g2(13, 0);
      put(std::integral_constant<int, 1>());
      new_desc();
      bar_sync(turn_me, 256);
      wgmma_fence();
      mma_h(hi, 2, 1);
      wgmma_commit();
      mma_h(hi, 3, 1);
      wgmma_n128(hi, dEA, dEB + 128);
      wgmma_commit();
      bar_arrive(turn_other, 256);
      wgmma_wait<1>(); refill_g2(14, 0);
      wgmma_wait<0>(); refill_g2(15, 0);
      fence_regs(hi);
      CT(2);
      convert(std::integral_constant<int, 3>(), hi); put(std::integral_constant<int, 3>());
      convert(std::integral_constant<int, 2>(), hi);
    }
    CT(3);
    new_desc();
    full(16); full(17);
    bar_sync(turn_me, 256);
    wgmma_fence();
    wgmma_n256_rs_init(acc, R, dB);
#pragma unroll
    for (int kk = 1; kk < 4; kk++) wgmma_n256_rs<1>(acc, R + 4 * kk, dB + kk * 2);
    wgmma_commit();
#pragma unroll
    for (int kk = 0; kk < 4; kk++) wgmma_n256_rs<1>(acc, R + 16 + 4 * kk, dB + SL + kk * 2);
    wgmma_commit();
    bar_arrive(turn_other, 256);
    put(std::integral_constant<int, 2>());
    wgmma_wait<1>(); refill_g2(16, 1);
    wgmma_wait<0>(); refill_g2(17, 1); fence_async_smem();
    {
      float cc[4];
      mbar_wait(BAR(B_WC), 0);
      CT(4);
      full(18);
      bar_sync(turn_me, 256);
      wgmma_fence();
      const uint64_t dC = make_desc(sb + OFF_WC);
      wgmma_n8_rs<0>(cc, R, dC);
#pragma unroll
      for (int i = 1; i < 12; i++) wgmma_n8_rs<1>(cc, R + 4 * i, dC + (i >> 2) * 64 + (i & 3) * 2);
#pragma unroll
      for (int kk = 0; kk < 4; kk++) wgmma_n8(cc, dA + 3 * SL + kk * 2, dC + 192 + kk * 2);
      wgmma_commit();
#pragma unroll
      for (int kk = 0; kk < 4; kk++) wgmma_n256_rs<1>(acc, R + 32 + 4 * kk, dB + 2 * SL + kk * 2);
      wgmma_commit();
      bar_arrive(turn_other, 256);
      const uint32_t cd = code_of(SM<uint32_t>(INFO_TAG));
      wgmma_wait<1>();
      fence_regs(cc);
      if (t == 0) mbar_arrive(BAR(B_CD));
      pkt_st128(&p.sc->cpart[((lane & 3) * 16 + grp) * 512 + eps * 64 + warp * 8 + (lane >> 2)], with_bit(cc[0], cd), with_bit(cc[1], cd >> 1), with_bit(cc[2], cd), with_bit(cc[3], cd >> 1));
      CT(5);
      wgmma_wait<0>(); refill_g2(18, 1);
    }
    kstep(19);
    wgmma_wait<0>(); refill_g2(19, 1);
#pragma unroll 1
    for (int k4 = 20; k4 < 44; k4 += 4) {
      new_desc();
#pragma unroll
      for (int s = 0; s < 4; s++) {
        kstep(k4 | s);
        prefetch_ffn(k4 | s);
        if (s == 1 && k4 == XPF_K) prefetch_l2(p.x + (grp * 128 + (tid >> 1)) * 1024 + eps * 128 + (tid & 1) * 64);
        if (s == 0 && k4 == 24 && warp == 4) mbar_wait(BAR(B_ALL), 0);
        wgmma_wait<0>();
        refill_g2(k4 | s, k4 == 20 ? 1 : 2);
      }
    }
    const int g = lane >> 2, q = lane & 3;
    const int row0 = grp * 128 + warp * 16 + g;
    uint4 ha[4], hb[4];
    new_desc();
    kstep(44);
#pragma unroll
    for (int i = 0; i < 4; i++) { ha[i] = ldg128(p.x + row0 * 1024 + eps * 128 + q * 8 + i * 32); hb[i] = ldg128(p.x + (row0 + 8) * 1024 + eps * 128 + q * 8 + i * 32); }
    wgmma_wait<0>();
    if (tid == 128) mbar_arrive_remote(mapa(BAR(B_PEER), m ^ 1));
    uint32_t hp[32];
    uint4 wv[4], info, cand;
    uint4* hst; bf16* op;
    {
      float as[64], ak[64];
      fence_regs(acc);
#pragma unroll
      for (int i = 0; i < 64; i++) asm volatile("mov.b32 %0, %1;" : "=f"(as[i]) : "f"(acc[64 + i]));
#pragma unroll
      for (int i = 0; i < 64; i++) asm volatile("mov.b32 %0, %1;" : "=f"(ak[i]) : "f"(acc[i]));
      full(45); full(46);
      bar_sync(turn_me, 256);
      wgmma_fence();
      mma_h(as, 1, 1); mma_h(as, 2, 1);
      wgmma_commit();
      bar_arrive(turn_other, 256);
      full(47);
      bar_sync(turn_me, 256);
      wgmma_fence();
      mma_h(as, 3, 1);
      wgmma_commit();
      mma_h(ak, 1, 0);
      wgmma_commit();
      bar_arrive(turn_other, 256);
      const uint32_t rx = mapa(sb + OFF_RECV + w * 16384 + t * 16, m ^ 1), rb = mapa(BAR(B_XCH + w), m ^ 1);
      mbar_wait(BAR(B_PEER), 0);
      wgmma_wait<1>();
      fence_regs(as);
      CT(6);
#pragma unroll
      for (int i = 0; i < 8; i++) {
        const float* ac = &as[8 * i];
        st_async_v4(rx + i * 2048, rb, pack_bf16(ac[0], ac[1]), pack_bf16(ac[2], ac[3]), pack_bf16(ac[4], ac[5]), pack_bf16(ac[6], ac[7]));
      }
      CT(7);
      bar_sync(turn_me, 256);
      wgmma_fence();
      mma_h(ak, 2, 0); mma_h(ak, 3, 0);
      wgmma_commit();
      if (w == 0) bar_arrive(turn_other, 256);
      mbar_wait(BAR(B_INFO), 0);
#pragma unroll
      for (int i = 0; i < 4; i++) wv[i] = lds128(sb + ((g & 1) ? OFF_WR + (i * 4 + q) * 16 : INFO_ONES));
      info = lds128(sb + OFF_INFO); cand = lds128(sb + INFO_CAND);
      hst = &p.sc->hstat[grp * 1024 + warp * 16 + g + zero_here()];
      op = p.out + row0 * 1024 + eps * 128 + q * 8;
      asm volatile("" : "+l"(hst), "+l"(op));
      mbar_wait(BAR(B_XCH + w), 0);
      CT(9);
#pragma unroll
      for (int i = 0; i < 8; i++) { const uint4 v = lds128(sb + OFF_RECV + w * 16384 + t * 16 + i * 2048); hp[4 * i] = v.x; hp[4 * i + 1] = v.y; hp[4 * i + 2] = v.z; hp[4 * i + 3] = v.w; }
      wgmma_wait<0>();
      fence_regs(ak);
      CT(10);
#pragma unroll
      for (int i = 0; i < 32; i++) hp[i] = badd2(pack_bf16(ak[2 * i], ak[2 * i + 1]), hp[i]);
    }
    auto swz = [](int row) { return ((row & 1) << 2) | ((row >> 1) & 3); };
#pragma unroll
    for (int jj = 0; jj < 16; jj += 2) {
      const int tr = 8 * (jj + (lane >> 4)) + (lane & 7), chunk = 2 * wi + ((lane >> 3) & 1);
      stsm_x4_t(sb + w * ST_BYTES + tr * 128 + ((chunk ^ swz(tr)) << 4), hp[2 * jj], hp[2 * jj + 1], hp[2 * jj + 2], hp[2 * jj + 3]);
    }
    tag = info.y;
    const uint32_t cd = code_of(tag);
    bar_sync(NB_BOTH, 256);
    CT(11);
    uint4 v[4];
    auto fetch = [&]() { v[0] = pkt_ld128(hst + q * 256); v[1] = pkt_ld128(hst + q * 256 + 128); v[2] = pkt_ld128(hst + q * 256 + 8); v[3] = pkt_ld128(hst + q * 256 + 136); };
    float st[6];
    {
      uint4 ya[4], yb[4];
#pragma unroll
      for (int i = 0; i < 4; i++) {
        const uint32_t ad = sb + (i >> 1) * ST_BYTES + (warp * 16 + g) * 128 + ((((i & 1) * 4 + q) ^ swz(g)) << 4);
        ya[i] = lds128(ad); yb[i] = lds128(ad + 1024);
      }
      fetch();
      const float z = __uint_as_float(zero_here());
      float sw[2][4], qa[2][4], qb[2][4];
#pragma unroll
      for (int i = 0; i < 8; i++) { sw[i >> 2][i & 3] = i ? 0.f : z; qa[i >> 2][i & 3] = 0.f; qb[i >> 2][i & 3] = 0.f; }
#pragma unroll
      for (int i = 0; i < 4; i++) {
        ha[i] = make_uint4(badd2(ha[i].x, ya[i].x), badd2(ha[i].y, ya[i].y), badd2(ha[i].z, ya[i].z), badd2(ha[i].w, ya[i].w));
        hb[i] = make_uint4(badd2(hb[i].x, yb[i].x), badd2(hb[i].y, yb[i].y), badd2(hb[i].z, yb[i].z), badd2(hb[i].w, yb[i].w));
        mma16816(sw[0], ha[i].x, hb[i].x, ha[i].y, hb[i].y, wv[i].x, wv[i].y);
        mma16816(qa[0], ha[i].x, hb[i].x, ha[i].y, hb[i].y, ha[i].x, ha[i].y);
        mma16816(qb[0], ha[i].x, hb[i].x, ha[i].y, hb[i].y, hb[i].x, hb[i].y);
        mma16816(sw[1], ha[i].z, hb[i].z, ha[i].w, hb[i].w, wv[i].z, wv[i].w);
        mma16816(qa[1], ha[i].z, hb[i].z, ha[i].w, hb[i].w, ha[i].z, ha[i].w);
        mma16816(qb[1], ha[i].z, hb[i].z, ha[i].w, hb[i].w, hb[i].z, hb[i].w);
      }
      const uint32_t s0 = with_bit(sw[0][0] + sw[1][0], cd), s1 = with_bit((g & 1) ? qa[0][1] + qa[1][1] : qa[0][0] + qa[1][0], cd >> 1), s2 = __float_as_uint(sw[0][1] + sw[1][1]);
      const uint32_t s3 = with_bit(sw[0][2] + sw[1][2], cd), s4 = with_bit((g & 1) ? qb[0][3] + qb[1][3] : qb[0][2] + qb[1][2], cd >> 1), s5 = __float_as_uint(sw[0][3] + sw[1][3]);
      if (q == (g >> 1)) { pkt_st128(hst + eps * 128, s0, s1, s2, tag); pkt_st128(hst + eps * 128 + 8, s3, s4, s5, tag); }
      CT(12);
      const uint32_t o1 = __shfl_sync(0xffffffffu, s1, (lane & 28) | (g >> 1)), o4 = __shfl_sync(0xffffffffu, s4, (lane & 28) | (g >> 1));
      uint32_t n = 0;
#pragma unroll 1
      while (true) {
        if (2 * q == eps) { v[0] = make_uint4(s0, o1, s2, tag); v[2] = make_uint4(s3, o4, s5, tag); }
        if (2 * q + 1 == eps) { v[1] = make_uint4(s0, o1, s2, tag); v[3] = make_uint4(s3, o4, s5, tag); }
        uint32_t bad = 0;
#pragma unroll
        for (int i = 0; i < 4; i++) { chk(bad, v[i].x, cd); chk(bad, v[i].y, cd >> 1); }
        bad &= 1;
#pragma unroll
        for (int i = 0; i < 4; i++) chk(bad, v[i].w, tag);
        if (!__any_sync(0xffffffffu, bad) || ++n > SPIN_LIMIT) break;
        if (bad) fetch();
      }
      st[0] = __uint_as_float(v[0].x) + __uint_as_float(v[1].x); st[1] = __uint_as_float(v[0].y) + __uint_as_float(v[1].y); st[2] = __uint_as_float(v[0].z) + __uint_as_float(v[1].z);
      st[3] = __uint_as_float(v[2].x) + __uint_as_float(v[3].x); st[4] = __uint_as_float(v[2].y) + __uint_as_float(v[3].y); st[5] = __uint_as_float(v[2].z) + __uint_as_float(v[3].z);
    }
    CT(13);
#pragma unroll
    for (int o = 1; o < 4; o <<= 1) {
#pragma unroll
      for (int i = 0; i < 6; i++) st[i] += __shfl_xor_sync(0xffffffffu, st[i], o);
    }
    float mb[2], inv[2];
#pragma unroll
    for (int i = 0; i < 2; i++) {
      const float mu = st[3 * i] * (1.f / 1024.f);
      mb[i] = bf16r(mu);
      inv[i] = fast_rcp(ref_sd(fmaxf(st[3 * i + 1] * (1.f / 1024.f) - mu * mu, 0.f)));
    }
    {
      const int srow = key_row(info.z);
      auto put_out = [&](bf16* dst, const uint4& h, float sc, float of, bool on) {
        auto cvt = [&](uint32_t x) { return pack_bf16(fmaf(bf_lo(x), sc, of), fmaf(bf_hi(x), sc, of)); };
        asm volatile("{\n.reg .pred p;\nsetp.ne.b32 p, %5, 0;\n@p st.global.v4.b32 [%0], {%1, %2, %3, %4};\n}\n"
                     :: "l"(dst), "r"(cvt(h.x)), "r"(cvt(h.y)), "r"(cvt(h.z)), "r"(cvt(h.w)), "r"((int)on) : "memory");
      };
#pragma unroll
      for (int i = 0; i < 4; i++) {
        put_out(op + i * 32, ha[i], 1.f + inv[0], -mb[0] * inv[0], row0 != srow);
        put_out(op + 8192 + i * 32, hb[i], 1.f + inv[1], -mb[1] * inv[1], row0 + 8 != srow);
      }
    }
    CT(14);
    uint32_t wkey = zero_here();
#pragma unroll
    for (int i = 0; i < 2; i++) {
      const uint32_t row = row0 + 8 * i, rr = row | (row << 16);
      const bool is_cand = __vcmpeq2(cand.x, rr) | __vcmpeq2(cand.y, rr) | __vcmpeq2(cand.z, rr) | __vcmpeq2(cand.w, rr);
      if (!is_cand) wkey = max(wkey, make_key(bf16r((st[3 * i + 2] - mb[i] * __uint_as_float(info.x)) * inv[i]), row));
    }
    wkey = __reduce_max_sync(0xffffffffu, wkey);
    if (eps == 0 && lane == 0) pkt_st64(&p.sc->key[grp * 8 + warp], wkey, tag);
    const bool beaten = (wkey >> 16) > (info.z >> 16);
    if (beaten) {
      const int br = key_row(wkey);
      if (br == row0 || br == row0 + 8) {
#pragma unroll
        for (int i = 0; i < 4; i++) {
          const uint4 h = br == row0 ? ha[i] : hb[i];
          uint2* dst = &p.sc->hrow[(grp * 8 + warp) * 512 + eps * 64 + i * 16 + q * 4];
          pkt_st128(dst, h.x, tag, h.y, tag); pkt_st128(dst + 2, h.z, tag, h.w, tag);
        }
      }
      __syncwarp();
    }
    uint32_t any;
    asm volatile("{\n.reg .pred p, q;\nsetp.ne.b32 p, %1, 0;\nbarrier.cta.red.or.aligned.pred q, %2, 256, p;\nselp.u32 %0, 1, 0, q;\n}\n" : "=r"(any) : "r"((int)beaten), "n"((int)NB_BOTH) : "memory");
    if (any) slow_path(p, grp, eps, tag, info.z, info.w);
  }
}

__global__ void __launch_bounds__(NTHR, 1) occupancy_probe_kernel() {}

typedef CUresult (*EncodeFn)(CUtensorMap*, CUtensorMapDataType, cuuint32_t, void*, const cuuint64_t*, const cuuint64_t*, const cuuint32_t*, const cuuint32_t*,
                             CUtensorMapInterleave, CUtensorMapSwizzle, CUtensorMapL2promotion, CUtensorMapFloatOOBfill);

static void make_tm(EncodeFn enc, CUtensorMap* tm, const void* ptr, uint64_t rows, uint64_t cols, uint32_t brows, uint32_t bcols, bool swz, bool wide) {
  cuuint64_t dims[2] = {cols, rows};
  cuuint64_t strides[1] = {cols * 2};
  cuuint32_t box[2] = {bcols, brows};
  cuuint32_t es[2] = {1, 1};
  enc(tm, CU_TENSOR_MAP_DATA_TYPE_BFLOAT16, 2, const_cast<void*>(ptr), dims, strides, box, es, CU_TENSOR_MAP_INTERLEAVE_NONE,
      swz ? CU_TENSOR_MAP_SWIZZLE_128B : CU_TENSOR_MAP_SWIZZLE_NONE, wide ? CU_TENSOR_MAP_L2_PROMOTION_L2_256B : CU_TENSOR_MAP_L2_PROMOTION_L2_128B, CU_TENSOR_MAP_FLOAT_OOB_FILL_NONE);
}

extern "C" void kernel_launch(void* const* d_in, const int* in_sizes, int n_in, void* d_out, int out_size) {
  (void)in_sizes; (void)n_in; (void)out_size;
  static EncodeFn enc = nullptr;
  static void* abT = nullptr;
  static void* sc = nullptr;
  static int map = 0;
  if (!enc) {
    void* fn = nullptr; cudaDriverEntryPointQueryResult st;
    cudaGetDriverEntryPoint("cuTensorMapEncodeTiled", &fn, cudaEnableDefault, &st);
    enc = (EncodeFn)fn;
    cudaGetSymbolAddress(&abT, g_abT);
    cudaGetSymbolAddress(&sc, g_sc);
    cudaFuncSetAttribute(fnet_moe_kernel<0>, cudaFuncAttributeMaxDynamicSharedMemorySize, SMEM_TOTAL);
    cudaFuncSetAttribute(fnet_moe_kernel<1>, cudaFuncAttributeMaxDynamicSharedMemorySize, SMEM_TOTAL);
    cudaFuncSetAttribute(occupancy_probe_kernel, cudaFuncAttributeMaxDynamicSharedMemorySize, SMEM_TOTAL);
    cudaFuncSetAttribute(occupancy_probe_kernel, cudaFuncAttributeNonPortableClusterSizeAllowed, 1);
    cudaLaunchConfig_t cfg = {};
    cfg.gridDim = dim3(128); cfg.blockDim = dim3(NTHR); cfg.dynamicSmemBytes = SMEM_TOTAL;
    cudaLaunchAttribute at[1];
    at[0].id = cudaLaunchAttributeClusterDimension; at[0].val.clusterDim.x = 16; at[0].val.clusterDim.y = 1; at[0].val.clusterDim.z = 1;
    cfg.attrs = at; cfg.numAttrs = 1;
    int ncl = 0;
    if (cudaOccupancyMaxActiveClusters(&ncl, occupancy_probe_kernel, &cfg) == cudaSuccess && ncl >= 8) map = 1;
    (void)cudaGetLastError();
  }
  Params p;
  const bf16* x = (const bf16*)d_in[0];
  make_tm(enc, &p.tmD0, d_in[3], 1024, 1024, 128, 64, true, true);
  make_tm(enc, &p.tmD1, d_in[4], 1024, 1024, 128, 64, true, true);
  make_tm(enc, &p.tmX, x, 2048, 1024, 256, 64, true, true);
  make_tm(enc, &p.tmAbS, abT, 2048, 2048, 64, 64, true, false);
  make_tm(enc, &p.tmAbL, abT, 2048, 2048, 128, 64, true, false);
  make_tm(enc, &p.tmW0, d_in[1], 2048, 2048, 128, 64, true, true);
  make_tm(enc, &p.tmW1, d_in[2], 2048, 2048, 128, 64, true, true);
  make_tm(enc, &p.tmG, d_in[7], 1024, 3584, 16, 64, false, false);
  make_tm(enc, &p.tmU, d_in[8], 1024, 3584, 16, 64, false, false);
  make_tm(enc, &p.tmDn, d_in[9], 3584, 1024, 8, 256, false, false);
  p.x = x; p.Dre = (const bf16*)d_in[3]; p.Dim = (const bf16*)d_in[4];
  p.wr = (const bf16*)d_in[6]; p.wdown = (const bf16*)d_in[9]; p.wgate = (const bf16*)d_in[7]; p.wup = (const bf16*)d_in[8]; p.Wre = (const bf16*)d_in[1]; p.Wim = (const bf16*)d_in[2];
  p.out = (bf16*)d_out; p.sc = (Scratch*)sc;
  if (map == 1) fnet_moe_kernel<1><<<NGRID, NTHR, SMEM_TOTAL>>>(p);
  else fnet_moe_kernel<0><<<NGRID, NTHR, SMEM_TOTAL>>>(p);
}
```

```cpp
#include <cuda.h>
#include <cuda_runtime.h>
#include <cuda_bf16.h>
#include <stdint.h>
#include <type_traits>

typedef __nv_bfloat16 bf16;

constexpr int NGRID = 132, NTHR = 384;
__device__ __forceinline__ int k_col(int tau, int j) {
  const int i = j < 18 ? j - 2 : j - 16;
  return j < 4 ? tau * 256 + j * 64 : ((tau + (i >> 1)) & 7) * 256 + (i & 1) * 64 + (j < 18 ? 0 : 128);
}
constexpr int A_BYTES = 128 * 64 * 2;
constexpr int B_BYTES = 256 * 64 * 2;
constexpr int ST_BYTES = A_BYTES + B_BYTES;
constexpr int OFF_AUX = 4 * ST_BYTES;
constexpr int OFF_BAR = OFF_AUX + 32768;
constexpr int OFF_XS = OFF_BAR + 256;
constexpr int OFF_WR = OFF_XS + 2048;
constexpr int OFF_REM = OFF_WR + 256;
constexpr int OFF_INFO = OFF_REM + 256;
constexpr int SMEM_TOTAL = OFF_INFO + 256;
constexpr int INFO_WSUM = OFF_INFO, INFO_TAG = OFF_INFO + 4, INFO_KEY = OFF_INFO + 8, INFO_CAND = OFF_INFO + 16, INFO_ONES = OFF_INFO + 48, INFO_DS = OFF_INFO + 64, INFO_DS2 = OFF_INFO + 192;
constexpr int OFF_RS = OFF_XS;
constexpr int OFF_WC = OFF_AUX;
constexpr int OFF_EXA = OFF_AUX + 4096;
constexpr int OFF_EXB = OFF_AUX + 6144;
constexpr int OFF_RECV = A_BYTES;
__host__ __device__ constexpr int off_y(int w) { return w * ST_BYTES; }
constexpr int NSRC = 112;
enum { B_FULL = 0, B_EMPTY = 4, B_LO = 5, B_ALL = 6, B_EP = 8, B_AW = 16, B_STAT = 24, B_WC = 25, B_CD = 26, B_HR = 27, B_INFO = 28, B_PEER = 29, B_XCH = 30, B_GUX = (OFF_INFO + 128 - OFF_BAR) / 8 };
enum { NB_TURN0 = 1, NB_TURN1 = 2, NB_BOTH = 3, NB_AUX = 4, NB_H = 5 };

struct Scratch;
struct Params {
  Scratch* sc; const bf16* wr; const bf16* x; const bf16* Dre; const bf16* Dim; const bf16* Wre; const bf16* Wim;
  const bf16* wgate; const bf16* wup; const bf16* wdown; bf16* out;
  CUtensorMap tmX, tmD0, tmD1, tmW0, tmW1, tmAbS, tmAbL, tmG, tmU, tmDn;
};

__device__ __align__(1024) bf16 g_abT[2048 * 2048];
struct Scratch {
  alignas(128) uint4 xz[2048];
  alignas(128) uint2 dsum[2048];
  alignas(128) uint32_t abflag[128 * 32];
  alignas(128) uint32_t abdone[128 * 2 * 32];
  alignas(128) uint2 u[4 * 512];
  alignas(128) uint2 cl[128 * 16];
  alignas(128) uint4 cpart[4 * 16 * 512];
  alignas(128) uint2 ch[4 * 128 * 16];
  alignas(128) uint2 rdone[128];
  alignas(128) uint2 sel[4 * 1024];
  alignas(128) uint2 selkey[4 * 128 * 16];
  alignas(128) uint4 ypart[4 * NSRC * 64];
  alignas(128) uint4 hstat[16 * 8 * 128];
  alignas(128) uint2 key[128];
  alignas(128) uint2 hrow[128 * 512];
  alignas(128) uint2 fpart[8 * 1024];
  alignas(128) uint32_t epoch;
};
__device__ Scratch g_sc;

#define SPIN_LIMIT (1u << 17)
#define PF2_K 24
#define UNIT_PACE 1500
#define XPF_K 40
#define XS_DELAY 300
#define U_CLK 3700
#define XROW_PF 0
#define DROW_PF 0
#define TM_PF 0
#define SPLIT17 1
#define LO_NS 500
#define UWEAK 0
#define CAND_EARLY 0
#define CHAIN1 1
#define ROW_NS 400
#define W_PF 8
#define START_PF 0
#define ND0 65
#define ND1 66
#define ND2 67
#define ND3 -1
#define ND4 69
#define LATE_REFILL 0
#define HI_DELAY 0
#define HI_PACE 1200
#define Z_CLK 9000
#define CH_CLK 28000
#define CP_DELAY 1500
#define SEL_CLK 29000
#define YPART_DELAY 16500
__device__ __forceinline__ uint32_t smem_u32(const void* p) { return (uint32_t)__cvta_generic_to_shared(p); }
__device__ __forceinline__ uint32_t clk32() { uint32_t c; asm volatile("mov.u32 %0, %%clock;" : "=r"(c)); return c; }
__device__ __forceinline__ uint32_t zero_here() { uint64_t c; asm volatile("mov.u64 %0, %%clock64;" : "=l"(c) :: "memory"); return (uint32_t)(c >> 32) & threadIdx.y; }
__device__ __forceinline__ uint32_t uniform_zero_here() { uint32_t c; asm volatile("mov.u32 %0, %%clock;" : "=r"(c) :: "memory"); return c & blockIdx.y; }
__device__ __forceinline__ void wait_clk(uint32_t t0, uint32_t dt) {
  asm volatile("{\n.reg .pred p;\n.reg .u32 c;\nLOOP:\nmov.u32 c, %%clock;\nsub.u32 c, c, %0;\nsetp.lt.u32 p, c, %1;\n@p nanosleep.u32 100;\n@p bra LOOP;\n}\n" :: "r"(t0), "r"(dt) : "memory");
}
__device__ __forceinline__ void mbar_init(uint32_t bar, uint32_t cnt) { asm volatile("mbarrier.init.shared::cta.b64 [%0], %1;" :: "r"(bar), "r"(cnt) : "memory"); }
__device__ __forceinline__ void mbar_expect_tx(uint32_t bar, uint32_t bytes) { asm volatile("mbarrier.arrive.expect_tx.shared::cta.b64 _, [%0], %1;" :: "r"(bar), "r"(bytes) : "memory"); }
__device__ __forceinline__ void mbar_arrive(uint32_t bar) { asm volatile("mbarrier.arrive.shared::cta.b64 _, [%0];" :: "r"(bar) : "memory"); }
__device__ __forceinline__ void mbar_arrive_remote(uint32_t cluster_addr) { asm volatile("mbarrier.arrive.shared::cluster.b64 _, [%0];" :: "r"(cluster_addr) : "memory"); }
__device__ __forceinline__ void mbar_wait(uint32_t bar, uint32_t parity) {
  asm volatile("{\n.reg .pred p;\nLOOP:\nmbarrier.try_wait.parity.shared::cta.b64 p, [%0], %1;\n@!p bra LOOP;\n}\n" :: "r"(bar), "r"(parity) : "memory");
}
__device__ __forceinline__ void tma_load_2d(uint32_t dst, const CUtensorMap* tm, uint32_t bar, int c0, int c1) {
  asm volatile("cp.async.bulk.tensor.2d.shared::cluster.global.mbarrier::complete_tx::bytes [%0], [%1, {%3, %4}], [%2];"
    :: "r"(dst), "l"(tm), "r"(bar), "r"(c0), "r"(c1) : "memory");
}
__device__ __forceinline__ void tma_load_2d_hint(uint32_t dst, const CUtensorMap* tm, uint32_t bar, int c0, int c1, uint64_t pol) {
  asm volatile("cp.async.bulk.tensor.2d.shared::cluster.global.mbarrier::complete_tx::bytes.L2::cache_hint [%0], [%1, {%3, %4}], [%2], %5;"
    :: "r"(dst), "l"(tm), "r"(bar), "r"(c0), "r"(c1), "l"(pol) : "memory");
}
__device__ __forceinline__ uint64_t policy_evict_first() { uint64_t p; asm volatile("createpolicy.fractional.L2::evict_first.b64 %0, 1.0;" : "=l"(p)); return p; }
__device__ __forceinline__ void tma_store_2d(const CUtensorMap* tm, uint32_t src, int c0, int c1) {
  asm volatile("cp.async.bulk.tensor.2d.global.shared::cta.bulk_group [%0, {%2, %3}], [%1];" :: "l"(tm), "r"(src), "r"(c0), "r"(c1) : "memory");
}
__device__ __forceinline__ void bulk_load(uint32_t dst, const void* src, uint32_t bytes, uint32_t bar) {
  asm volatile("cp.async.bulk.shared::cluster.global.mbarrier::complete_tx::bytes [%0], [%1], %2, [%3];" :: "r"(dst), "l"(src), "r"(bytes), "r"(bar) : "memory");
}
__device__ __forceinline__ void prefetch_l2(const void* p) { asm volatile("prefetch.global.L2 [%0];" :: "l"(p)); }
__device__ __forceinline__ void bulk_commit() { asm volatile("cp.async.bulk.commit_group;" ::: "memory"); }
__device__ __forceinline__ void bulk_wait_all() { asm volatile("cp.async.bulk.wait_group 0;" ::: "memory"); }
__device__ __forceinline__ void fence_async_smem() { asm volatile("fence.proxy.async.shared::cta;" ::: "memory"); }
__device__ __forceinline__ void wgmma_fence() { asm volatile("wgmma.fence.sync.aligned;" ::: "memory"); }
__device__ __forceinline__ void wgmma_commit() { asm volatile("wgmma.commit_group.sync.aligned;" ::: "memory"); }
template<int N> __device__ __forceinline__ void wgmma_wait() { asm volatile("wgmma.wait_group.sync.aligned %0;" :: "n"(N) : "memory"); }
__device__ __forceinline__ void bar_sync(int id, int n) { asm volatile("bar.sync %0, %1;" :: "r"(id), "r"(n) : "memory"); }
__device__ __forceinline__ void bar_arrive(int id, int n) { asm volatile("bar.arrive %0, %1;" :: "r"(id), "r"(n) : "memory"); }
__device__ __forceinline__ void cluster_wait() { asm volatile("barrier.cluster.wait.aligned;" ::: "memory"); }
template<int R> __device__ __forceinline__ void reg_inc() { asm volatile("setmaxnreg.inc.sync.aligned.u32 %0;" :: "n"(R)); }
template<int R> __device__ __forceinline__ void reg_dec() { asm volatile("setmaxnreg.dec.sync.aligned.u32 %0;" :: "n"(R)); }
__device__ __forceinline__ bool elect_one() {
  uint32_t p;
  asm volatile("{\n.reg .pred q;\nelect.sync _|q, 0xffffffff;\nselp.u32 %0, 1, 0, q;\n}\n" : "=r"(p));
  return p != 0;
}
__device__ __forceinline__ uint32_t mapa(uint32_t addr, uint32_t cta) { uint32_t r; asm volatile("mapa.shared::cluster.u32 %0, %1, %2;" : "=r"(r) : "r"(addr), "r"(cta)); return r; }
__device__ __forceinline__ void st_async_v4(uint32_t addr, uint32_t bar, uint32_t a, uint32_t b, uint32_t c, uint32_t d) {
  asm volatile("st.async.weak.shared::cluster.mbarrier::complete_tx::bytes.v4.b32 [%0], {%2, %3, %4, %5}, [%1];" :: "r"(addr), "r"(bar), "r"(a), "r"(b), "r"(c), "r"(d) : "memory");
}
__device__ __forceinline__ void st_async_b32(uint32_t addr, uint32_t bar, uint32_t a) {
  asm volatile("st.async.weak.shared::cluster.mbarrier::complete_tx::bytes.b32 [%0], %2, [%1];" :: "r"(addr), "r"(bar), "r"(a) : "memory");
}
__device__ __forceinline__ void stsm_x4(uint32_t addr, uint32_t a, uint32_t b, uint32_t c, uint32_t d) {
  asm volatile("stmatrix.sync.aligned.m8n8.x4.shared.b16 [%0], {%1, %2, %3, %4};" :: "r"(addr), "r"(a), "r"(b), "r"(c), "r"(d) : "memory");
}
__device__ __forceinline__ void stsm_x4_t(uint32_t addr, uint32_t a, uint32_t b, uint32_t c, uint32_t d) {
  asm volatile("stmatrix.sync.aligned.m8n8.x4.trans.shared.b16 [%0], {%1, %2, %3, %4};" :: "r"(addr), "r"(a), "r"(b), "r"(c), "r"(d) : "memory");
}
__device__ __forceinline__ uint4 lds128(uint32_t addr) { uint4 v; asm volatile("ld.shared.v4.b32 {%0, %1, %2, %3}, [%4];" : "=r"(v.x), "=r"(v.y), "=r"(v.z), "=r"(v.w) : "r"(addr) : "memory"); return v; }
extern __shared__ __align__(1024) uint8_t smem_raw[];
template<class T> __device__ __forceinline__ T& SM(int off) { return *reinterpret_cast<T*>(smem_raw + off); }
__device__ __forceinline__ uint4 ldg_nc128(const void* p) { uint4 v; asm volatile("ld.global.nc.v4.b32 {%0, %1, %2, %3}, [%4];" : "=r"(v.x), "=r"(v.y), "=r"(v.z), "=r"(v.w) : "l"(p)); return v; }
__device__ __forceinline__ uint4 ldg128(const void* p) { uint4 v; asm volatile("ld.global.L1::no_allocate.v4.b32 {%0, %1, %2, %3}, [%4];" : "=r"(v.x), "=r"(v.y), "=r"(v.z), "=r"(v.w) : "l"(p) : "memory"); return v; }
__device__ __forceinline__ void pkt_st128(void* p, uint32_t a, uint32_t b, uint32_t c, uint32_t d) {
  asm volatile("{\n.reg .b128 v;\n.reg .b64 lo, hi;\nmov.b64 lo, {%1, %2};\nmov.b64 hi, {%3, %4};\nmov.b128 v, {lo, hi};\nst.relaxed.gpu.global.b128 [%0], v;\n}\n"
    :: "l"(p), "r"(a), "r"(b), "r"(c), "r"(d) : "memory");
}
__device__ __forceinline__ uint4 pkt_ld128(const void* p) {
  uint4 r;
  asm volatile("{\n.reg .b128 v;\n.reg .b64 lo, hi;\nld.relaxed.gpu.global.b128 v, [%4];\nmov.b128 {lo, hi}, v;\nmov.b64 {%0, %1}, lo;\nmov.b64 {%2, %3}, hi;\n}\n"
    : "=r"(r.x), "=r"(r.y), "=r"(r.z), "=r"(r.w) : "l"(p) : "memory");
  return r;
}
__device__ __forceinline__ void pkt_st64(void* p, uint32_t a, uint32_t b) {
  asm volatile("{\n.reg .b64 v;\nmov.b64 v, {%1, %2};\nst.relaxed.gpu.global.b64 [%0], v;\n}\n" :: "l"(p), "r"(a), "r"(b) : "memory");
}
__device__ __forceinline__ uint2 pkt_ld64(const void* p) {
  uint2 r;
  asm volatile("{\n.reg .b64 v;\nld.relaxed.gpu.global.b64 v, [%2];\nmov.b64 {%0, %1}, v;\n}\n" : "=r"(r.x), "=r"(r.y) : "l"(p) : "memory");
  return r;
}
__device__ __forceinline__ void pkt_clear128(void* p) { pkt_st128(p, 0, 0, 0, 0); }
__device__ __forceinline__ uint32_t ld_relaxed32(const void* p) { uint32_t v; asm volatile("ld.relaxed.gpu.global.b32 %0, [%1];" : "=r"(v) : "l"(p) : "memory"); return v; }
__device__ __forceinline__ uint32_t ld_acquire32(const void* p) { uint32_t v; asm volatile("ld.acquire.gpu.global.b32 %0, [%1];" : "=r"(v) : "l"(p) : "memory"); return v; }
__device__ __forceinline__ void st_relaxed32(void* p, uint32_t v) { asm volatile("st.relaxed.gpu.global.b32 [%0], %1;" :: "l"(p), "r"(v) : "memory"); }
__device__ __forceinline__ uint32_t poll64(const void* p, uint32_t tag, int ns) {
  uint2 v; uint32_t n = 0;
  bool more;
#pragma unroll 1
  do {
    v = pkt_ld64(p);
    more = !(v.y == tag) && ++n < SPIN_LIMIT;
    if (more) { __nanosleep(ns); }
  } while (more);
  return v.x;
}
__device__ __forceinline__ uint32_t poll64_warp(const void* p, uint32_t tag, int ns) {
  uint2 v; uint32_t n = 0;
  bool more;
#pragma unroll 1
  do {
    v = pkt_ld64(p);
    more = !(__all_sync(0xffffffffu, v.y == tag)) && ++n < SPIN_LIMIT;
    if (more) { __nanosleep(ns); }
  } while (more);
  return v.x;
}
__device__ __forceinline__ uint32_t code_of(uint32_t tag) { return tag % 3u + 1u; }
__device__ __forceinline__ uint32_t with_bit(uint32_t v, uint32_t bit) { return (v & ~1u) | (bit & 1u); }
__device__ __forceinline__ uint32_t with_bit(float v, uint32_t bit) { return with_bit(__float_as_uint(v), bit); }
__device__ __forceinline__ float no_bit(uint32_t v) { return __uint_as_float(v & ~1u); }
__device__ __forceinline__ void chk(uint32_t& bad, uint32_t a, uint32_t want) { bad |= a ^ want; asm("" : "+r"(bad)); }
__device__ __forceinline__ void chk_code(uint32_t& bad, const uint4& v, uint32_t c0, uint32_t c1) { chk(bad, v.x, c0); chk(bad, v.y, c1); chk(bad, v.z, c0); chk(bad, v.w, c1); }
__device__ __forceinline__ uint32_t pack_bf16(float lo, float hi) { uint32_t r; asm("cvt.rn.bf16x2.f32 %0, %1, %2;" : "=r"(r) : "f"(hi), "f"(lo)); return r; }
__device__ __forceinline__ float bf_lo(uint32_t v) { return __uint_as_float(v << 16); }
__device__ __forceinline__ float bf_hi(uint32_t v) { return __uint_as_float(v & 0xFFFF0000u); }
__device__ __forceinline__ float bf16r(float x) { return __uint_as_float(pack_bf16(0.f, x)); }
__device__ __forceinline__ void st_bf16(bf16* p, float x) { *reinterpret_cast<uint16_t*>(p) = (uint16_t)pack_bf16(x, 0.f); }
__device__ __forceinline__ float fast_rcp(float x) { float r; asm("rcp.approx.f32 %0, %1;" : "=f"(r) : "f"(x)); return r; }
__device__ __forceinline__ float ldbf(const bf16* p) { return __bfloat162float(*p); }
__device__ __forceinline__ uint32_t badd2(uint32_t a, uint32_t b) { uint32_t r; asm("add.rn.bf16x2 %0, %1, %2;" : "=r"(r) : "r"(a), "r"(b)); return r; }
__device__ __forceinline__ uint32_t bfma2(uint32_t a, uint32_t b, uint32_t c) { uint32_t r; asm("fma.rn.bf16x2 %0, %1, %2, %3;" : "=r"(r) : "r"(a), "r"(b), "r"(c)); return r; }
__device__ __forceinline__ float warp_sum(float v) {
#pragma unroll
  for (int o = 16; o > 0; o >>= 1) v += __shfl_xor_sync(0xffffffffu, v, o);
  return v;
}
template<int N> __device__ __forceinline__ void fold(float* v, int o, int lane) {
  const bool up = lane & o;
#pragma unroll
  for (int i = 0; i < N / 2; i++) {
    const float keep = up ? v[N / 2 + i] : v[i], send = up ? v[i] : v[N / 2 + i];
    v[i] = keep + __shfl_xor_sync(0xffffffffu, send, o);
  }
}
__device__ __forceinline__ uint32_t make_key(float r_bf, int row) {
  const uint32_t u = __float_as_uint(r_bf);
  return (((u & 0x80000000u) ? ~u : (u | 0x80000000u)) & 0xFFFF0000u) | (0xFFFFu - (uint32_t)row);
}
__device__ __forceinline__ int key_row(uint32_t key) { return (0xFFFF - (int)(key & 0xFFFFu)) & 2047; }
__device__ __forceinline__ float key_val(uint32_t key) { const uint32_t o = key & 0xFFFF0000u; return __uint_as_float((o & 0x80000000u) ? (o & 0x7FFFFFFFu) : (~o & 0xFFFF0000u)); }
__device__ __forceinline__ float ref_sd(float var) { float r; asm("sqrt.approx.f32 %0, %1;" : "=f"(r) : "f"(bf16r(bf16r(var) + 1e-5f))); return bf16r(r); }
__device__ __forceinline__ uint64_t make_desc(uint32_t addr) { return (uint64_t)((addr & 0x3FFFF) >> 4) | ((uint64_t)64 << 32) | ((uint64_t)1 << 62); }
__device__ __forceinline__ uint64_t make_desc_noswz(uint32_t addr) { return (uint64_t)((addr & 0x3FFFF) >> 4) | ((uint64_t)8 << 32); }
#define ACC8(d, o) "+f"(d[o]), "+f"(d[o + 1]), "+f"(d[o + 2]), "+f"(d[o + 3]), "+f"(d[o + 4]), "+f"(d[o + 5]), "+f"(d[o + 6]), "+f"(d[o + 7])
#define ACC64(d, o) ACC8(d, o), ACC8(d, o + 8), ACC8(d, o + 16), ACC8(d, o + 24), ACC8(d, o + 32), ACC8(d, o + 40), ACC8(d, o + 48), ACC8(d, o + 56)
#define REGS64 "%0, %1, %2, %3, %4, %5, %6, %7, %8, %9, %10, %11, %12, %13, %14, %15, %16, %17, %18, %19, %20, %21, %22, %23, %24, %25, %26, %27, %28, %29, %30, %31, " \
    "%32, %33, %34, %35, %36, %37, %38, %39, %40, %41, %42, %43, %44, %45, %46, %47, %48, %49, %50, %51, %52, %53, %54, %55, %56, %57, %58, %59, %60, %61, %62, %63"
#define REGS128 REGS64 ", %64, %65, %66, %67, %68, %69, %70, %71, %72, %73, %74, %75, %76, %77, %78, %79, %80, %81, %82, %83, %84, %85, %86, %87, %88, %89, %90, %91, %92, %93, %94, %95, " \
    "%96, %97, %98, %99, %100, %101, %102, %103, %104, %105, %106, %107, %108, %109, %110, %111, %112, %113, %114, %115, %116, %117, %118, %119, %120, %121, %122, %123, %124, %125, %126, %127"
__device__ __forceinline__ void wgmma_n256(float (&d)[128], uint64_t da, uint64_t db) {
  asm volatile("wgmma.mma_async.sync.aligned.m64n256k16.f32.bf16.bf16 {" REGS128 "}, %128, %129, 1, 1, 1, 0, 0;\n"
    : ACC64(d, 0), ACC64(d, 64) : "l"(da), "l"(db));
}
#define OUT8(d, o) "=f"(d[o]), "=f"(d[o + 1]), "=f"(d[o + 2]), "=f"(d[o + 3]), "=f"(d[o + 4]), "=f"(d[o + 5]), "=f"(d[o + 6]), "=f"(d[o + 7])
#define OUT64(d, o) OUT8(d, o), OUT8(d, o + 8), OUT8(d, o + 16), OUT8(d, o + 24), OUT8(d, o + 32), OUT8(d, o + 40), OUT8(d, o + 48), OUT8(d, o + 56)
__device__ __forceinline__ void wgmma_n256_rs_init(float (&d)[128], const uint32_t* a, uint64_t db) {
  asm volatile("wgmma.mma_async.sync.aligned.m64n256k16.f32.bf16.bf16 {" REGS128 "}, {%128, %129, %130, %131}, %132, 0, 1, 1, 0;\n"
    : OUT64(d, 0), OUT64(d, 64) : "r"(a[0]), "r"(a[1]), "r"(a[2]), "r"(a[3]), "l"(db));
}
template<int ACCUM> __device__ __forceinline__ void wgmma_n256_rs(float (&d)[128], const uint32_t* a, uint64_t db) {
  asm volatile("wgmma.mma_async.sync.aligned.m64n256k16.f32.bf16.bf16 {" REGS128 "}, {%128, %129, %130, %131}, %132, %133, 1, 1, 0;\n"
    : ACC64(d, 0), ACC64(d, 64) : "r"(a[0]), "r"(a[1]), "r"(a[2]), "r"(a[3]), "l"(db), "n"(ACCUM));
}
template<int ACCUM> __device__ __forceinline__ void wgmma_n8_rs(float (&d)[4], const uint32_t* a, uint64_t db) {
  asm volatile("wgmma.mma_async.sync.aligned.m64n8k16.f32.bf16.bf16 {%0, %1, %2, %3}, {%4, %5, %6, %7}, %8, %9, 1, 1, 0;\n"
    : "+f"(d[0]), "+f"(d[1]), "+f"(d[2]), "+f"(d[3]) : "r"(a[0]), "r"(a[1]), "r"(a[2]), "r"(a[3]), "l"(db), "n"(ACCUM));
}
__device__ __forceinline__ void wgmma_n8(float (&d)[4], uint64_t da, uint64_t db) {
  asm volatile("wgmma.mma_async.sync.aligned.m64n8k16.f32.bf16.bf16 {%0, %1, %2, %3}, %4, %5, 1, 1, 1, 0, 0;\n"
    : "+f"(d[0]), "+f"(d[1]), "+f"(d[2]), "+f"(d[3]) : "l"(da), "l"(db));
}
__device__ __forceinline__ void wgmma_n128(float (&d)[64], uint64_t da, uint64_t db) {
  asm volatile("wgmma.mma_async.sync.aligned.m64n128k16.f32.bf16.bf16 {" REGS64 "}, %64, %65, 1, 1, 1, 0, 0;\n" : ACC64(d, 0) : "l"(da), "l"(db));
}
template<int N> __device__ __forceinline__ void fence_regs(float (&d)[N]) {
#pragma unroll
  for (int i = 0; i < N; i++) asm volatile("" : "+f"(d[i]) :: "memory");
}
__device__ __forceinline__ void mma16816(float (&c)[4], uint32_t a0, uint32_t a1, uint32_t a2, uint32_t a3, uint32_t b0, uint32_t b1) {
  asm volatile("mma.sync.aligned.m16n8k16.row.col.f32.bf16.bf16.f32 {%0, %1, %2, %3}, {%4, %5, %6, %7}, {%8, %9}, {%0, %1, %2, %3};"
               : "+f"(c[0]), "+f"(c[1]), "+f"(c[2]), "+f"(c[3]) : "r"(a0), "r"(a1), "r"(a2), "r"(a3), "r"(b0), "r"(b1));
}
__device__ __forceinline__ void fma8(float* acc, const uint4& v, float x) {
  acc[0] = fmaf(bf_lo(v.x), x, acc[0]); acc[1] = fmaf(bf_hi(v.x), x, acc[1]); acc[2] = fmaf(bf_lo(v.y), x, acc[2]); acc[3] = fmaf(bf_hi(v.y), x, acc[3]);
  acc[4] = fmaf(bf_lo(v.z), x, acc[4]); acc[5] = fmaf(bf_hi(v.z), x, acc[5]); acc[6] = fmaf(bf_lo(v.w), x, acc[6]); acc[7] = fmaf(bf_hi(v.w), x, acc[7]);
}
template<int PITCH> __device__ __forceinline__ void gemv8x8(float (&acc)[8], uint32_t addr, const float (&x)[8]) {
  uint4 v[2][2];
  v[0][0] = lds128(addr); v[0][1] = lds128(addr + PITCH);
#pragma unroll
  for (int b = 0; b < 4; b++) {
    if (b < 3) { v[(b + 1) & 1][0] = lds128(addr + (2 * b + 2) * PITCH); v[(b + 1) & 1][1] = lds128(addr + (2 * b + 3) * PITCH); }
    acc[0] += __uint_as_float(zero_here());
    fma8(acc, v[b & 1][0], x[2 * b]); fma8(acc, v[b & 1][1], x[2 * b + 1]);
  }
}
__device__ __forceinline__ float swiglu(float g, float u) {
  g = bf16r(g); u = bf16r(u);
  return bf16r(bf16r(g * fast_rcp(1.f + __expf(-g))) * u);
}

#define CT(slot) do {} while (0)
#define TIM(slot) do {} while (0)

constexpr int H_BUF0 = 0, H_BUF1 = 16384, H_RED = 32768, H_KEYS = H_RED + 1024, H_ROW = H_KEYS + 1024, H_ACT = H_ROW + 8192, H_PART = H_ACT + 4096;
__device__ __forceinline__ void hsync() { bar_sync(NB_H, 256); }
template<int N> __device__ __forceinline__ void block_sum(float (&v)[N], int warp, int lane) {
#pragma unroll
  for (int i = 0; i < N; i++) v[i] = warp_sum(v[i]);
  hsync();
  if (lane == 0) {
#pragma unroll
    for (int i = 0; i < N; i++) SM<float>(H_RED + (i * 8 + warp) * 4) = v[i];
  }
  hsync();
#pragma unroll
  for (int i = 0; i < N; i++) {
    const float4 a = SM<float4>(H_RED + i * 32), b = SM<float4>(H_RED + i * 32 + 16);
    v[i] = ((a.x + a.y) + (a.z + a.w)) + ((b.x + b.y) + (b.z + b.w));
  }
}
__device__ __forceinline__ void fft_first(int j, float2 v0, float2 v1, float2 v2, float2 v3) {
  const float2 a = make_float2(v0.x + v2.x, v0.y + v2.y), b = make_float2(v0.x - v2.x, v0.y - v2.y);
  const float2 c = make_float2(v1.x + v3.x, v1.y + v3.y), d = make_float2(v1.y - v3.y, v3.x - v1.x);
  SM<float4>(H_BUF1 + j * 32) = make_float4(a.x + c.x, a.y + c.y, b.x + d.x, b.y + d.y);
  SM<float4>(H_BUF1 + j * 32 + 16) = make_float4(a.x - c.x, a.y - c.y, b.x - d.x, b.y - d.y);
}
template<int NB> __device__ __forceinline__ void fft_passes(int tid) {
  constexpr int q = 256 * NB;
#pragma unroll 1
  for (int ps = 1; ps < 5; ps++) {
    const int ns = 1 << (2 * ps), k = tid & (ns - 1);
    float s1, c1;
    __sincosf(-1.57079632679f * __fdividef((float)k, (float)ns), &s1, &c1);
    const float c2 = c1 * c1 - s1 * s1, s2 = 2.f * c1 * s1, c3 = c1 * c2 - s1 * s2, s3 = c1 * s2 + s1 * c2;
    hsync();
#pragma unroll
    for (int i = 0; i < NB; i++) {
      const int j = tid + 256 * i;
      const float2* in = &SM<float2>((ps & 1) ? H_BUF1 : H_BUF0);
      float2* o = &SM<float2>((ps & 1) ? H_BUF0 : H_BUF1) + (j - k) * 4 + k;
      const float2 v0 = in[j], x1 = in[j + q], x2 = in[j + 2 * q], x3 = in[j + 3 * q];
      const float2 v1 = make_float2(x1.x * c1 - x1.y * s1, x1.x * s1 + x1.y * c1);
      const float2 v2 = make_float2(x2.x * c2 - x2.y * s2, x2.x * s2 + x2.y * c2);
      const float2 v3 = make_float2(x3.x * c3 - x3.y * s3, x3.x * s3 + x3.y * c3);
      const float2 a = make_float2(v0.x + v2.x, v0.y + v2.y), b = make_float2(v0.x - v2.x, v0.y - v2.y);
      const float2 c = make_float2(v1.x + v3.x, v1.y + v3.y), d = make_float2(v1.y - v3.y, v3.x - v1.x);
      o[0] = make_float2(a.x + c.x, a.y + c.y); o[ns] = make_float2(b.x + d.x, b.y + d.y);
      o[2 * ns] = make_float2(a.x - c.x, a.y - c.y); o[3 * ns] = make_float2(b.x - d.x, b.y - d.y);
    }
  }
  hsync();
}
template<int NR> __device__ __forceinline__ void ln_rows(const float (&h)[NR][4], float (&hn)[NR][4], int warp, int lane) {
  float s[NR], q[NR];
#pragma unroll
  for (int i = 0; i < NR; i++) s[i] = (h[i][0] + h[i][1]) + (h[i][2] + h[i][3]);
  block_sum(s, warp, lane);
#pragma unroll
  for (int i = 0; i < NR; i++) {
    s[i] *= 1.f / 1024.f; q[i] = 0.f;
#pragma unroll
    for (int z = 0; z < 4; z++) q[i] = fmaf(h[i][z] - s[i], h[i][z] - s[i], q[i]);
  }
  block_sum(q, warp, lane);
#pragma unroll
  for (int i = 0; i < NR; i++) {
    const float mb = bf16r(s[i]), inv = fast_rcp(ref_sd(q[i] * (1.f / 1024.f)));
#pragma unroll
    for (int z = 0; z < 4; z++) hn[i][z] = bf16r(bf16r(h[i][z] - mb) * inv);
  }
}
__device__ __forceinline__ float routed_out(float h, float hn, float y, float r) {
  const float sig = bf16r(fast_rcp(1.f + __expf(-r)));
  return h + bf16r(hn + bf16r(bf16r(y) * sig));
}

__device__ __forceinline__ void helper_cta(const Params& p, const int hi, const uint32_t t_entry) {
  const int tid = threadIdx.x, warp = tid >> 5, lane = tid & 31;
  const float w0 = ldbf(p.wr + tid), w1 = ldbf(p.wr + tid + 256), w2 = ldbf(p.wr + tid + 512), w3 = ldbf(p.wr + tid + 768), wf = ldbf(p.wr);
  const uint32_t tag = ld_relaxed32(&p.sc->epoch) + 1;
  pkt_clear128(&p.sc->u[hi * 512 + tid * 2]);
  if (tid == 0 && w0 != 123.f) TIM(12);
  fft_first(tid, make_float2(w0, 0.f), make_float2(w1, 0.f), make_float2(w2, 0.f), make_float2(w3, 0.f));
  fft_passes<1>(tid);
  const uint32_t c0 = code_of(tag), c1 = c0 >> 1;
  {
    const float off = wf - SM<float>(H_BUF1) * (1.f / 1024.f);
    const float4 v = SM<float4>(H_BUF1 + tid * 32), u = SM<float4>(H_BUF1 + tid * 32 + 16);
    pkt_st128(&p.sc->u[hi * 512 + ((tid & 192) + (tid & 1) * 32 + ((tid >> 1) & 31)) * 2], with_bit(pack_bf16((tid ? v.x : 0.f) - off, v.z - off), c0), with_bit(pack_bf16(v.y, v.w), c1),
              with_bit(pack_bf16(u.x - off, u.z - off), c0), with_bit(pack_bf16(u.y, u.w), c1));
    pkt_clear128(&p.sc->sel[hi * 1024 + tid * 2]); pkt_clear128(&p.sc->sel[hi * 1024 + 512 + tid * 2]);
    if (tid < 128) { pkt_clear128(&p.sc->selkey[(hi * 128 + tid) * 16]); pkt_clear128(&p.sc->selkey[(hi * 128 + tid) * 16 + 2]); }
    else if (tid >= 192) pkt_clear128(&p.sc->cl[(hi * 32 + ((tid - 192) >> 1)) * 16 + (tid & 1) * 2]);
    hsync();
  }
  if (tid == 0) TIM(0);
  {
    float tw[8];
#pragma unroll
    for (int i = 0; i < 4; i++) __sincosf((float)(tid + 256 * i) * (-6.28318530718f / 2048.f), &tw[2 * i], &tw[2 * i + 1]);
    wait_clk(t_entry, Z_CLK);
    uint2 z[8]; uint32_t n = 0;
    bool more;
#pragma unroll 1
    do {
      uint32_t bad = 0;
#pragma unroll
      for (int i = 0; i < 8; i++) z[i] = pkt_ld64(reinterpret_cast<const uint2*>(&p.sc->xz[tid + 256 * i]) + 1);
#pragma unroll
      for (int i = 0; i < 8; i++) chk(bad, z[i].y, tag);
      more = !(!bad) && ++n < SPIN_LIMIT;
      if (more) { __nanosleep(150); }
    } while (more);
#pragma unroll
    for (int i = 0; i < 2; i++)
      fft_first(tid + 256 * i, make_float2(bf_lo(z[i].x), bf_hi(z[i].x)), make_float2(bf_lo(z[i + 2].x), bf_hi(z[i + 2].x)),
                make_float2(bf_lo(z[i + 4].x), bf_hi(z[i + 4].x)), make_float2(bf_lo(z[i + 6].x), bf_hi(z[i + 6].x)));
    if (tid == 0) TIM(7);
    fft_passes<2>(tid);
    if (tid == 0) TIM(1);
    uint32_t k8[8];
#pragma unroll
    for (int i = 0; i < 4; i++) {
      const int k = tid + 256 * i;
      const float2 v0 = SM<float2>(H_BUF1 + k * 8), v1 = SM<float2>(H_BUF1 + (k + 1024) * 8);
      const float w = v1.x * tw[2 * i + 1] - v1.y * tw[2 * i];
      const uint32_t a = __float_as_uint(v0.x + w), b = __float_as_uint(v0.x - w);
      k8[2 * i] = (((a & 0x80000000u) ? ~a : (a | 0x80000000u)) & ~2047u) | k;
      k8[2 * i + 1] = (((b & 0x80000000u) ? ~b : (b | 0x80000000u)) & ~2047u) | (k + 1024);
    }
    uint32_t lim = 0xFFFFFFFFu;
#pragma unroll 1
    for (int r = 0; r < 4; r++) {
      uint32_t mx = 0;
#pragma unroll
      for (int i = 0; i < 8; i++) mx = max(mx, k8[i] <= lim ? k8[i] : 0u);
      mx = __reduce_max_sync(0xffffffffu, mx);
      if (lane == 0) SM<uint32_t>(H_KEYS + (warp * 4 + r) * 4) = mx;
      lim = mx - 1;
    }
    hsync();
    if (tid < 32) {
      const uint32_t me = SM<uint32_t>(H_KEYS + tid * 4);
      int rank = 0;
#pragma unroll
      for (int i = 0; i < 8; i++) { const uint4 o = SM<uint4>(H_KEYS + i * 16); rank += (o.x > me) + (o.y > me) + (o.z > me) + (o.w > me); }
      if (rank < 8) SM<uint16_t>(H_KEYS + 256 + rank * 2) = me & 2047u;
    }
    hsync();
    if (tid >= 128) pkt_st64(&p.sc->cl[(hi * 32 + ((tid - 128) >> 2)) * 16 + (tid & 3)], SM<uint32_t>(H_KEYS + 256 + (tid & 3) * 4), tag);
  }
  const uint32_t cpair = SM<uint32_t>(H_KEYS + 256 + hi * 4);
  const int ca = cpair & 0xFFFF, cb = cpair >> 16;
  if (tid < 128) prefetch_l2(((tid & 32) ? p.Wim : p.Wre) + (size_t)((tid & 64) ? cb : ca) * 2048 + lane * 64);
  if (tid == 0) TIM(2);
  {
    const int e0 = (tid >> 2) * 16 + (tid & 3) * 2;
    const uint32_t wa = *reinterpret_cast<const uint32_t*>(p.wr + e0), wb = *reinterpret_cast<const uint32_t*>(p.wr + e0 + 8);
    wait_clk(t_entry, CH_CLK);
    uint4 va, vb; uint32_t n = 0;
    bool more;
#pragma unroll 1
    do {
      const uint2* src = &p.sc->ch[(hi * 128 + (tid >> 1)) * 16 + (tid & 1) * 2];
      va = pkt_ld128(src); vb = pkt_ld128(src + 4);
      more = !((va.y == tag && va.w == tag && vb.y == tag && vb.w == tag)) && ++n < SPIN_LIMIT;
      if (more) { __nanosleep(150); }
    } while (more);
    if (tid == 0) TIM(3);
    const float h[2][4] = {{bf_lo(va.x), bf_hi(va.x), bf_lo(va.z), bf_hi(va.z)}, {bf_lo(vb.x), bf_hi(vb.x), bf_lo(vb.z), bf_hi(vb.z)}};
    float hn[2][4], r[2];
    ln_rows<2>(h, hn, warp, lane);
    if (tid == 0) TIM(13);
#pragma unroll
    for (int i = 0; i < 2; i++) r[i] = (hn[i][0] * bf_lo(wa) + hn[i][1] * bf_lo(wb)) + (hn[i][2] * bf_hi(wa) + hn[i][3] * bf_hi(wb));
    block_sum(r, warp, lane);
    const uint32_t ka = make_key(bf16r(r[0]), ca), kb = make_key(bf16r(r[1]), cb), mine = max(ka, kb);
    const bool s2 = kb > ka;
    pkt_st128(&p.sc->sel[hi * 1024 + tid * 2], s2 ? pack_bf16(hn[1][0], hn[1][1]) : pack_bf16(hn[0][0], hn[0][1]), tag, s2 ? pack_bf16(hn[1][2], hn[1][3]) : pack_bf16(hn[0][2], hn[0][3]), tag);
    pkt_st128(&p.sc->sel[hi * 1024 + 512 + tid * 2], s2 ? vb.x : va.x, tag, s2 ? vb.z : va.z, tag);
    if (tid < 128) pkt_st64(&p.sc->selkey[(hi * 128 + tid) * 16], mine, tag);
    if (tid == 0) TIM(14);
  }
}

__device__ __forceinline__ void slow_path(const Params& p, int grp, int eps, uint32_t tag, uint32_t key, int win) {
  const int tid = threadIdx.x, warp = tid >> 5, lane = tid & 31;
  uint32_t best = __reduce_max_sync(0xffffffffu, poll64(&p.sc->key[tid & 127], tag, 200));
  if (lane == 0) SM<uint32_t>(H_KEYS + warp * 4) = best;
  hsync();
  { const uint4 b4 = SM<uint4>(H_KEYS); best = max(max(b4.x, b4.y), max(b4.z, b4.w)); }
  const int tw = key_row(best), col = eps * 128 + (tid & 127);
  if ((tw >> 7) != grp) return;
  if (tid < 128) {
    const int pos = (col >> 4) * 8 + (col & 7);
    const uint32_t a = poll64(&p.sc->sel[win * 1024 + 512 + pos], tag, 100), b = poll64(&p.sc->sel[win * 1024 + pos], tag, 100);
    poll64(&p.sc->rdone[col >> 3], tag, 100);
    st_bf16(p.out + key_row(key) * 1024 + col, (col & 8) ? bf_hi(a) + bf_hi(b) : bf_lo(a) + bf_lo(b));
  }
  const uint32_t h0 = poll64(&p.sc->hrow[(tw >> 4) * 512 + 2 * tid], tag, 100), h1 = poll64(&p.sc->hrow[(tw >> 4) * 512 + 2 * tid + 1], tag, 100);
  float h[1][4] = {{bf_lo(h0), bf_hi(h0), bf_lo(h1), bf_hi(h1)}}, hn[1][4];
  ln_rows<1>(h, hn, warp, lane);
  SM<float4>(H_ROW + tid * 16) = make_float4(hn[0][0], hn[0][1], hn[0][2], hn[0][3]);
  SM<float4>(H_ROW + 4096 + tid * 16) = make_float4(h[0][0], h[0][1], h[0][2], h[0][3]);
  hsync();
#pragma unroll 1
  for (int ph = 0; ph < 2; ph++) {
    const int part = min(tid / 56, 3), fh = tid >> 7, len = ph ? 224 : 512, ld = ph ? 1024 : 3584;
    const bf16* wp = ph ? p.wdown + (eps * 448 + fh * 224) * 1024 + (tid & 127) * 8
                        : ((part & 1) ? p.wup : p.wgate) + (part >> 1) * 512 * 3584 + eps * 448 + min(tid - part * 56, 55) * 8;
    const int xo = ph ? H_ACT + fh * 224 * 4 : H_ROW + (part >> 1) * 2048;
    float acc[8] = {0.f, 0.f, 0.f, 0.f, 0.f, 0.f, 0.f, 0.f};
#pragma unroll 8
    for (int d = 0; d < (len & ~7); d++) fma8(acc, ldg_nc128(wp + d * ld), SM<float>(xo + d * 4));
    SM<float4>(H_PART + tid * 32) = make_float4(acc[0], acc[1], acc[2], acc[3]);
    SM<float4>(H_PART + tid * 32 + 16) = make_float4(acc[4], acc[5], acc[6], acc[7]);
    hsync();
    if (ph) break;
#pragma unroll 1
    for (int f = tid; f < 448; f += 256)
      SM<float>(H_ACT + f * 4) = swiglu(SM<float>(H_PART + f * 4) + SM<float>(H_PART + (896 + f) * 4), SM<float>(H_PART + (448 + f) * 4) + SM<float>(H_PART + (1344 + f) * 4));
    hsync();
  }
#pragma unroll 1
  for (int e = tid; e < 1024; e += 256) pkt_st64(&p.sc->fpart[eps * 1024 + e], __float_as_uint(SM<float>(H_PART + e * 4) + SM<float>(H_PART + (1024 + e) * 4)), tag);
  if (tid < 128) {
    float y = 0.f;
#pragma unroll 1
    for (int q = 0; q < 8; q++) y += __uint_as_float(poll64(&p.sc->fpart[q * 1024 + col], tag, 200));
    st_bf16(p.out + tw * 1024 + col, routed_out(SM<float>(H_ROW + 4096 + col * 4), SM<float>(H_ROW + col * 4), y, key_val(best)));
  }
}

template<int MAP>
__global__ void __cluster_dims__(2, 1, 1) __launch_bounds__(NTHR, 1)
fnet_moe_kernel(const __grid_constant__ Params p) {
  const uint32_t t_entry = clk32();
  uint32_t smid;
  asm("mov.u32 %0, %%smid;" : "=r"(smid));
  const int tpc = smid >> 1, m = blockIdx.x & 1;
  if (MAP == 1 ? tpc >= 64 : (tpc >> 1) == 30) {
    if (threadIdx.x < 256) helper_cta(p, (tpc & 1) * 2 + m, t_entry);
    return;
  }
  const uint32_t sb = smem_u32(smem_raw);
  const int tid = threadIdx.x, lane = tid & 31;
  const int e7 = ((tpc - 32) * 37) >> 8;
  const int tau = MAP == 1 || tpc < 32 ? (tpc & 7) : (tpc < 60 ? tpc - 31 - 7 * e7 : 0);
  const int eps = MAP == 1 || tpc < 32 ? (tpc >> 3) : (tpc < 60 ? 4 + e7 : tpc - 58);
  const int cid = tau * 16 + eps * 2 + m;
  const int grp = tau * 2 + m;
  auto BAR = [&](int i) { return sb + OFF_BAR + 8 * i; };
  const CUtensorMap* tmD = &p.tmD0 + m;
#define LOAD_STREAM(d, tm, bar, c0, c1) tma_load_2d_hint(d, tm, bar, c0, c1, pol_ef)
#define LOAD_W tma_load_2d
#define LOAD_D tma_load_2d
#define LOAD_X tma_load_2d
#define LOAD_F LOAD_STREAM

  uint32_t tag = 0;
  uint4 wq = make_uint4(0, 0, 0, 0);
  if ((tid >> 5) == 4) {
    if (elect_one()) {
      const uint64_t pol_ef = policy_evict_first();
#pragma unroll
      for (int k = 0; k < 4; k++) mbar_init(BAR(B_FULL + k), 1);
      asm volatile("fence.mbarrier_init.release.cluster;" ::: "memory");
#pragma unroll
      for (int k = 0; k < 4; k++) {
        mbar_expect_tx(BAR(B_FULL + k), ST_BYTES);
        tma_load_2d(sb + k * ST_BYTES + A_BYTES, &p.tmX, BAR(B_FULL + k), k * 64, tau * 256);
        LOAD_D(sb + k * ST_BYTES, tmD, BAR(B_FULL + k), k * 64, eps * 128);
        TIM(k);
      }
    }
  } else if ((tid >> 5) == 1) {
    if (elect_one()) {
#pragma unroll
      for (int s = 0; s < 4; s++) mbar_init(BAR(B_EMPTY + s), 1);
#pragma unroll
      for (int s = 0; s < 8; s++) { mbar_init(BAR(B_EP + s), 4); mbar_init(BAR(B_AW + s), 1); }
      mbar_init(BAR(B_STAT), 4); mbar_init(BAR(B_WC), 1); mbar_init(BAR(B_CD), 2);
      mbar_init(BAR(B_HR), 1); mbar_init(BAR(B_INFO), 1); mbar_init(BAR(B_PEER), 1);
      mbar_init(BAR(B_XCH), 1); mbar_init(BAR(B_XCH + 1), 1); mbar_init(BAR(B_GUX), 1);
      asm volatile("fence.mbarrier_init.release.cluster;" ::: "memory");
      mbar_expect_tx(BAR(B_XCH), 16384); mbar_expect_tx(BAR(B_XCH + 1), 16384); mbar_expect_tx(BAR(B_GUX), 256);
    }
  } else if (tid >= 256) {
    if (START_PF) prefetch_l2(((tid & 64) ? (cid < 64 ? p.Dre : p.Dim) + (cid & 63) * 16384 : p.x + cid * 16384) + ((tid >> 2) & 15) * 1024 + (tid & 3) * 64);
    tag = ld_relaxed32(&p.sc->epoch + threadIdx.y);
    wq = ldg128(p.wr + (tid & 127) * 8);
  }
  const int warp = __shfl_sync(0xffffffffu, tid >> 5, 0);
  __syncthreads();
  asm volatile("barrier.cluster.arrive.relaxed.aligned;" ::: "memory");
  const int abrow = m * 1024 + eps * 128;
  const bool ffn = eps > 0;
  const int fc = (tau * 7 + eps - 1) * 64, src = (fc >> 5) + m;

  if (warp >= 8) {
    reg_dec<72>();
    cluster_wait();
    tag = __shfl_sync(0xffffffffu, tag, 0) + 1;
    const int a = warp - 8;
    int lane, j;
    auto fresh_ids = [&]() { uint32_t l; asm volatile("mov.u32 %0, %%laneid;" : "=r"(l)); lane = l; j = a * 32 + l; };
    fresh_ids();
    const uint32_t buf = sb + OFF_AUX + a * 8192, bar0 = BAR(B_AW + 2 * a);
    if (a == 0 && lane < 16) pkt_clear128(&p.sc->xz[cid * 16 + lane]);
    if (lane < 2) pkt_clear128(&p.sc->dsum[cid * 16 + a * 4 + lane * 2]);
    if (a == 3 && lane < 6) pkt_clear128((lane < 4 ? &p.sc->abdone[(cid * 2 + (lane >> 1)) * 32] : &p.sc->abflag[cid * 32]) + (lane & 1) * 4);
    {
      const float s = warp_sum(((bf_lo(wq.x) + bf_hi(wq.x)) + (bf_lo(wq.y) + bf_hi(wq.y))) + ((bf_lo(wq.z) + bf_hi(wq.z)) + (bf_lo(wq.w) + bf_hi(wq.w))));
      if ((j >> 4) == eps) SM<uint4>(OFF_WR + (j & 15) * 16) = wq;
      if (lane == 0) { SM<float>(INFO_DS + a * 4) = s; SM<uint32_t>(INFO_ONES + a * 4) = 0x3F803F80u; }
    }
    const uint32_t c0 = code_of(tag), c1 = c0 >> 1;
    const bf16* xrows = p.x + (cid * 16 + a * 4) * 1024;
    const bf16* drows = (cid < 64 ? p.Dre : p.Dim) + ((cid & 63) * 16 + a * 4) * 1024;
    if (XROW_PF) {
      wait_clk(t_entry, XROW_PF);
      prefetch_l2(xrows + lane * 64); prefetch_l2(xrows + 2048 + lane * 64);
    }
    fresh_ids();
    {
      wait_clk(t_entry, U_CLK);
      uint4 u[8]; uint32_t n = 0;
      bool more;
#pragma unroll 1
      do {
        uint32_t bad = 0;
#pragma unroll
        for (int q = 0; q < 8; q++) u[q] = UWEAK && n == 0 ? ldg128(&p.sc->u[a * 512 + (q * 32 + lane) * 2]) : pkt_ld128(&p.sc->u[a * 512 + (q * 32 + lane) * 2]);
        if (n == 0 && lane < 2) { mbar_expect_tx(bar0 + lane * 8, 4096); bulk_load(buf + lane * 4096, xrows + lane * 2048, 4096, bar0 + lane * 8); }
#pragma unroll
        for (int q = 0; q < 8; q++) chk_code(bad, u[q], c0, c1);
        more = !(!__any_sync(0xffffffffu, bad & 1)) && ++n < SPIN_LIMIT;
        if (more) { __nanosleep(200); }
      } while (more);
      if (j == 0) TIM(96);
      if (DROW_PF) { prefetch_l2(drows + lane * 64); prefetch_l2(drows + 2048 + lane * 64); }
#pragma unroll 1
      for (int r2 = 0; r2 < 2; r2++) {
        float v8[8];
        mbar_wait(bar0 + r2 * 8, 0);
        if (lane == 0) TIM(140 + r2 * 4 + a);
#pragma unroll
        for (int r = 0; r < 2; r++) {
          float s0 = 0.f, s1 = 0.f, q0 = 0.f, q1 = 0.f;
          uint32_t zr = 0, zi = 0;
#pragma unroll
          for (int q = 0; q < 4; q++) {
            const uint4 v = lds128(buf + r2 * 4096 + r * 2048 + (q * 32 + lane) * 16);
            const uint32_t ww[4] = {v.x, v.y, v.z, v.w};
#pragma unroll
            for (int z = 0; z < 4; z++) {
              const float lo = bf_lo(ww[z]), hi = bf_hi(ww[z]);
              s0 += lo; q0 = fmaf(lo, lo, q0); s0 += hi; q0 = fmaf(hi, hi, q0);
            }
            zr = bfma2(v.x, u[2 * q].x, zr); zi = bfma2(v.x, u[2 * q].y, zi); zr = bfma2(v.y, u[2 * q].z, zr); zi = bfma2(v.y, u[2 * q].w, zi);
            zr = bfma2(v.z, u[2 * q + 1].x, zr); zi = bfma2(v.z, u[2 * q + 1].y, zi); zr = bfma2(v.w, u[2 * q + 1].z, zr); zi = bfma2(v.w, u[2 * q + 1].w, zi);
          }
          v8[4 * r] = s0 + s1; v8[4 * r + 1] = q0 + q1; v8[4 * r + 2] = bf_lo(zr) + bf_hi(zr); v8[4 * r + 3] = bf_lo(zi) + bf_hi(zi);
        }
        fold<8>(v8, 16, lane);
        if (lane == 0) { mbar_expect_tx(bar0 + r2 * 8, 4096); bulk_load(buf + r2 * 4096, drows + r2 * 2048, 4096, bar0 + r2 * 8); }
        fold<4>(v8, 8, lane); fold<2>(v8, 4, lane);
        v8[0] += __shfl_xor_sync(0xffffffffu, v8[0], 2);
        v8[0] += __shfl_xor_sync(0xffffffffu, v8[0], 1);
        SM<float>(OFF_REM + a * 64 + r2 * 32 + (lane >> 2) * 4) = v8[0];
        if (lane == 0) TIM(148 + r2 * 4 + a);
      }
    }
    bar_sync(NB_AUX, 128);
    fresh_ids();
    if (a == 0 && lane < 16) {
      const float4 v = SM<float4>(OFF_REM + lane * 16);
      const float mean = v.x * (1.f / 1024.f), rs = fast_rcp(ref_sd(fmaxf(v.y * (1.f / 1024.f) - mean * mean, 0.f)));
      pkt_st128(&p.sc->xz[cid * 16 + lane], __float_as_uint(bf16r(mean)) | (tag & 0xFFFFu), __float_as_uint(rs), pack_bf16(v.z * rs, v.w * rs), tag);
    }
    if (j == 32) { const float4 v = SM<float4>(INFO_DS); SM<float2>(INFO_WSUM) = make_float2((v.x + v.y) + (v.z + v.w), __uint_as_float(tag)); }
    if (j == 0) TIM(98);
#pragma unroll 1
    for (int r2 = 0; r2 < 2; r2++) {
      mbar_wait(bar0 + r2 * 8, 1);
      uint4 dv[8];
#pragma unroll
      for (int q = 0; q < 8; q++) dv[q] = lds128(buf + r2 * 4096 + (lane >> 4) * 2048 + q * 256 + (lane & 15) * 16);
      float s0 = __uint_as_float(zero_here()), s1 = 0.f;
#pragma unroll
      for (int q = 0; q < 8; q++) {
        const uint4 v = dv[q];
        s0 += bf_lo(v.x); s0 += bf_hi(v.x); s0 += bf_lo(v.y); s0 += bf_hi(v.y); s0 += bf_lo(v.z); s0 += bf_hi(v.z); s0 += bf_lo(v.w); s0 += bf_hi(v.w);
      }
      s0 += s1;
#pragma unroll
      for (int o = 8; o > 0; o >>= 1) s0 += __shfl_xor_sync(0xffffffffu, s0, o);
      SM<float>(INFO_DS2 + (a * 4 + r2 * 2 + (lane >> 4)) * 4) = s0;
    }
    bar_sync(NB_AUX, 128);
    if (a == 1 && lane < 16) pkt_st64(&p.sc->dsum[cid * 16 + lane], SM<uint32_t>(INFO_DS2 + lane * 4), tag);
    if (j == 0) TIM(99);
    uint4* cpart = &p.sc->cpart[grp * 512 + eps * 64];
    pkt_clear128(cpart + (j >> 5) * 8192 + lane); pkt_clear128(cpart + (j >> 5) * 8192 + 32 + lane);
    if (a == 3) pkt_st64(&p.sc->ch[((lane >> 3) * 128 + cid) * 16 + (lane & 7)], 0, 0);
    {
      wait_clk(clk32(), XS_DELAY);
      uint2 v0, v1, cs; uint32_t n = 0;
      const uint32_t t16 = tag & 0xFFFFu;
      bool more;
#pragma unroll 1
      do {
        v0 = pkt_ld64(&p.sc->xz[tau * 256 + j]); v1 = pkt_ld64(&p.sc->xz[tau * 256 + 128 + j]); cs = pkt_ld64(&p.sc->dsum[m * 1024 + eps * 128 + j]);
        more = !(__all_sync(0xffffffffu, (v0.x & 0xFFFFu) == t16 && (v1.x & 0xFFFFu) == t16 && cs.y == tag)) && ++n < SPIN_LIMIT;
        if (more) { __nanosleep(200); }
      } while (more);
      const int ro = OFF_RS + ((j & 7) >> 1) * 272 + (j >> 3) * 8 + (j & 1) * 4;
      SM<uint32_t>(ro) = v0.y ^ (m << 31); SM<uint32_t>(ro + 128) = v1.y ^ (m << 31);
      const uint32_t n0 = (v0.x >> 16) ^ 0x8000u, n1 = (v1.x >> 16) ^ 0x8000u;
      SM<uint4>(OFF_EXB + j * 16) = make_uint4(n0 | (n0 << 16), n0, 0, 0);
      SM<uint4>(OFF_EXB + 2048 + j * 16) = make_uint4(n1 | (n1 << 16), n1, 0, 0);
      const float c = 0.5f * __uint_as_float(cs.x), hi = bf16r(c), mid = bf16r(c - hi), lo = bf16r((c - hi) - mid);
      SM<uint4>(OFF_EXA + j * 16) = make_uint4((__float_as_uint(hi) >> 16) | __float_as_uint(mid), __float_as_uint(lo) >> 16, 0, 0);
      fence_async_smem();
      __syncwarp();
      if (lane == 0) mbar_arrive(BAR(B_STAT));
    }
    if (j == 0) TIM(100);
    if (TM_PF && j < 3) asm volatile("prefetch.tensormap [%0];" :: "l"(j == 0 ? &p.tmAbS : j == 1 ? &p.tmAbL : m ? &p.tmW1 : &p.tmW0) : "memory");
    {
      if (a == 3) {
        const uint32_t cl = poll64_warp(&p.sc->cl[cid * 16 + (lane & 3)], tag, 100);
        if (lane == 0) TIM(101);
        const bf16* wm = (m ? p.Wim : p.Wre) + tau * 256 + lane * 8;
        uint4 v[8];
#pragma unroll
        for (int i = 0; i < 8; i++) v[i] = ldg128(wm + ((__shfl_sync(0xffffffffu, cl, i >> 1) >> ((i & 1) * 16)) & 2047) * 2048);
        const int pos = cid * 4 + (lane & 3);
        const bf16* xc = p.x + ((__shfl_sync(0xffffffffu, cl, lane >> 3) >> ((lane & 4) * 4)) & 2047) * 1024 + (pos >> 3) * 16 + (pos & 7);
        const float x0 = ldbf(xc), x1 = ldbf(xc + 8);
        if (lane < 4) SM<uint32_t>(INFO_CAND + lane * 4) = cl;
#pragma unroll
        for (int i = 0; i < 8; i++) SM<uint4>(OFF_WC + (lane >> 3) * 1024 + i * 128 + (((lane & 7) ^ i) << 4)) = v[i];
        fence_async_smem();
        __syncwarp();
        if (lane == 0) { mbar_arrive(BAR(B_WC)); TIM(102); }
        mbar_wait(BAR(B_CD), 0);
        wait_clk(clk32(), CP_DELAY);
        uint32_t n = 0;
        bool more;
#pragma unroll 1
        do {
          uint32_t bad = 0;
#pragma unroll
          for (int i = 0; i < 8; i++) v[i] = pkt_ld128(&p.sc->cpart[((lane >> 3) * 16 + 2 * i + ((lane >> 2) & 1)) * 512 + pos]);
#pragma unroll
          for (int i = 0; i < 8; i++) chk_code(bad, v[i], c0, c1);
          more = !(!__any_sync(0xffffffffu, bad & 1)) && ++n < SPIN_LIMIT;
          if (more) { __nanosleep(200); }
        } while (more);
        float y[4] = {0.f, 0.f, 0.f, 0.f};
#pragma unroll
        for (int i = 0; i < 8; i++) { y[0] += no_bit(v[i].x); y[2] += no_bit(v[i].y); y[1] += no_bit(v[i].z); y[3] += no_bit(v[i].w); }
#pragma unroll
        for (int i = 0; i < 4; i++) y[i] = bf16r(y[i]);
        __syncwarp();
        fold<4>(y, 4, lane);
        pkt_st64(&p.sc->ch[((lane >> 3) * 128 + cid) * 16 + (lane & 7)], pack_bf16(x0 + bf16r(y[0]), x1 + bf16r(y[1])), tag);
        if (lane == 0) TIM(119);
      }
      if (a < 2) {
        uint32_t* fl = lane == 0 && a == 0 ? &p.sc->abflag[cid * 32] : &p.sc->abdone[(((cid & 15) + (lane & 7) * 16) * 2 + a) * 32 + tau];
        asm volatile("" : "+l"(fl));
        if (lane == 0) {
          if (a == 1) mbar_wait(BAR(B_LO), 0);
          const uint32_t t1 = clk32();
#pragma unroll 1
          for (int i = 0; i < 4; i++) {
            if (a == 1) wait_clk(t1, HI_DELAY + i * HI_PACE);
            const int w = i >> 1, c = 2 * a + (i & 1);
            mbar_wait(BAR(B_EP + w * 4 + c), 0);
            TIM(64 + a * 8 + i);
            fence_async_smem();
            tma_store_2d(&p.tmAbS, sb + c * ST_BYTES + w * 8192, tau * 256 + c * 64, abrow + w * 64);
          }
          bulk_commit();
          bulk_wait_all();
          mbar_arrive(BAR(a ? B_HR : B_LO));
          TIM(68 + a * 8);
          asm volatile("fence.proxy.async.global;" ::: "memory");
          asm volatile("st.release.gpu.global.b32 [%0], %1;" :: "l"(fl), "r"(tag) : "memory");
          TIM(69 + a * 8);
        }
        __syncwarp();
        if (lane >= 8 && lane < 16) st_relaxed32(fl, tag);
        __nanosleep(500);
        uint32_t n = 0;
#pragma unroll 1
        while (!__all_sync(0xffffffffu, ld_acquire32(&p.sc->abdone[(cid * 2 + a) * 32 + (lane & 7)]) == tag) && ++n < SPIN_LIMIT) {}
        if (lane == 0) {
          asm volatile("fence.proxy.async.global;" ::: "memory");
          mbar_arrive(BAR(B_ALL + a));
          TIM(80 + a);
        }
      } else if (a == 2) {
        if (elect_one()) {
          const uint32_t* fl = &p.sc->abflag[((cid + 16) & 127) * 32];
          mbar_wait(BAR(B_LO), 0);
          mbar_wait(BAR(B_FULL), 0); mbar_wait(BAR(B_FULL + 1), 0);
          __nanosleep(LO_NS);
          uint32_t n = 0;
#pragma unroll 1
          while (ld_acquire32(fl) != tag && ++n < SPIN_LIMIT) {}
          asm volatile("fence.proxy.async.global;" ::: "memory");
          tma_load_2d(sb, &p.tmAbL, BAR(B_FULL), k_col(tau, 4), abrow);
          tma_load_2d(sb + ST_BYTES, &p.tmAbL, BAR(B_FULL + 1), k_col(tau, 5), abrow);
          TIM(130);
          mbar_wait(BAR(B_HR), 0); mbar_wait(BAR(B_FULL + 2), 0); mbar_wait(BAR(B_ALL), 0);
          tma_load_2d(sb + 2 * ST_BYTES, &p.tmAbL, BAR(B_FULL + 2), k_col(tau, 6), abrow);
          TIM(132);
          mbar_wait(BAR(B_EMPTY), 0);
          tma_load_2d(sb + 3 * ST_BYTES, &p.tmAbL, BAR(B_FULL + 3), k_col(tau, 7), abrow);
          TIM(133);
        }
      }
      __syncwarp();
    }
    mbar_wait(BAR(B_CD), 0);
    const uint64_t pol_ef = policy_evict_first();
    auto load_unit = [&](int v) {
      if (elect_one()) {
        const uint32_t dst = buf + (v & 1) * 4096, bar = bar0 + (v & 1) * 8;
        mbar_expect_tx(bar, 4096);
        if (v < 8) {
          LOAD_F(dst, &p.tmG, bar, fc, m * 512 + (a * 8 + v) * 16);
          LOAD_F(dst + 2048, &p.tmU, bar, fc, m * 512 + (a * 8 + v) * 16);
        } else LOAD_F(dst, &p.tmDn, bar, a * 256, src * 32 + (v - 8) * 8);
      }
    };
    if (TM_PF && j < 3) asm volatile("prefetch.tensormap [%0];" :: "l"(j == 0 ? &p.tmG : j == 1 ? &p.tmU : &p.tmDn) : "memory");
    wait_clk(t_entry, SEL_CLK);
    if (ffn) { load_unit(0); load_unit(1); }
    {
      if (a == 3) {
        const uint32_t kk = poll64_warp(&p.sc->selkey[((lane & 3) * 128 + cid) * 16], tag, 100), key = __reduce_max_sync(0xffffffffu, kk);
        const int win = __ffs(__ballot_sync(0xffffffffu, kk == key)) - 1;
        if (lane == 0) SM<uint2>(INFO_KEY) = make_uint2(key, win);
      }
      bar_sync(NB_AUX, 128);
      const uint2* sel = &p.sc->sel[SM<uint32_t>(INFO_KEY + 4) * 1024];
      uint4 v; uint32_t n = 0;
      bool more;
#pragma unroll 1
      do {
        v = pkt_ld128(sel + m * 256 + 2 * j);
        more = !(__all_sync(0xffffffffu, v.y == tag && v.w == tag)) && ++n < SPIN_LIMIT;
        if (more) { __nanosleep(100); }
      } while (more);
      const int d = (j >> 2) * 16 + (j & 3) * 2;
      SM<float2>(OFF_XS + d * 4) = make_float2(bf_lo(v.x), bf_lo(v.z));
      SM<float2>(OFF_XS + (d + 8) * 4) = make_float2(bf_hi(v.x), bf_hi(v.z));
    }
    bar_sync(NB_AUX, 128);
    if (j == 0) {
      mbar_arrive(BAR(B_INFO)); TIM(103);
      if (cid == 0) st_relaxed32(&p.sc->epoch, tag);
    }
    const uint32_t t2 = clk32();
    fresh_ids();
    if (!ffn) {
      wait_clk(t2, YPART_DELAY);
    } else {
      const int r = lane >> 3;
      float acc[8] = {0.f, 0.f, 0.f, 0.f, 0.f, 0.f, 0.f, 0.f};
#pragma unroll 1
      for (int v = 0; v < 8; v++) {
        const uint4 x0 = lds128(sb + OFF_XS + ((a * 8 + v) * 16 + (r & 1) * 8) * 4), x1 = lds128(sb + OFF_XS + ((a * 8 + v) * 16 + (r & 1) * 8 + 4) * 4);
        const float xv[8] = {__uint_as_float(x0.x), __uint_as_float(x0.y), __uint_as_float(x0.z), __uint_as_float(x0.w), __uint_as_float(x1.x), __uint_as_float(x1.y), __uint_as_float(x1.z), __uint_as_float(x1.w)};
        mbar_wait(bar0 + (v & 1) * 8, (v >> 1) & 1);
        gemv8x8<128>(acc, buf + (v & 1) * 4096 + r * 1024 + (lane & 7) * 16, xv);
        fence_regs(acc);
        __syncwarp();
        wait_clk(t2, v * UNIT_PACE);
        load_unit(v + 2);
        if (j == 0) TIM(104 + v);
      }
      pkt_clear128(&p.sc->ypart[(a * NSRC + src) * 64 + lane * 2]); pkt_clear128(&p.sc->ypart[(a * NSRC + src) * 64 + lane * 2 + 1]);
      fold<8>(acc, 8, lane);
      bar_sync(NB_AUX, 128);
      SM<float4>(OFF_XS + (a * 128 + (r >> 1) * 64 + (lane & 7) * 8 + (r & 1) * 4) * 4) = make_float4(acc[0], acc[1], acc[2], acc[3]);
      bar_sync(NB_AUX, 128);
      auto psum = [&](int i) { return (SM<float>(OFF_XS + i * 4) + SM<float>(OFF_XS + (128 + i) * 4)) + (SM<float>(OFF_XS + (256 + i) * 4) + SM<float>(OFF_XS + (384 + i) * 4)); };
      if (a < 2) st_async_b32(mapa(sb + OFF_REM + j * 4, m ^ 1), mapa(BAR(B_GUX), m ^ 1), __float_as_uint(psum(a * 64 + (m ^ 1) * 32 + lane)));
      const float og = psum(m * 32 + lane), ou = psum(64 + m * 32 + lane);
      mbar_wait(BAR(B_GUX), 0);
      const float rg = SM<float>(OFF_REM + lane * 4), ru = SM<float>(OFF_REM + 128 + lane * 4);
      const float act = swiglu(m ? rg + og : og + rg, m ? ru + ou : ou + ru);
      if (j == 0) TIM(112);
      float y[8] = {0.f, 0.f, 0.f, 0.f, 0.f, 0.f, 0.f, 0.f};
#pragma unroll 1
      for (int v = 8; v < 12; v++) {
        float av[8];
#pragma unroll
        for (int i = 0; i < 8; i++) av[i] = __shfl_sync(0xffffffffu, act, (v - 8) * 8 + i);
        mbar_wait(bar0 + (v & 1) * 8, (v >> 1) & 1);
        gemv8x8<512>(y, buf + (v & 1) * 4096 + lane * 16, av);
        fence_regs(y);
        __syncwarp();
        if (v < 10) load_unit(v + 2);
        if (j == 0) TIM(105 + v);
      }
      fresh_ids();
      uint4* ypart = &p.sc->ypart[(a * NSRC + src) * 64 + lane * 2];
      pkt_st128(ypart, with_bit(y[0], c0), with_bit(y[1], c1), with_bit(y[2], c0), with_bit(y[3], c1));
      pkt_st128(ypart + 1, with_bit(y[4], c0), with_bit(y[5], c1), with_bit(y[6], c0), with_bit(y[7], c1));
      if (lane == 0) TIM(160 + a);
      __nanosleep(ROW_NS);
    }
    {
      float y[8] = {0.f, 0.f, 0.f, 0.f, 0.f, 0.f, 0.f, 0.f};
      uint32_t hh = 0;
      if (j >= NSRC) hh = poll64(&p.sc->sel[SM<uint32_t>(INFO_KEY + 4) * 1024 + (j & 8) * 64 + (cid >> 1) * 8 + (j & 7)], tag, 100);
      if (j < NSRC) {
        const uint4* yp = &p.sc->ypart[((cid >> 5) * NSRC + j) * 64 + (cid & 31) * 2];
        uint4 va, vb; uint32_t n = 0;
        bool more;
#pragma unroll 1
        do {
          uint32_t bad = 0;
          va = pkt_ld128(yp); vb = pkt_ld128(yp + 1);
          chk_code(bad, va, c0, c1); chk_code(bad, vb, c0, c1);
          more = !(!(bad & 1)) && ++n < SPIN_LIMIT;
          if (more) { __nanosleep(300); }
        } while (more);
        y[0] = no_bit(va.x); y[1] = no_bit(va.y); y[2] = no_bit(va.z); y[3] = no_bit(va.w);
        y[4] = no_bit(vb.x); y[5] = no_bit(vb.y); y[6] = no_bit(vb.z); y[7] = no_bit(vb.w);
      }
      __syncwarp();
      if (lane == 0) TIM(164 + a);
      fold<8>(y, 16, lane); fold<4>(y, 8, lane); fold<2>(y, 4, lane);
      y[0] += __shfl_xor_sync(0xffffffffu, y[0], 2);
      y[0] += __shfl_xor_sync(0xffffffffu, y[0], 1);
      SM<float>(OFF_AUX + a * 8192 + (lane >> 2) * 4) = y[0];
      const float hn = m ? bf_hi(hh) : bf_lo(hh), h = __shfl_down_sync(0xffffffffu, hn, 8);
      bar_sync(NB_AUX, 128);
      if ((j >> 3) == 14) {
        const uint32_t key = SM<uint32_t>(INFO_KEY);
        const int o = OFF_AUX + (j & 7) * 4;
        const float ys = (SM<float>(o) + SM<float>(o + 8192)) + (SM<float>(o + 16384) + SM<float>(o + 24576));
        st_bf16(p.out + key_row(key) * 1024 + cid * 8 + (j & 7), routed_out(h, hn, ys, key_val(key)));
        if (j == 112) TIM(118);
        __threadfence();
        if (j == 112) TIM(117);
        __syncwarp(0xFF0000);
        if (j == 112) pkt_st64(&p.sc->rdone[cid], 0, tag);
      }
    }
  } else {
    reg_inc<216>();
    cluster_wait();
    const uint32_t sb = __shfl_sync(0xffffffffu, smem_u32(smem_raw), 0);
    auto BAR = [&](int i) { return sb + OFF_BAR + 8 * i; };
    const int w = warp >> 2, wi = warp & 3, t = tid & 127;
    const int turn_me = NB_TURN0 + w, turn_other = NB_TURN1 - w;
    const uint64_t dA0 = make_desc(sb + w * 8192);
    uint64_t dA, dB;
    int tau, eps, m, grp, abrow, fc, src;
    bool ffn;
    const CUtensorMap* tmD; const CUtensorMap* tmW;
    auto new_desc = [&](int salt) {
      const uint32_t z = salt < 0 ? uniform_zero_here() : salt & blockIdx.y;
      dA = dA0 + z; dB = dA0 + (z + ((A_BYTES - w * 8192) >> 4));
      const int c = cid + z;
      tau = c >> 4; eps = (c >> 1) & 7; m = c & 1; grp = tau * 2 + m; abrow = m * 1024 + eps * 128;
      ffn = eps > 0; fc = (tau * 7 + eps - 1) * 64; src = (fc >> 5) + m;
      tmD = &p.tmD0 + m; tmW = &p.tmW0 + m;
    };
    constexpr int SL = ST_BYTES >> 4;
    float acc[128];
#pragma unroll
    for (int i = 0; i < 128; i++) acc[i] = 0.f;
    if (w == 1) bar_arrive(NB_TURN0, 256);
    auto full = [&](int k) { mbar_wait(BAR(B_FULL + (k & 3)), (k >> 2) & 1); CT(64 + k); };
    const uint64_t pol_ef = policy_evict_first();
    auto refill_g1 = [&](int k) {
      if (warp == 4) {
        if (elect_one()) {
          const int s = k & 3;
          TIM(k + 4);
          mbar_expect_tx(BAR(B_FULL + s), ST_BYTES);
          LOAD_X(sb + s * ST_BYTES + A_BYTES, &p.tmX, BAR(B_FULL + s), (k + 4) * 64, tau * 256);
          LOAD_D(sb + s * ST_BYTES, tmD, BAR(B_FULL + s), (k + 4) * 64, eps * 128);
        }
        __syncwarp();
      }
    };
    auto refill_g2 = [&](int k, int mode) {
      if (warp == 4) {
        if (elect_one()) {
          const int s = k & 3, s0 = k_col(tau, k - 12);
          TIM(k + 4);
          mbar_expect_tx(BAR(B_FULL + s), mode ? ST_BYTES : B_BYTES);
          if (k == 19) mbar_arrive(BAR(B_EMPTY));
          LOAD_W(sb + s * ST_BYTES + A_BYTES, tmW, BAR(B_FULL + s), s0, grp * 128);
          LOAD_W(sb + s * ST_BYTES + A_BYTES + 16384, tmW, BAR(B_FULL + s), s0, (grp ^ 1) * 128);
          if (mode == 2) tma_load_2d(sb + s * ST_BYTES, &p.tmAbL, BAR(B_FULL + s), s0, abrow);
        }
        __syncwarp();
      }
    };
    auto mma_ss = [&](int k) {
#pragma unroll
      for (int kk = 0; kk < 4; kk++) wgmma_n256(acc, dA + (k & 3) * SL + kk * 2, dB + (k & 3) * SL + kk * 2);
    };
    const bf16* pf; int pf_step; bool pf_on;
    auto pf_ffn = [&](int v) {
      pf_on = ffn && v >= 0 && v < 12;
      pf = v < 8 ? ((lane & 16) ? p.wup : p.wgate) + (m * 512 + (wi * 8 + v) * 16 + (lane & 15)) * 3584 + fc : p.wdown + (src * 32 + (v - 8) * 8) * 1024 + t * 64;
      pf_step = v < 8 ? 16 * 3584 : 8192;
    };
    auto prefetch = [&](int s) { if (pf_on && (wi >> 1) == (s & 1)) prefetch_l2(pf + (s >> 1) * pf_step); };
    auto kstep = [&](int k) {
      full(k);
      bar_sync(turn_me, 256);
      wgmma_fence();
      mma_ss(k);
      wgmma_commit();
      bar_arrive(turn_other, 256);
    };

#pragma unroll 1
    for (int k4 = 0; k4 < 12; k4 += 4) {
      new_desc(k4);
#pragma unroll
      for (int s = 0; s < 4; s++) {
        kstep(k4 | s);
        if (s == 0) {
          if (w == 0) pf_ffn((k4 >> 1) - 2);
          else {
            pf_on = W_PF && k4 == 8;
            pf = (m ? p.Wim : p.Wre) + (tau * 256 + eps * 32 + wi * 4 + (lane >> 3)) * 2048 + k_col(tau, lane & 7);
            pf_step = 16 * 2048;
          }
          pf += zero_here();
        }
        if (LATE_REFILL && (k4 | s)) refill_g1((k4 | s) - 1);
        prefetch(s);
        wgmma_wait<0>();
        if (!LATE_REFILL || (k4 | s) == 11) refill_g1(k4 | s);
      }
    }
    uint32_t R[64];
    auto load_rs = [&](auto gi) {
      const uint32_t rsa = sb + OFF_RS + (lane & 3) * 272;
#pragma unroll
      for (int i = 4 * decltype(gi)::value; i < 4 * decltype(gi)::value + 4; i++) { const uint4 v = lds128(rsa + i * 16); R[4 * i] = v.x; R[4 * i + 1] = v.y; R[4 * i + 2] = v.z; R[4 * i + 3] = v.w; }
    };
    new_desc(ND0);
    kstep(12);
    mbar_wait(BAR(B_STAT), 0);
    CT(1);
    load_rs(std::integral_constant<int, 0>());
    load_rs(std::integral_constant<int, 1>());
    wgmma_wait<0>(); refill_g2(12, 0);
    load_rs(std::integral_constant<int, 3>());
    auto mma_h = [&](float (&d)[64], int s, int half) {
#pragma unroll
      for (int kk = 0; kk < 4; kk++) wgmma_n128(d, dA + s * SL + kk * 2, dB + s * SL + half * 1024 + kk * 2);
    };
    const int rho = 16 * wi + (lane & 15);
    const uint32_t arow = sb + w * 8192 + rho * 128;
    auto convert = [&](auto cc, float (&d)[64]) {
      const float z = __uint_as_float(zero_here());
#pragma unroll
      for (int jj = 8 * decltype(cc)::value; jj < 8 * decltype(cc)::value + 8; jj++) {
        const float r0 = __uint_as_float(R[2 * jj]), r1 = __uint_as_float(R[2 * jj + 1]);
        const float* ac = &d[4 * (jj & 15)];
        R[2 * jj] = pack_bf16(fmaf(ac[0], r0, z), fmaf(ac[1], r1, z));
        R[2 * jj + 1] = pack_bf16(fmaf(ac[2], r0, z), fmaf(ac[3], r1, z));
      }
    };
    auto put = [&](auto cc) {
      constexpr int c = decltype(cc)::value;
#pragma unroll
      for (int jj = 8 * c; jj < 8 * c + 8; jj += 2)
        stsm_x4(arow + c * ST_BYTES + ((((jj & 7) + (lane >> 4)) ^ (rho & 7)) << 4), R[2 * jj], R[2 * jj + 1], R[2 * jj + 2], R[2 * jj + 3]);
      __syncwarp();
      if (lane == 0) mbar_arrive(BAR(B_EP + w * 4 + c));
    };
    {
      float lo[64], hi[64];
      fence_regs(acc);
#pragma unroll
      for (int i = 0; i < 64; i++) asm volatile("mov.b32 %0, %1;" : "=f"(lo[i]) : "f"(acc[i]));
#pragma unroll
      for (int i = 0; i < 64; i++) asm volatile("mov.b32 %0, %1;" : "=f"(hi[i]) : "f"(acc[64 + i]));
      const uint64_t dEA = make_desc_noswz(sb + OFF_EXA + w * 1024), dEB = make_desc_noswz(sb + OFF_EXB);
      full(13); full(14);
      bar_sync(turn_me, 256);
      wgmma_fence();
      mma_h(lo, 1, 0); mma_h(lo, 2, 0);
      wgmma_commit();
      bar_arrive(turn_other, 256);
      new_desc(ND1);
      full(15);
      bar_sync(turn_me, 256);
      wgmma_fence();
      mma_h(lo, 3, 0);
      wgmma_n128(lo, dEA, dEB);
      wgmma_commit();
      mma_h(hi, 1, 1);
      wgmma_commit();
      bar_arrive(turn_other, 256);
      new_desc(ND2);
      wgmma_wait<1>();
      fence_regs(lo);
      CT(15);
      convert(std::integral_constant<int, 0>(), lo); put(std::integral_constant<int, 0>());
      convert(std::integral_constant<int, 1>(), lo);
      wgmma_wait<0>(); refill_g2(13, 0);
      put(std::integral_constant<int, 1>());
      bar_sync(turn_me, 256);
      wgmma_fence();
      mma_h(hi, 2, 1);
      wgmma_commit();
      mma_h(hi, 3, 1);
      wgmma_n128(hi, dEA, dEB + 128);
      wgmma_commit();
      bar_arrive(turn_other, 256);
      load_rs(std::integral_constant<int, 2>());
      wgmma_wait<1>(); refill_g2(14, 0);
      wgmma_wait<0>(); refill_g2(15, 0);
      fence_regs(hi);
      CT(2);
      convert(std::integral_constant<int, 3>(), hi); put(std::integral_constant<int, 3>());
      convert(std::integral_constant<int, 2>(), hi);
    }
    CT(3);
    float cc[4];
    auto cand_mma = [&]() {
      const uint64_t dC = make_desc(sb + OFF_WC);
      wgmma_n8_rs<0>(cc, R, dC);
#pragma unroll
      for (int i = 1; i < 12; i++) wgmma_n8_rs<1>(cc, R + 4 * i, dC + (i >> 2) * 64 + (i & 3) * 2);
#pragma unroll
      for (int kk = 0; kk < 4; kk++) wgmma_n8(cc, dA + 3 * SL + kk * 2, dC + 192 + kk * 2);
      wgmma_commit();
    };
    auto cand_pub = [&]() {
      fence_regs(cc);
      const uint32_t cd = code_of(SM<uint32_t>(INFO_TAG));
      if (t == 0) mbar_arrive(BAR(B_CD));
      pkt_st128(&p.sc->cpart[((lane & 3) * 16 + grp) * 512 + eps * 64 + warp * 8 + (lane >> 2)], with_bit(cc[0], cd), with_bit(cc[1], cd >> 1), with_bit(cc[2], cd), with_bit(cc[3], cd >> 1));
      CT(5);
    };
    new_desc(ND3);
    if (CAND_EARLY) { fence_async_smem(); mbar_wait(BAR(B_WC), 0); CT(4); }
    full(16);
    if (!SPLIT17) full(17);
    bar_sync(turn_me, 256);
    wgmma_fence();
    if (CAND_EARLY) cand_mma();
    wgmma_n256_rs_init(acc, R, dB);
#pragma unroll
    for (int kk = 1; kk < 4; kk++) wgmma_n256_rs<1>(acc, R + 4 * kk, dB + kk * 2);
    wgmma_commit();
    if (SPLIT17) { full(17); wgmma_fence(); }
#pragma unroll
    for (int kk = 0; kk < 4; kk++) wgmma_n256_rs<1>(acc, R + 16 + 4 * kk, dB + SL + kk * 2);
    wgmma_commit();
    bar_arrive(turn_other, 256);
    if (CAND_EARLY) { wgmma_wait<2>(); put(std::integral_constant<int, 2>()); cand_pub(); }
    else put(std::integral_constant<int, 2>());
    wgmma_wait<1>(); refill_g2(16, 1);
    wgmma_wait<0>(); refill_g2(17, 1);
    if (!CAND_EARLY) { fence_async_smem(); mbar_wait(BAR(B_WC), 0); CT(4); }
    full(18);
    bar_sync(turn_me, 256);
    wgmma_fence();
    if (!CAND_EARLY) cand_mma();
#pragma unroll
    for (int kk = 0; kk < 4; kk++) wgmma_n256_rs<1>(acc, R + 32 + 4 * kk, dB + 2 * SL + kk * 2);
    wgmma_commit();
    bar_arrive(turn_other, 256);
    if (!CAND_EARLY) { wgmma_wait<1>(); cand_pub(); }
    wgmma_wait<0>(); refill_g2(18, 1);
    kstep(19);
    wgmma_wait<0>(); refill_g2(19, 1);
#pragma unroll 1
    for (int k4 = 20; k4 < 44; k4 += 4) {
      new_desc(k4);
#pragma unroll
      for (int s = 0; s < 4; s++) {
        kstep(k4 | s);
        if (s == 0) {
          if (w == 0) { pf_ffn((k4 >> 1) - PF2_K / 2 + 4); pf_on = pf_on && k4 >= PF2_K; }
          else {
            pf_on = k4 == XPF_K;
            pf = p.x + (grp * 128 + (t >> 1)) * 1024 + eps * 128 + (t & 1) * 64;
            pf_step = 64 * 1024;
          }
          pf += zero_here();
        }
        if (s == LATE_REFILL && k4 == 20 && warp == 4) mbar_wait(BAR(B_ALL), 0);
        if (s == 2 + LATE_REFILL && k4 == 28 && warp == 4) mbar_wait(BAR(B_ALL + 1), 0);
        if (LATE_REFILL && (k4 | s) > 20) refill_g2((k4 | s) - 1, 2);
        prefetch(s);
        wgmma_wait<0>();
        if (!LATE_REFILL) refill_g2(k4 | s, 2);
      }
    }
    new_desc(ND4);
    const int g = lane >> 2, q = lane & 3;
    const int row0 = grp * 128 + warp * 16 + g;
    uint4 ha[4], hb[4];
    kstep(44);
    if (LATE_REFILL) refill_g2(43, 2);
    uint4* hst = &p.sc->hstat[grp * 1024 + warp * 16 + g];
    if (q == (g >> 1)) { pkt_clear128(hst + eps * 128); pkt_clear128(hst + eps * 128 + 8); }
    mbar_wait(BAR(B_INFO), 0);
    uint4 wv[4];
#pragma unroll
    for (int i = 0; i < 4; i++) wv[i] = lds128(sb + ((g & 1) ? OFF_WR + (i * 4 + q) * 16 : INFO_ONES));
    const uint4 info = lds128(sb + OFF_INFO);
#pragma unroll
    for (int i = 0; i < 4; i++) { ha[i] = ldg128(p.x + row0 * 1024 + eps * 128 + q * 8 + i * 32); hb[i] = ldg128(p.x + (row0 + 8) * 1024 + eps * 128 + q * 8 + i * 32); }
    wgmma_wait<0>();
    if (tid == 128) mbar_arrive_remote(mapa(BAR(B_PEER), m ^ 1));
    uint32_t hp[32];
    bf16* op; uint4* hpub;
    uint32_t cd, ast, ald, zr;
    auto swz = [](int row) { return ((row & 1) << 2) | ((row >> 1) & 3); };
    {
      float as[64], ak[64];
      fence_regs(acc);
#pragma unroll
      for (int i = 0; i < 64; i++) asm volatile("mov.b32 %0, %1;" : "=f"(as[i]) : "f"(acc[64 + i]));
#pragma unroll
      for (int i = 0; i < 64; i++) asm volatile("mov.b32 %0, %1;" : "=f"(ak[i]) : "f"(acc[i]));
      full(45); full(46);
      bar_sync(turn_me, 256);
      wgmma_fence();
      mma_h(as, 1, 1); mma_h(as, 2, 1);
      wgmma_commit();
      bar_arrive(turn_other, 256);
      full(47);
      bar_sync(turn_me, 256);
      wgmma_fence();
      mma_h(as, 3, 1);
      wgmma_commit();
      mma_h(ak, 1, 0);
      wgmma_commit();
      bar_arrive(turn_other, 256);
      const uint32_t rx = mapa(sb + OFF_RECV + w * 16384 + t * 16, m ^ 1), rb = mapa(BAR(B_XCH + w), m ^ 1);
      mbar_wait(BAR(B_PEER), 0);
      wgmma_wait<1>();
      fence_regs(as);
      CT(6);
#pragma unroll
      for (int i = 0; i < 8; i++) {
        const float* ac = &as[8 * i];
        st_async_v4(rx + i * 2048, rb, pack_bf16(ac[0], ac[1]), pack_bf16(ac[2], ac[3]), pack_bf16(ac[4], ac[5]), pack_bf16(ac[6], ac[7]));
      }
      CT(7);
      bar_sync(turn_me, 256);
      wgmma_fence();
      mma_h(ak, 2, 0); mma_h(ak, 3, 0);
      wgmma_commit();
      if (w == 0) bar_arrive(turn_other, 256);
      op = p.out + row0 * 1024 + eps * 128 + q * 8;
      hpub = hst + eps * 128; hst += q * 256;
      cd = code_of(info.y);
      ast = sb + w * ST_BYTES + (8 * (lane >> 4) + (lane & 7)) * 128 + (((2 * wi + ((lane >> 3) & 1)) ^ swz(lane & 7)) << 4);
      ald = sb + (warp * 16 + g) * 128 + ((q ^ swz(g)) << 4);
      asm volatile("" : "+l"(op), "+l"(hpub), "+l"(hst), "+r"(cd), "+r"(ast), "+r"(ald));
      zr = zero_here();
#pragma unroll
      for (int i = 0; i < 4; i++) { ha[i].x += zr; hb[i].x += zr; asm volatile("" : "+r"(ha[i].x), "+r"(hb[i].x)); }
      ast += (uint32_t)(clock64() >> 32) & zr;
      mbar_wait(BAR(B_XCH + w), 0);
      CT(9);
#pragma unroll
      for (int i = 0; i < 8; i++) { const uint4 v = lds128(sb + OFF_RECV + w * 16384 + t * 16 + i * 2048); hp[4 * i] = v.x; hp[4 * i + 1] = v.y; hp[4 * i + 2] = v.z; hp[4 * i + 3] = v.w; }
      wgmma_wait<0>();
      fence_regs(ak);
      CT(10);
#pragma unroll
      for (int i = 0; i < 32; i++) hp[i] = badd2(pack_bf16(ak[2 * i], ak[2 * i + 1]), hp[i]);
    }
#pragma unroll
    for (int jj = 0; jj < 16; jj += 2) stsm_x4_t(ast + jj * 1024, hp[2 * jj], hp[2 * jj + 1], hp[2 * jj + 2], hp[2 * jj + 3]);
    tag = info.y;
    bar_sync(NB_BOTH, 256);
    CT(11);
    uint4 v[4];
    auto fetch = [&]() { v[0] = pkt_ld128(hst); v[1] = pkt_ld128(hst + 128); v[2] = pkt_ld128(hst + 8); v[3] = pkt_ld128(hst + 136); };
    float st[6];
    {
      uint4 ya[4], yb[4];
#pragma unroll
      for (int i = 0; i < 4; i++) {
        const uint32_t ad = (ald ^ ((i & 1) << 6)) + (i >> 1) * ST_BYTES;
        ya[i] = lds128(ad); yb[i] = lds128(ad + 1024);
      }
      fetch();
      const float z = __uint_as_float((uint32_t)(clock64() >> 32) & zr);
      float sw[2][4], qa[2][4], qb[2][4];
#pragma unroll
      for (int i = 0; i < 8; i++) { sw[i >> 2][i & 3] = i ? 0.f : z; qa[i >> 2][i & 3] = 0.f; qb[i >> 2][i & 3] = 0.f; }
#pragma unroll
      for (int i = 0; i < 4; i++) {
        ha[i] = make_uint4(badd2(ha[i].x, ya[i].x), badd2(ha[i].y, ya[i].y), badd2(ha[i].z, ya[i].z), badd2(ha[i].w, ya[i].w));
        hb[i] = make_uint4(badd2(hb[i].x, yb[i].x), badd2(hb[i].y, yb[i].y), badd2(hb[i].z, yb[i].z), badd2(hb[i].w, yb[i].w));
        mma16816(sw[0], ha[i].x, hb[i].x, ha[i].y, hb[i].y, wv[i].x, wv[i].y);
        mma16816(qa[0], ha[i].x, hb[i].x, ha[i].y, hb[i].y, ha[i].x, ha[i].y);
        mma16816(qb[0], ha[i].x, hb[i].x, ha[i].y, hb[i].y, hb[i].x, hb[i].y);
        mma16816(sw[1], ha[i].z, hb[i].z, ha[i].w, hb[i].w, wv[i].z, wv[i].w);
        mma16816(qa[1], ha[i].z, hb[i].z, ha[i].w, hb[i].w, ha[i].z, ha[i].w);
        mma16816(qb[1], ha[i].z, hb[i].z, ha[i].w, hb[i].w, hb[i].z, hb[i].w);
      }
      const uint32_t s0 = with_bit(sw[0][0] + sw[1][0], cd), s1 = with_bit((g & 1) ? qa[0][1] + qa[1][1] : qa[0][0] + qa[1][0], cd >> 1), s2 = __float_as_uint(sw[0][1] + sw[1][1]);
      const uint32_t s3 = with_bit(sw[0][2] + sw[1][2], cd), s4 = with_bit((g & 1) ? qb[0][3] + qb[1][3] : qb[0][2] + qb[1][2], cd >> 1), s5 = __float_as_uint(sw[0][3] + sw[1][3]);
      if (q == (g >> 1)) { pkt_st128(hpub, s0, s1, s2, tag); pkt_st128(hpub + 8, s3, s4, s5, tag); }
      CT(12);
      const uint32_t o1 = __shfl_sync(0xffffffffu, s1, (lane & 28) | (g >> 1)), o4 = __shfl_sync(0xffffffffu, s4, (lane & 28) | (g >> 1));
      uint32_t n = 0;
      bool more;
#pragma unroll 1
      do {
        if (2 * q == eps) { v[0] = make_uint4(s0, o1, s2, tag); v[2] = make_uint4(s3, o4, s5, tag); }
        if (2 * q + 1 == eps) { v[1] = make_uint4(s0, o1, s2, tag); v[3] = make_uint4(s3, o4, s5, tag); }
        uint32_t bad = 0;
#pragma unroll
        for (int i = 0; i < 4; i++) { chk(bad, v[i].x, cd); chk(bad, v[i].y, cd >> 1); }
        bad &= 1;
#pragma unroll
        for (int i = 0; i < 4; i++) chk(bad, v[i].w, tag);
        more = !(!__any_sync(0xffffffffu, bad)) && ++n < SPIN_LIMIT;
        if (more) { if (bad) fetch(); }
      } while (more);
      st[0] = no_bit(v[0].x) + no_bit(v[1].x); st[1] = no_bit(v[0].y) + no_bit(v[1].y); st[2] = __uint_as_float(v[0].z) + __uint_as_float(v[1].z);
      st[3] = no_bit(v[2].x) + no_bit(v[3].x); st[4] = no_bit(v[2].y) + no_bit(v[3].y); st[5] = __uint_as_float(v[2].z) + __uint_as_float(v[3].z);
    }
    CT(13);
#pragma unroll
    for (int o = 1; o < 4; o <<= 1) {
#pragma unroll
      for (int i = 0; i < 6; i++) st[i] += __shfl_xor_sync(0xffffffffu, st[i], o);
    }
    float mb[2], inv[2];
#pragma unroll
    for (int i = 0; i < 2; i++) {
      const float mu = st[3 * i] * (1.f / 1024.f);
      mb[i] = bf16r(mu);
      inv[i] = fast_rcp(ref_sd(fmaxf(st[3 * i + 1] * (1.f / 1024.f) - mu * mu, 0.f)));
    }
    {
      const int srow = key_row(info.z);
      auto put_out = [&](bf16* dst, const uint4& h, float sc, float of, bool on) {
        auto cvt = [&](uint32_t x) { return pack_bf16(fmaf(bf_lo(x), sc, of), fmaf(bf_hi(x), sc, of)); };
        asm volatile("{\n.reg .pred p;\nsetp.ne.b32 p, %5, 0;\n@p st.global.v4.b32 [%0], {%1, %2, %3, %4};\n}\n"
                     :: "l"(dst), "r"(cvt(h.x)), "r"(cvt(h.y)), "r"(cvt(h.z)), "r"(cvt(h.w)), "r"((int)on) : "memory");
      };
#pragma unroll
      for (int i = 0; i < 4; i++) {
        put_out(op + i * 32, ha[i], 1.f + inv[0], -mb[0] * inv[0], row0 != srow);
        put_out(op + 8192 + i * 32, hb[i], 1.f + inv[1], -mb[1] * inv[1], row0 + 8 != srow);
      }
    }
    CT(14);
    const uint4 cand = lds128(sb + INFO_CAND);
    uint32_t wkey = zero_here();
#pragma unroll
    for (int i = 0; i < 2; i++) {
      const uint32_t row = row0 + 8 * i, rr = row | (row << 16);
      const bool is_cand = __vcmpeq2(cand.x, rr) | __vcmpeq2(cand.y, rr) | __vcmpeq2(cand.z, rr) | __vcmpeq2(cand.w, rr);
      if (!is_cand) wkey = max(wkey, make_key(bf16r((st[3 * i + 2] - mb[i] * __uint_as_float(info.x)) * inv[i]), row));
    }
    wkey = __reduce_max_sync(0xffffffffu, wkey);
    if (eps == 0 && lane == 0) pkt_st64(&p.sc->key[grp * 8 + warp], wkey, tag);
    const bool beaten = (wkey >> 16) > (info.z >> 16);
    if (__builtin_expect(beaten, 0)) {
      const int br = key_row(wkey);
      if (br == row0 || br == row0 + 8) {
#pragma unroll
        for (int i = 0; i < 4; i++) {
          const uint4 h = br == row0 ? ha[i] : hb[i];
          uint2* dst = &p.sc->hrow[(grp * 8 + warp) * 512 + eps * 64 + i * 16 + q * 4];
          pkt_st128(dst, h.x, tag, h.y, tag); pkt_st128(dst + 2, h.z, tag, h.w, tag);
        }
      }
      __syncwarp();
    }
    uint32_t any;
    asm volatile("{\n.reg .pred p, q;\nsetp.ne.b32 p, %1, 0;\nbarrier.cta.red.or.aligned.pred q, %2, 256, p;\nselp.u32 %0, 1, 0, q;\n}\n" : "=r"(any) : "r"((int)beaten), "n"((int)NB_BOTH) : "memory");
    if (__builtin_expect(any, 0)) slow_path(p, grp, eps, tag, info.z, info.w);
  }
}

__global__ void __launch_bounds__(NTHR, 1) occupancy_probe_kernel() {}

typedef CUresult (*EncodeFn)(CUtensorMap*, CUtensorMapDataType, cuuint32_t, void*, const cuuint64_t*, const cuuint64_t*, const cuuint32_t*, const cuuint32_t*,
                             CUtensorMapInterleave, CUtensorMapSwizzle, CUtensorMapL2promotion, CUtensorMapFloatOOBfill);

static void make_tm(EncodeFn enc, CUtensorMap* tm, const void* ptr, uint64_t rows, uint64_t cols, uint32_t brows, uint32_t bcols, bool swz, bool wide) {
  cuuint64_t dims[2] = {cols, rows};
  cuuint64_t strides[1] = {cols * 2};
  cuuint32_t box[2] = {bcols, brows};
  cuuint32_t es[2] = {1, 1};
  enc(tm, CU_TENSOR_MAP_DATA_TYPE_BFLOAT16, 2, const_cast<void*>(ptr), dims, strides, box, es, CU_TENSOR_MAP_INTERLEAVE_NONE,
      swz ? CU_TENSOR_MAP_SWIZZLE_128B : CU_TENSOR_MAP_SWIZZLE_NONE, wide ? CU_TENSOR_MAP_L2_PROMOTION_L2_256B : CU_TENSOR_MAP_L2_PROMOTION_L2_128B, CU_TENSOR_MAP_FLOAT_OOB_FILL_NONE);
}

extern "C" void kernel_launch(void* const* d_in, const int* in_sizes, int n_in, void* d_out, int out_size) {
  (void)in_sizes; (void)n_in; (void)out_size;
  static EncodeFn enc = nullptr;
  static void* abT = nullptr;
  static void* sc = nullptr;
  static int map = 0;
  if (!enc) {
    void* fn = nullptr; cudaDriverEntryPointQueryResult st;
    cudaGetDriverEntryPoint("cuTensorMapEncodeTiled", &fn, cudaEnableDefault, &st);
    enc = (EncodeFn)fn;
    cudaGetSymbolAddress(&abT, g_abT);
    cudaGetSymbolAddress(&sc, g_sc);
    cudaFuncSetAttribute(fnet_moe_kernel<0>, cudaFuncAttributeMaxDynamicSharedMemorySize, SMEM_TOTAL);
    cudaFuncSetAttribute(fnet_moe_kernel<1>, cudaFuncAttributeMaxDynamicSharedMemorySize, SMEM_TOTAL);
    cudaFuncSetAttribute(occupancy_probe_kernel, cudaFuncAttributeMaxDynamicSharedMemorySize, SMEM_TOTAL);
    cudaFuncSetAttribute(occupancy_probe_kernel, cudaFuncAttributeNonPortableClusterSizeAllowed, 1);
    cudaLaunchConfig_t cfg = {};
    cfg.gridDim = dim3(128); cfg.blockDim = dim3(NTHR); cfg.dynamicSmemBytes = SMEM_TOTAL;
    cudaLaunchAttribute at[1];
    at[0].id = cudaLaunchAttributeClusterDimension; at[0].val.clusterDim.x = 16; at[0].val.clusterDim.y = 1; at[0].val.clusterDim.z = 1;
    cfg.attrs = at; cfg.numAttrs = 1;
    int ncl = 0;
    if (cudaOccupancyMaxActiveClusters(&ncl, occupancy_probe_kernel, &cfg) == cudaSuccess && ncl >= 8) map = 1;
    (void)cudaGetLastError();
  }
  Params p;
  const bf16* x = (const bf16*)d_in[0];
  make_tm(enc, &p.tmD0, d_in[3], 1024, 1024, 128, 64, true, true);
  make_tm(enc, &p.tmD1, d_in[4], 1024, 1024, 128, 64, true, true);
  make_tm(enc, &p.tmX, x, 2048, 1024, 256, 64, true, true);
  make_tm(enc, &p.tmAbS, abT, 2048, 2048, 64, 64, true, false);
  make_tm(enc, &p.tmAbL, abT, 2048, 2048, 128, 64, true, false);
  make_tm(enc, &p.tmW0, d_in[1], 2048, 2048, 128, 64, true, true);
  make_tm(enc, &p.tmW1, d_in[2], 2048, 2048, 128, 64, true, true);
  make_tm(enc, &p.tmG, d_in[7], 1024, 3584, 16, 64, false, false);
  make_tm(enc, &p.tmU, d_in[8], 1024, 3584, 16, 64, false, false);
  make_tm(enc, &p.tmDn, d_in[9], 3584, 1024, 8, 256, false, false);
  p.x = x; p.Dre = (const bf16*)d_in[3]; p.Dim = (const bf16*)d_in[4];
  p.wr = (const bf16*)d_in[6]; p.wdown = (const bf16*)d_in[9]; p.wgate = (const bf16*)d_in[7]; p.wup = (const bf16*)d_in[8]; p.Wre = (const bf16*)d_in[1]; p.Wim = (const bf16*)d_in[2];
  p.out = (bf16*)d_out; p.sc = (Scratch*)sc;
  if (map == 1) fnet_moe_kernel<1><<<NGRID, NTHR, SMEM_TOTAL>>>(p);
  else fnet_moe_kernel<0><<<NGRID, NTHR, SMEM_TOTAL>>>(p);
}
```

```cpp
#include <cuda.h>
#include <cuda_runtime.h>
#include <cuda_bf16.h>
#include <stdint.h>
#include <type_traits>

typedef __nv_bfloat16 bf16;

constexpr int NGRID = 132, NTHR = 384;
__device__ __forceinline__ int k_col(int tau, int j) {
  const int i = j < 18 ? j - 2 : j - 16;
  return j < 4 ? tau * 256 + j * 64 : ((tau + (i >> 1)) & 7) * 256 + (i & 1) * 64 + (j < 18 ? 0 : 128);
}
constexpr int A_BYTES = 128 * 64 * 2;
constexpr int B_BYTES = 256 * 64 * 2;
constexpr int ST_BYTES = A_BYTES + B_BYTES;
constexpr int OFF_AUX = 4 * ST_BYTES;
constexpr int OFF_BAR = OFF_AUX + 32768;
constexpr int OFF_XS = OFF_BAR + 256;
constexpr int OFF_WR = OFF_XS + 2048;
constexpr int OFF_REM = OFF_WR + 256;
constexpr int OFF_INFO = OFF_REM + 256;
constexpr int SMEM_TOTAL = OFF_INFO + 256;
constexpr int INFO_WSUM = OFF_INFO, INFO_TAG = OFF_INFO + 4, INFO_KEY = OFF_INFO + 8, INFO_CAND = OFF_INFO + 16, INFO_LN = OFF_INFO + 32, INFO_ONES = OFF_INFO + 48, INFO_DS = OFF_INFO + 64, INFO_DS2 = OFF_INFO + 192;
constexpr int OFF_RS = OFF_XS;
constexpr int OFF_WC = OFF_AUX;
constexpr int OFF_EXA = OFF_AUX + 4096;
constexpr int OFF_EXB = OFF_AUX + 6144;
constexpr int OFF_RECV = A_BYTES;
__host__ __device__ constexpr int off_y(int w) { return w * ST_BYTES; }
constexpr int NSRC = 112;
enum { B_FULL = 0, B_EMPTY = 4, B_LO = 5, B_ALL = 6, B_EP = 8, B_AW = 16, B_STAT = 24, B_WC = 25, B_CD = 26, B_HR = 27, B_INFO = 28, B_PEER = 29, B_XCH = 30, B_GUX = (OFF_INFO + 128 - OFF_BAR) / 8 };
enum { NB_TURN0 = 1, NB_TURN1 = 2, NB_BOTH = 3, NB_AUX = 4, NB_H = 5 };

struct Scratch;
struct Params {
  Scratch* sc; const bf16* wr; const bf16* x; const bf16* Dre; const bf16* Dim; const bf16* Wre; const bf16* Wim;
  const bf16* wgate; const bf16* wup; const bf16* wdown; bf16* out;
  CUtensorMap tmX, tmD0, tmD1, tmW0, tmW1, tmAbS, tmAbL, tmG, tmU, tmDn;
};

__device__ __align__(1024) bf16 g_abT[2048 * 2048];
struct Scratch {
  alignas(128) uint4 xz[2048];
  alignas(128) uint2 dsum[2048];
  alignas(128) uint32_t abflag[128 * 32];
  alignas(128) uint32_t abdone[128 * 2 * 32];
  alignas(128) uint2 u[4 * 512];
  alignas(128) uint2 cl[128 * 16];
  alignas(128) uint4 cpart[4 * 16 * 512];
  alignas(128) uint2 ch[8 * 512];
  alignas(128) uint4 cs[128 * 8];
  alignas(128) uint2 rdone[128];
  alignas(128) uint4 ypart[4 * NSRC * 64];
  alignas(128) uint4 hstat[16 * 8 * 128];
  alignas(128) uint2 key[128];
  alignas(128) uint2 hrow[128 * 512];
  alignas(128) uint2 fpart[8 * 1024];
  alignas(128) uint32_t epoch;
};
__device__ Scratch g_sc;

#define SPIN_LIMIT (1u << 17)
#define PF2_K 24
#define UNIT_PACE 1500
#define XPF_K 40
#define XS_DELAY 300
#define U_CLK 3700
#define XROW_PF 0
#define DROW_PF 0
#define TM_PF 0
#define SPLIT17 1
#define LO_NS 500
#define CAND_EARLY 0
#define CHAIN1 0
#define ROW_NS 400
#define W_PF 8
#define START_PF 0
#define ND0 65
#define ND1 66
#define ND2 67
#define ND3 -1
#define ND4 69
#define LATE_REFILL 0
#define HI_DELAY 0
#define HI_PACE 1200
#define LU_LATE 0
#define CS_WEAK 0
#define Z_CLK 9000
#define CP_DELAY 1500
#define CS_DELAY 800
#define YPART_DELAY 16500
__device__ __forceinline__ uint32_t smem_u32(const void* p) { return (uint32_t)__cvta_generic_to_shared(p); }
__device__ __forceinline__ uint32_t clk32() { uint32_t c; asm volatile("mov.u32 %0, %%clock;" : "=r"(c)); return c; }
__device__ __forceinline__ uint32_t zero_here() { uint64_t c; asm volatile("mov.u64 %0, %%clock64;" : "=l"(c) :: "memory"); return (uint32_t)(c >> 32) & blockIdx.y; }
__device__ __forceinline__ uint32_t uniform_zero_here() { uint32_t c; asm volatile("mov.u32 %0, %%clock;" : "=r"(c) :: "memory"); return c & blockIdx.y; }
__device__ __forceinline__ void wait_clk(uint32_t t0, uint32_t dt) {
  asm volatile("{\n.reg .pred p;\n.reg .u32 c;\nLOOP:\nmov.u32 c, %%clock;\nsub.u32 c, c, %0;\nsetp.lt.u32 p, c, %1;\n@p nanosleep.u32 100;\n@p bra LOOP;\n}\n" :: "r"(t0), "r"(dt) : "memory");
}
__device__ __forceinline__ void mbar_init(uint32_t bar, uint32_t cnt) { asm volatile("mbarrier.init.shared::cta.b64 [%0], %1;" :: "r"(bar), "r"(cnt) : "memory"); }
__device__ __forceinline__ void mbar_expect_tx(uint32_t bar, uint32_t bytes) { asm volatile("mbarrier.arrive.expect_tx.shared::cta.b64 _, [%0], %1;" :: "r"(bar), "r"(bytes) : "memory"); }
__device__ __forceinline__ void mbar_arrive(uint32_t bar) { asm volatile("mbarrier.arrive.shared::cta.b64 _, [%0];" :: "r"(bar) : "memory"); }
__device__ __forceinline__ void mbar_arrive_remote(uint32_t cluster_addr) { asm volatile("mbarrier.arrive.shared::cluster.b64 _, [%0];" :: "r"(cluster_addr) : "memory"); }
__device__ __forceinline__ void mbar_wait(uint32_t bar, uint32_t parity) {
  asm volatile("{\n.reg .pred p;\nLOOP:\nmbarrier.try_wait.parity.shared::cta.b64 p, [%0], %1;\n@!p bra LOOP;\n}\n" :: "r"(bar), "r"(parity) : "memory");
}
__device__ __forceinline__ void tma_load_2d(uint32_t dst, const CUtensorMap* tm, uint32_t bar, int c0, int c1) {
  asm volatile("cp.async.bulk.tensor.2d.shared::cluster.global.mbarrier::complete_tx::bytes [%0], [%1, {%3, %4}], [%2];"
    :: "r"(dst), "l"(tm), "r"(bar), "r"(c0), "r"(c1) : "memory");
}
__device__ __forceinline__ void tma_load_2d_hint(uint32_t dst, const CUtensorMap* tm, uint32_t bar, int c0, int c1, uint64_t pol) {
  asm volatile("cp.async.bulk.tensor.2d.shared::cluster.global.mbarrier::complete_tx::bytes.L2::cache_hint [%0], [%1, {%3, %4}], [%2], %5;"
    :: "r"(dst), "l"(tm), "r"(bar), "r"(c0), "r"(c1), "l"(pol) : "memory");
}
__device__ __forceinline__ uint64_t policy_evict_first() { uint64_t p; asm volatile("createpolicy.fractional.L2::evict_first.b64 %0, 1.0;" : "=l"(p)); return p; }
__device__ __forceinline__ void tma_store_2d(const CUtensorMap* tm, uint32_t src, int c0, int c1) {
  asm volatile("cp.async.bulk.tensor.2d.global.shared::cta.bulk_group [%0, {%2, %3}], [%1];" :: "l"(tm), "r"(src), "r"(c0), "r"(c1) : "memory");
}
__device__ __forceinline__ void bulk_load(uint32_t dst, const void* src, uint32_t bytes, uint32_t bar) {
  asm volatile("cp.async.bulk.shared::cluster.global.mbarrier::complete_tx::bytes [%0], [%1], %2, [%3];" :: "r"(dst), "l"(src), "r"(bytes), "r"(bar) : "memory");
}
__device__ __forceinline__ void prefetch_l2(const void* p) { asm volatile("prefetch.global.L2 [%0];" :: "l"(p)); }
__device__ __forceinline__ void bulk_commit() { asm volatile("cp.async.bulk.commit_group;" ::: "memory"); }
__device__ __forceinline__ void bulk_wait_all() { asm volatile("cp.async.bulk.wait_group 0;" ::: "memory"); }
__device__ __forceinline__ void fence_async_smem() { asm volatile("fence.proxy.async.shared::cta;" ::: "memory"); }
__device__ __forceinline__ void wgmma_fence() { asm volatile("wgmma.fence.sync.aligned;" ::: "memory"); }
__device__ __forceinline__ void wgmma_commit() { asm volatile("wgmma.commit_group.sync.aligned;" ::: "memory"); }
template<int N> __device__ __forceinline__ void wgmma_wait() { asm volatile("wgmma.wait_group.sync.aligned %0;" :: "n"(N) : "memory"); }
__device__ __forceinline__ void bar_sync(int id, int n) { asm volatile("bar.sync %0, %1;" :: "r"(id), "r"(n) : "memory"); }
__device__ __forceinline__ void bar_arrive(int id, int n) { asm volatile("bar.arrive %0, %1;" :: "r"(id), "r"(n) : "memory"); }
__device__ __forceinline__ void cluster_wait() { asm volatile("barrier.cluster.wait.aligned;" ::: "memory"); }
template<int R> __device__ __forceinline__ void reg_inc() { asm volatile("setmaxnreg.inc.sync.aligned.u32 %0;" :: "n"(R)); }
template<int R> __device__ __forceinline__ void reg_dec() { asm volatile("setmaxnreg.dec.sync.aligned.u32 %0;" :: "n"(R)); }
__device__ __forceinline__ bool elect_one() {
  uint32_t p;
  asm volatile("{\n.reg .pred q;\nelect.sync _|q, 0xffffffff;\nselp.u32 %0, 1, 0, q;\n}\n" : "=r"(p));
  return p != 0;
}
__device__ __forceinline__ uint32_t mapa(uint32_t addr, uint32_t cta) { uint32_t r; asm volatile("mapa.shared::cluster.u32 %0, %1, %2;" : "=r"(r) : "r"(addr), "r"(cta)); return r; }
__device__ __forceinline__ void st_async_v4(uint32_t addr, uint32_t bar, uint32_t a, uint32_t b, uint32_t c, uint32_t d) {
  asm volatile("st.async.weak.shared::cluster.mbarrier::complete_tx::bytes.v4.b32 [%0], {%2, %3, %4, %5}, [%1];" :: "r"(addr), "r"(bar), "r"(a), "r"(b), "r"(c), "r"(d) : "memory");
}
__device__ __forceinline__ void st_async_b32(uint32_t addr, uint32_t bar, uint32_t a) {
  asm volatile("st.async.weak.shared::cluster.mbarrier::complete_tx::bytes.b32 [%0], %2, [%1];" :: "r"(addr), "r"(bar), "r"(a) : "memory");
}
__device__ __forceinline__ void stsm_x4(uint32_t addr, uint32_t a, uint32_t b, uint32_t c, uint32_t d) {
  asm volatile("stmatrix.sync.aligned.m8n8.x4.shared.b16 [%0], {%1, %2, %3, %4};" :: "r"(addr), "r"(a), "r"(b), "r"(c), "r"(d) : "memory");
}
__device__ __forceinline__ void stsm_x4_t(uint32_t addr, uint32_t a, uint32_t b, uint32_t c, uint32_t d) {
  asm volatile("stmatrix.sync.aligned.m8n8.x4.trans.shared.b16 [%0], {%1, %2, %3, %4};" :: "r"(addr), "r"(a), "r"(b), "r"(c), "r"(d) : "memory");
}
__device__ __forceinline__ uint4 lds128(uint32_t addr) { uint4 v; asm volatile("ld.shared.v4.b32 {%0, %1, %2, %3}, [%4];" : "=r"(v.x), "=r"(v.y), "=r"(v.z), "=r"(v.w) : "r"(addr) : "memory"); return v; }
extern __shared__ __align__(1024) uint8_t smem_raw[];
template<class T> __device__ __forceinline__ T& SM(int off) { return *reinterpret_cast<T*>(smem_raw + off); }
__device__ __forceinline__ uint4 ldg_nc128(const void* p) { uint4 v; asm volatile("ld.global.nc.v4.b32 {%0, %1, %2, %3}, [%4];" : "=r"(v.x), "=r"(v.y), "=r"(v.z), "=r"(v.w) : "l"(p)); return v; }
__device__ __forceinline__ uint4 ldg128(const void* p) { uint4 v; asm volatile("ld.global.L1::no_allocate.v4.b32 {%0, %1, %2, %3}, [%4];" : "=r"(v.x), "=r"(v.y), "=r"(v.z), "=r"(v.w) : "l"(p) : "memory"); return v; }
__device__ __forceinline__ void pkt_st128(void* p, uint32_t a, uint32_t b, uint32_t c, uint32_t d) {
  asm volatile("{\n.reg .b128 v;\n.reg .b64 lo, hi;\nmov.b64 lo, {%1, %2};\nmov.b64 hi, {%3, %4};\nmov.b128 v, {lo, hi};\nst.relaxed.gpu.global.b128 [%0], v;\n}\n"
    :: "l"(p), "r"(a), "r"(b), "r"(c), "r"(d) : "memory");
}
__device__ __forceinline__ uint4 pkt_ld128(const void* p) {
  uint4 r;
  asm volatile("{\n.reg .b128 v;\n.reg .b64 lo, hi;\nld.relaxed.gpu.global.b128 v, [%4];\nmov.b128 {lo, hi}, v;\nmov.b64 {%0, %1}, lo;\nmov.b64 {%2, %3}, hi;\n}\n"
    : "=r"(r.x), "=r"(r.y), "=r"(r.z), "=r"(r.w) : "l"(p) : "memory");
  return r;
}
__device__ __forceinline__ void pkt_st64(void* p, uint32_t a, uint32_t b) {
  asm volatile("{\n.reg .b64 v;\nmov.b64 v, {%1, %2};\nst.relaxed.gpu.global.b64 [%0], v;\n}\n" :: "l"(p), "r"(a), "r"(b) : "memory");
}
__device__ __forceinline__ uint2 pkt_ld64(const void* p) {
  uint2 r;
  asm volatile("{\n.reg .b64 v;\nld.relaxed.gpu.global.b64 v, [%2];\nmov.b64 {%0, %1}, v;\n}\n" : "=r"(r.x), "=r"(r.y) : "l"(p) : "memory");
  return r;
}
__device__ __forceinline__ void pkt_clear128(void* p) { pkt_st128(p, 0, 0, 0, 0); }
__device__ __forceinline__ uint32_t ld_relaxed32(const void* p) { uint32_t v; asm volatile("ld.relaxed.gpu.global.b32 %0, [%1];" : "=r"(v) : "l"(p) : "memory"); return v; }
__device__ __forceinline__ uint32_t ld_acquire32(const void* p) { uint32_t v; asm volatile("ld.acquire.gpu.global.b32 %0, [%1];" : "=r"(v) : "l"(p) : "memory"); return v; }
__device__ __forceinline__ void st_relaxed32(void* p, uint32_t v) { asm volatile("st.relaxed.gpu.global.b32 [%0], %1;" :: "l"(p), "r"(v) : "memory"); }
__device__ __forceinline__ uint32_t poll64(const void* p, uint32_t tag, int ns) {
  uint2 v; uint32_t n = 0;
  bool more;
#pragma unroll 1
  do {
    v = pkt_ld64(p);
    more = !(v.y == tag) && ++n < SPIN_LIMIT;
    if (more) { __nanosleep(ns); }
  } while (more);
  return v.x;
}
__device__ __forceinline__ uint32_t poll64_warp(const void* p, uint32_t tag, int ns) {
  uint2 v; uint32_t n = 0;
  bool more;
#pragma unroll 1
  do {
    v = pkt_ld64(p);
    more = !(__all_sync(0xffffffffu, v.y == tag)) && ++n < SPIN_LIMIT;
    if (more) { __nanosleep(ns); }
  } while (more);
  return v.x;
}
__device__ __forceinline__ uint32_t code_of(uint32_t tag) { return tag % 3u + 1u; }
__device__ __forceinline__ uint32_t with_bit(uint32_t v, uint32_t bit) { return (v & ~1u) | (bit & 1u); }
__device__ __forceinline__ uint32_t with_bit(float v, uint32_t bit) { return with_bit(__float_as_uint(v), bit); }
__device__ __forceinline__ float no_bit(uint32_t v) { return __uint_as_float(v & ~1u); }
__device__ __forceinline__ void chk(uint32_t& bad, uint32_t a, uint32_t want) { bad |= a ^ want; asm("" : "+r"(bad)); }
__device__ __forceinline__ void chk_code(uint32_t& bad, const uint4& v, uint32_t c0, uint32_t c1) { chk(bad, v.x, c0); chk(bad, v.y, c1); chk(bad, v.z, c0); chk(bad, v.w, c1); }
__device__ __forceinline__ uint32_t pack_bf16(float lo, float hi) { uint32_t r; asm("cvt.rn.bf16x2.f32 %0, %1, %2;" : "=r"(r) : "f"(hi), "f"(lo)); return r; }
__device__ __forceinline__ float bf_lo(uint32_t v) { return __uint_as_float(v << 16); }
__device__ __forceinline__ float bf_hi(uint32_t v) { return __uint_as_float(v & 0xFFFF0000u); }
__device__ __forceinline__ float bf16r(float x) { return __uint_as_float(pack_bf16(0.f, x)); }
__device__ __forceinline__ void st_bf16(bf16* p, float x) { *reinterpret_cast<uint16_t*>(p) = (uint16_t)pack_bf16(x, 0.f); }
__device__ __forceinline__ float fast_rcp(float x) { float r; asm("rcp.approx.f32 %0, %1;" : "=f"(r) : "f"(x)); return r; }
__device__ __forceinline__ float ldbf(const bf16* p) { return __bfloat162float(*p); }
__device__ __forceinline__ uint32_t badd2(uint32_t a, uint32_t b) { uint32_t r; asm("add.rn.bf16x2 %0, %1, %2;" : "=r"(r) : "r"(a), "r"(b)); return r; }
__device__ __forceinline__ uint32_t bfma2(uint32_t a, uint32_t b, uint32_t c) { uint32_t r; asm("fma.rn.bf16x2 %0, %1, %2, %3;" : "=r"(r) : "r"(a), "r"(b), "r"(c)); return r; }
__device__ __forceinline__ float warp_sum(float v) {
#pragma unroll
  for (int o = 16; o > 0; o >>= 1) v += __shfl_xor_sync(0xffffffffu, v, o);
  return v;
}
template<int N> __device__ __forceinline__ void fold(float* v, int o, int lane) {
  const bool up = lane & o;
#pragma unroll
  for (int i = 0; i < N / 2; i++) {
    const float keep = up ? v[N / 2 + i] : v[i], send = up ? v[i] : v[N / 2 + i];
    v[i] = keep + __shfl_xor_sync(0xffffffffu, send, o);
  }
}
__device__ __forceinline__ uint32_t make_key(float r_bf, int row) {
  const uint32_t u = __float_as_uint(r_bf);
  return (((u & 0x80000000u) ? ~u : (u | 0x80000000u)) & 0xFFFF0000u) | (0xFFFFu - (uint32_t)row);
}
__device__ __forceinline__ int key_row(uint32_t key) { return (0xFFFF - (int)(key & 0xFFFFu)) & 2047; }
__device__ __forceinline__ float key_val(uint32_t key) { const uint32_t o = key & 0xFFFF0000u; return __uint_as_float((o & 0x80000000u) ? (o & 0x7FFFFFFFu) : (~o & 0xFFFF0000u)); }
__device__ __forceinline__ float ref_sd(float var) { float r; asm("sqrt.approx.f32 %0, %1;" : "=f"(r) : "f"(bf16r(bf16r(var) + 1e-5f))); return bf16r(r); }
__device__ __forceinline__ uint64_t make_desc(uint32_t addr) { return (uint64_t)((addr & 0x3FFFF) >> 4) | ((uint64_t)64 << 32) | ((uint64_t)1 << 62); }
__device__ __forceinline__ uint64_t make_desc_noswz(uint32_t addr) { return (uint64_t)((addr & 0x3FFFF) >> 4) | ((uint64_t)8 << 32); }
#define ACC8(d, o) "+f"(d[o]), "+f"(d[o + 1]), "+f"(d[o + 2]), "+f"(d[o + 3]), "+f"(d[o + 4]), "+f"(d[o + 5]), "+f"(d[o + 6]), "+f"(d[o + 7])
#define ACC64(d, o) ACC8(d, o), ACC8(d, o + 8), ACC8(d, o + 16), ACC8(d, o + 24), ACC8(d, o + 32), ACC8(d, o + 40), ACC8(d, o + 48), ACC8(d, o + 56)
#define REGS64 "%0, %1, %2, %3, %4, %5, %6, %7, %8, %9, %10, %11, %12, %13, %14, %15, %16, %17, %18, %19, %20, %21, %22, %23, %24, %25, %26, %27, %28, %29, %30, %31, " \
    "%32, %33, %34, %35, %36, %37, %38, %39, %40, %41, %42, %43, %44, %45, %46, %47, %48, %49, %50, %51, %52, %53, %54, %55, %56, %57, %58, %59, %60, %61, %62, %63"
#define REGS128 REGS64 ", %64, %65, %66, %67, %68, %69, %70, %71, %72, %73, %74, %75, %76, %77, %78, %79, %80, %81, %82, %83, %84, %85, %86, %87, %88, %89, %90, %91, %92, %93, %94, %95, " \
    "%96, %97, %98, %99, %100, %101, %102, %103, %104, %105, %106, %107, %108, %109, %110, %111, %112, %113, %114, %115, %116, %117, %118, %119, %120, %121, %122, %123, %124, %125, %126, %127"
__device__ __forceinline__ void wgmma_n256(float (&d)[128], uint64_t da, uint64_t db) {
  asm volatile("wgmma.mma_async.sync.aligned.m64n256k16.f32.bf16.bf16 {" REGS128 "}, %128, %129, 1, 1, 1, 0, 0;\n"
    : ACC64(d, 0), ACC64(d, 64) : "l"(da), "l"(db));
}
#define OUT8(d, o) "=f"(d[o]), "=f"(d[o + 1]), "=f"(d[o + 2]), "=f"(d[o + 3]), "=f"(d[o + 4]), "=f"(d[o + 5]), "=f"(d[o + 6]), "=f"(d[o + 7])
#define OUT64(d, o) OUT8(d, o), OUT8(d, o + 8), OUT8(d, o + 16), OUT8(d, o + 24), OUT8(d, o + 32), OUT8(d, o + 40), OUT8(d, o + 48), OUT8(d, o + 56)
__device__ __forceinline__ void wgmma_n256_rs_init(float (&d)[128], const uint32_t* a, uint64_t db) {
  asm volatile("wgmma.mma_async.sync.aligned.m64n256k16.f32.bf16.bf16 {" REGS128 "}, {%128, %129, %130, %131}, %132, 0, 1, 1, 0;\n"
    : OUT64(d, 0), OUT64(d, 64) : "r"(a[0]), "r"(a[1]), "r"(a[2]), "r"(a[3]), "l"(db));
}
template<int ACCUM> __device__ __forceinline__ void wgmma_n256_rs(float (&d)[128], const uint32_t* a, uint64_t db) {
  asm volatile("wgmma.mma_async.sync.aligned.m64n256k16.f32.bf16.bf16 {" REGS128 "}, {%128, %129, %130, %131}, %132, %133, 1, 1, 0;\n"
    : ACC64(d, 0), ACC64(d, 64) : "r"(a[0]), "r"(a[1]), "r"(a[2]), "r"(a[3]), "l"(db), "n"(ACCUM));
}
template<int ACCUM> __device__ __forceinline__ void wgmma_n8_rs(float (&d)[4], const uint32_t* a, uint64_t db) {
  asm volatile("wgmma.mma_async.sync.aligned.m64n8k16.f32.bf16.bf16 {%0, %1, %2, %3}, {%4, %5, %6, %7}, %8, %9, 1, 1, 0;\n"
    : "+f"(d[0]), "+f"(d[1]), "+f"(d[2]), "+f"(d[3]) : "r"(a[0]), "r"(a[1]), "r"(a[2]), "r"(a[3]), "l"(db), "n"(ACCUM));
}
__device__ __forceinline__ void wgmma_n8(float (&d)[4], uint64_t da, uint64_t db) {
  asm volatile("wgmma.mma_async.sync.aligned.m64n8k16.f32.bf16.bf16 {%0, %1, %2, %3}, %4, %5, 1, 1, 1, 0, 0;\n"
    : "+f"(d[0]), "+f"(d[1]), "+f"(d[2]), "+f"(d[3]) : "l"(da), "l"(db));
}
__device__ __forceinline__ void wgmma_n128(float (&d)[64], uint64_t da, uint64_t db) {
  asm volatile("wgmma.mma_async.sync.aligned.m64n128k16.f32.bf16.bf16 {" REGS64 "}, %64, %65, 1, 1, 1, 0, 0;\n" : ACC64(d, 0) : "l"(da), "l"(db));
}
template<int N> __device__ __forceinline__ void fence_regs(float (&d)[N]) {
#pragma unroll
  for (int i = 0; i < N; i++) asm volatile("" : "+f"(d[i]) :: "memory");
}
__device__ __forceinline__ void mma16816(float (&c)[4], uint32_t a0, uint32_t a1, uint32_t a2, uint32_t a3, uint32_t b0, uint32_t b1) {
  asm volatile("mma.sync.aligned.m16n8k16.row.col.f32.bf16.bf16.f32 {%0, %1, %2, %3}, {%4, %5, %6, %7}, {%8, %9}, {%0, %1, %2, %3};"
               : "+f"(c[0]), "+f"(c[1]), "+f"(c[2]), "+f"(c[3]) : "r"(a0), "r"(a1), "r"(a2), "r"(a3), "r"(b0), "r"(b1));
}
__device__ __forceinline__ void fma8(float* acc, const uint4& v, float x) {
  acc[0] = fmaf(bf_lo(v.x), x, acc[0]); acc[1] = fmaf(bf_hi(v.x), x, acc[1]); acc[2] = fmaf(bf_lo(v.y), x, acc[2]); acc[3] = fmaf(bf_hi(v.y), x, acc[3]);
  acc[4] = fmaf(bf_lo(v.z), x, acc[4]); acc[5] = fmaf(bf_hi(v.z), x, acc[5]); acc[6] = fmaf(bf_lo(v.w), x, acc[6]); acc[7] = fmaf(bf_hi(v.w), x, acc[7]);
}
template<int PITCH> __device__ __forceinline__ void gemv8x8(float (&acc)[8], uint32_t addr, const float (&x)[8]) {
  uint4 v[2][2];
  v[0][0] = lds128(addr); v[0][1] = lds128(addr + PITCH);
#pragma unroll
  for (int b = 0; b < 4; b++) {
    if (b < 3) { v[(b + 1) & 1][0] = lds128(addr + (2 * b + 2) * PITCH); v[(b + 1) & 1][1] = lds128(addr + (2 * b + 3) * PITCH); }
    acc[0] += __uint_as_float(zero_here());
    fma8(acc, v[b & 1][0], x[2 * b]); fma8(acc, v[b & 1][1], x[2 * b + 1]);
  }
}
__device__ __forceinline__ float swiglu(float g, float u) {
  g = bf16r(g); u = bf16r(u);
  return bf16r(bf16r(g * fast_rcp(1.f + __expf(-g))) * u);
}

#define CT(slot) do {} while (0)
#define TIM(slot) do {} while (0)

constexpr int H_BUF0 = 0, H_BUF1 = 16384, H_RED = 32768, H_KEYS = H_RED + 1024, H_ROW = H_KEYS + 1024, H_ACT = H_ROW + 8192, H_PART = H_ACT + 4096;
__device__ __forceinline__ void hsync() { bar_sync(NB_H, 256); }
template<int N> __device__ __forceinline__ void block_sum(float (&v)[N], int warp, int lane) {
#pragma unroll
  for (int i = 0; i < N; i++) v[i] = warp_sum(v[i]);
  hsync();
  if (lane == 0) {
#pragma unroll
    for (int i = 0; i < N; i++) SM<float>(H_RED + (i * 8 + warp) * 4) = v[i];
  }
  hsync();
#pragma unroll
  for (int i = 0; i < N; i++) {
    const float4 a = SM<float4>(H_RED + i * 32), b = SM<float4>(H_RED + i * 32 + 16);
    v[i] = ((a.x + a.y) + (a.z + a.w)) + ((b.x + b.y) + (b.z + b.w));
  }
}
__device__ __forceinline__ void fft_first(int j, float2 v0, float2 v1, float2 v2, float2 v3) {
  const float2 a = make_float2(v0.x + v2.x, v0.y + v2.y), b = make_float2(v0.x - v2.x, v0.y - v2.y);
  const float2 c = make_float2(v1.x + v3.x, v1.y + v3.y), d = make_float2(v1.y - v3.y, v3.x - v1.x);
  SM<float4>(H_BUF1 + j * 32) = make_float4(a.x + c.x, a.y + c.y, b.x + d.x, b.y + d.y);
  SM<float4>(H_BUF1 + j * 32 + 16) = make_float4(a.x - c.x, a.y - c.y, b.x - d.x, b.y - d.y);
}
template<int NB> __device__ __forceinline__ void fft_passes(int tid) {
  constexpr int q = 256 * NB;
#pragma unroll 1
  for (int ps = 1; ps < 5; ps++) {
    const int ns = 1 << (2 * ps), k = tid & (ns - 1);
    float s1, c1;
    __sincosf(-1.57079632679f * __fdividef((float)k, (float)ns), &s1, &c1);
    const float c2 = c1 * c1 - s1 * s1, s2 = 2.f * c1 * s1, c3 = c1 * c2 - s1 * s2, s3 = c1 * s2 + s1 * c2;
    hsync();
#pragma unroll
    for (int i = 0; i < NB; i++) {
      const int j = tid + 256 * i;
      const float2* in = &SM<float2>((ps & 1) ? H_BUF1 : H_BUF0);
      float2* o = &SM<float2>((ps & 1) ? H_BUF0 : H_BUF1) + (j - k) * 4 + k;
      const float2 v0 = in[j], x1 = in[j + q], x2 = in[j + 2 * q], x3 = in[j + 3 * q];
      const float2 v1 = make_float2(x1.x * c1 - x1.y * s1, x1.x * s1 + x1.y * c1);
      const float2 v2 = make_float2(x2.x * c2 - x2.y * s2, x2.x * s2 + x2.y * c2);
      const float2 v3 = make_float2(x3.x * c3 - x3.y * s3, x3.x * s3 + x3.y * c3);
      const float2 a = make_float2(v0.x + v2.x, v0.y + v2.y), b = make_float2(v0.x - v2.x, v0.y - v2.y);
      const float2 c = make_float2(v1.x + v3.x, v1.y + v3.y), d = make_float2(v1.y - v3.y, v3.x - v1.x);
      o[0] = make_float2(a.x + c.x, a.y + c.y); o[ns] = make_float2(b.x + d.x, b.y + d.y);
      o[2 * ns] = make_float2(a.x - c.x, a.y - c.y); o[3 * ns] = make_float2(b.x - d.x, b.y - d.y);
    }
  }
  hsync();
}
template<int NR> __device__ __forceinline__ void ln_rows(const float (&h)[NR][4], float (&hn)[NR][4], int warp, int lane) {
  float s[NR], q[NR];
#pragma unroll
  for (int i = 0; i < NR; i++) s[i] = (h[i][0] + h[i][1]) + (h[i][2] + h[i][3]);
  block_sum(s, warp, lane);
#pragma unroll
  for (int i = 0; i < NR; i++) {
    s[i] *= 1.f / 1024.f; q[i] = 0.f;
#pragma unroll
    for (int z = 0; z < 4; z++) q[i] = fmaf(h[i][z] - s[i], h[i][z] - s[i], q[i]);
  }
  block_sum(q, warp, lane);
#pragma unroll
  for (int i = 0; i < NR; i++) {
    const float mb = bf16r(s[i]), inv = fast_rcp(ref_sd(q[i] * (1.f / 1024.f)));
#pragma unroll
    for (int z = 0; z < 4; z++) hn[i][z] = bf16r(bf16r(h[i][z] - mb) * inv);
  }
}
__device__ __forceinline__ float routed_out(float h, float hn, float y, float r) {
  const float sig = bf16r(fast_rcp(1.f + __expf(-r)));
  return h + bf16r(hn + bf16r(bf16r(y) * sig));
}

__device__ __forceinline__ void helper_cta(const Params& p, const int hi, const uint32_t t_entry) {
  const int tid = threadIdx.x, warp = tid >> 5, lane = tid & 31;
  const float w0 = ldbf(p.wr + tid), w1 = ldbf(p.wr + tid + 256), w2 = ldbf(p.wr + tid + 512), w3 = ldbf(p.wr + tid + 768), wf = ldbf(p.wr);
  const uint32_t tag = ld_relaxed32(&p.sc->epoch) + 1;
  pkt_clear128(&p.sc->u[hi * 512 + tid * 2]);
  if (tid == 0 && w0 != 123.f) TIM(12);
  fft_first(tid, make_float2(w0, 0.f), make_float2(w1, 0.f), make_float2(w2, 0.f), make_float2(w3, 0.f));
  fft_passes<1>(tid);
  const uint32_t c0 = code_of(tag), c1 = c0 >> 1;
  {
    const float off = wf - SM<float>(H_BUF1) * (1.f / 1024.f);
    const float4 v = SM<float4>(H_BUF1 + tid * 32), u = SM<float4>(H_BUF1 + tid * 32 + 16);
    pkt_st128(&p.sc->u[hi * 512 + ((tid & 192) + (tid & 1) * 32 + ((tid >> 1) & 31)) * 2], with_bit(pack_bf16((tid ? v.x : 0.f) - off, v.z - off), c0), with_bit(pack_bf16(v.y, v.w), c1),
              with_bit(pack_bf16(u.x - off, u.z - off), c0), with_bit(pack_bf16(u.y, u.w), c1));
    if (tid < 64) pkt_clear128(&p.sc->cl[(hi * 32 + (tid >> 1)) * 16 + (tid & 1) * 2]);
    hsync();
  }
  if (tid == 0) TIM(0);
  {
    float tw[8];
#pragma unroll
    for (int i = 0; i < 4; i++) __sincosf((float)(tid + 256 * i) * (-6.28318530718f / 2048.f), &tw[2 * i], &tw[2 * i + 1]);
    wait_clk(t_entry, Z_CLK);
    uint2 z[8]; uint32_t n = 0;
    bool more;
#pragma unroll 1
    do {
      uint32_t bad = 0;
#pragma unroll
      for (int i = 0; i < 8; i++) z[i] = pkt_ld64(reinterpret_cast<const uint2*>(&p.sc->xz[tid]) + 512 * i + 1);
#pragma unroll
      for (int i = 0; i < 8; i++) chk(bad, z[i].y, tag);
      more = !(!bad) && ++n < SPIN_LIMIT;
      if (more) { __nanosleep(150); }
    } while (more);
#pragma unroll
    for (int i = 0; i < 2; i++)
      fft_first(tid + 256 * i, make_float2(bf_lo(z[i].x), bf_hi(z[i].x)), make_float2(bf_lo(z[i + 2].x), bf_hi(z[i + 2].x)),
                make_float2(bf_lo(z[i + 4].x), bf_hi(z[i + 4].x)), make_float2(bf_lo(z[i + 6].x), bf_hi(z[i + 6].x)));
    if (tid == 0) TIM(7);
    fft_passes<2>(tid);
    if (tid == 0) TIM(1);
    uint32_t k8[8];
#pragma unroll
    for (int i = 0; i < 4; i++) {
      const int k = tid + 256 * i;
      const float2 v0 = SM<float2>(H_BUF1 + k * 8), v1 = SM<float2>(H_BUF1 + (k + 1024) * 8);
      const float w = v1.x * tw[2 * i + 1] - v1.y * tw[2 * i];
      const uint32_t a = __float_as_uint(v0.x + w), b = __float_as_uint(v0.x - w);
      k8[2 * i] = (((a & 0x80000000u) ? ~a : (a | 0x80000000u)) & ~2047u) | k;
      k8[2 * i + 1] = (((b & 0x80000000u) ? ~b : (b | 0x80000000u)) & ~2047u) | (k + 1024);
    }
    uint32_t lim = 0xFFFFFFFFu;
#pragma unroll 1
    for (int r = 0; r < 4; r++) {
      uint32_t mx = 0;
#pragma unroll
      for (int i = 0; i < 8; i++) mx = max(mx, k8[i] <= lim ? k8[i] : 0u);
      mx = __reduce_max_sync(0xffffffffu, mx);
      if (lane == 0) SM<uint32_t>(H_KEYS + (warp * 4 + r) * 4) = mx;
      lim = mx - 1;
    }
    hsync();
    if (tid < 32) {
      const uint32_t me = SM<uint32_t>(H_KEYS + tid * 4);
      int rank = 0;
#pragma unroll
      for (int i = 0; i < 8; i++) { const uint4 o = SM<uint4>(H_KEYS + i * 16); rank += (o.x > me) + (o.y > me) + (o.z > me) + (o.w > me); }
      if (rank < 8) SM<uint16_t>(H_KEYS + 256 + rank * 2) = me & 2047u;
    }
    hsync();
    if (tid >= 128) pkt_st64(&p.sc->cl[(hi * 32 + ((tid - 128) >> 2)) * 16 + (tid & 3)], SM<uint32_t>(H_KEYS + 256 + (tid & 3) * 4), tag);
  }
  const uint32_t cpair = SM<uint32_t>(H_KEYS + 256 + hi * 4);
  const int ca = cpair & 0xFFFF, cb = cpair >> 16;
  if (tid < 128) prefetch_l2(((tid & 32) ? p.Wim : p.Wre) + (size_t)((tid & 64) ? cb : ca) * 2048 + lane * 64);
  if (tid == 0) TIM(2);
}

__device__ __forceinline__ void slow_path(const Params& p, int grp, int eps, uint32_t tag, uint32_t key, int win, float mb, float inv) {
  const int tid = threadIdx.x + zero_here(), warp = tid >> 5, lane = tid & 31;
  uint32_t best = __reduce_max_sync(0xffffffffu, poll64(&p.sc->key[tid & 127], tag, 200));
  if (lane == 0) SM<uint32_t>(H_KEYS + warp * 4) = best;
  hsync();
  { const uint4 b4 = SM<uint4>(H_KEYS); best = max(max(b4.x, b4.y), max(b4.z, b4.w)); }
  const int tw = key_row(best), col = eps * 128 + (tid & 127);
  if ((tw >> 7) != grp) return;
  if (tid < 128) {
    const int pos = (col >> 4) * 8 + (col & 7);
    const uint32_t a = poll64(&p.sc->ch[win * 512 + pos], tag, 100);
    const float hc = (col & 8) ? bf_hi(a) : bf_lo(a);
    poll64(&p.sc->rdone[col >> 3], tag, 100);
    st_bf16(p.out + key_row(key) * 1024 + col, hc + bf16r(bf16r(hc - mb) * inv));
  }
  const uint32_t h0 = poll64(&p.sc->hrow[(tw >> 4) * 512 + 2 * tid], tag, 100), h1 = poll64(&p.sc->hrow[(tw >> 4) * 512 + 2 * tid + 1], tag, 100);
  float h[1][4] = {{bf_lo(h0), bf_hi(h0), bf_lo(h1), bf_hi(h1)}}, hn[1][4];
  ln_rows<1>(h, hn, warp, lane);
  SM<float4>(H_ROW + tid * 16) = make_float4(hn[0][0], hn[0][1], hn[0][2], hn[0][3]);
  SM<float4>(H_ROW + 4096 + tid * 16) = make_float4(h[0][0], h[0][1], h[0][2], h[0][3]);
  hsync();
#pragma unroll 1
  for (int ph = 0; ph < 2; ph++) {
    const int part = min(tid / 56, 3), fh = tid >> 7, len = ph ? 224 : 512, ld = ph ? 1024 : 3584;
    const bf16* wp = ph ? p.wdown + (eps * 448 + fh * 224) * 1024 + (tid & 127) * 8
                        : ((part & 1) ? p.wup : p.wgate) + (part >> 1) * 512 * 3584 + eps * 448 + min(tid - part * 56, 55) * 8;
    const int xo = ph ? H_ACT + fh * 224 * 4 : H_ROW + (part >> 1) * 2048;
    float acc[8] = {0.f, 0.f, 0.f, 0.f, 0.f, 0.f, 0.f, 0.f};
#pragma unroll 8
    for (int d = 0; d < (len & ~7); d++) fma8(acc, ldg_nc128(wp + d * ld), SM<float>(xo + d * 4));
    SM<float4>(H_PART + tid * 32) = make_float4(acc[0], acc[1], acc[2], acc[3]);
    SM<float4>(H_PART + tid * 32 + 16) = make_float4(acc[4], acc[5], acc[6], acc[7]);
    hsync();
    if (ph) break;
#pragma unroll 1
    for (int f = tid; f < 448; f += 256)
      SM<float>(H_ACT + f * 4) = swiglu(SM<float>(H_PART + f * 4) + SM<float>(H_PART + (896 + f) * 4), SM<float>(H_PART + (448 + f) * 4) + SM<float>(H_PART + (1344 + f) * 4));
    hsync();
  }
#pragma unroll 1
  for (int e = tid; e < 1024; e += 256) pkt_st64(&p.sc->fpart[eps * 1024 + e], __float_as_uint(SM<float>(H_PART + e * 4) + SM<float>(H_PART + (1024 + e) * 4)), tag);
  if (tid < 128) {
    float y = 0.f;
#pragma unroll 1
    for (int q = 0; q < 8; q++) y += __uint_as_float(poll64(&p.sc->fpart[q * 1024 + col], tag, 200));
    st_bf16(p.out + tw * 1024 + col, routed_out(SM<float>(H_ROW + 4096 + col * 4), SM<float>(H_ROW + col * 4), y, key_val(best)));
  }
}

template<int MAP>
__global__ void __cluster_dims__(2, 1, 1) __launch_bounds__(NTHR, 1)
fnet_moe_kernel(const __grid_constant__ Params p) {
  const uint32_t t_entry = clk32();
  uint32_t smid;
  asm("mov.u32 %0, %%smid;" : "=r"(smid));
  const int tpc = smid >> 1, m = blockIdx.x & 1;
  if (MAP == 1 ? tpc >= 64 : (tpc >> 1) == 30) {
    if (threadIdx.x < 256) helper_cta(p, (tpc & 1) * 2 + m, t_entry);
    return;
  }
  const uint32_t sb = smem_u32(smem_raw);
  const int tid = threadIdx.x, lane = tid & 31;
  const int e7 = ((tpc - 32) * 37) >> 8;
  const int tau = MAP == 1 || tpc < 32 ? (tpc & 7) : (tpc < 60 ? tpc - 31 - 7 * e7 : 0);
  const int eps = MAP == 1 || tpc < 32 ? (tpc >> 3) : (tpc < 60 ? 4 + e7 : tpc - 58);
  const int cid = tau * 16 + eps * 2 + m;
  auto BAR = [&](int i) { return sb + OFF_BAR + 8 * i; };
  const CUtensorMap* tmD = &p.tmD0 + m;
#define LOAD_STREAM(d, tm, bar, c0, c1) tma_load_2d_hint(d, tm, bar, c0, c1, pol_ef)
#define LOAD_W tma_load_2d
#define LOAD_D tma_load_2d
#define LOAD_X tma_load_2d
#define LOAD_F LOAD_STREAM

  uint32_t tag = 0;
  uint4 wq = make_uint4(0, 0, 0, 0);
  if ((tid >> 5) == 4) {
    if (elect_one()) {
      const uint64_t pol_ef = policy_evict_first();
#pragma unroll
      for (int k = 0; k < 4; k++) mbar_init(BAR(B_FULL + k), 1);
      asm volatile("fence.mbarrier_init.release.cluster;" ::: "memory");
#pragma unroll
      for (int k = 0; k < 4; k++) {
        mbar_expect_tx(BAR(B_FULL + k), ST_BYTES);
        tma_load_2d(sb + k * ST_BYTES + A_BYTES, &p.tmX, BAR(B_FULL + k), k * 64, tau * 256);
        LOAD_D(sb + k * ST_BYTES, tmD, BAR(B_FULL + k), k * 64, eps * 128);
        TIM(k);
      }
    }
  } else if ((tid >> 5) == 1) {
    if (elect_one()) {
#pragma unroll
      for (int s = 0; s < 4; s++) mbar_init(BAR(B_EMPTY + s), 1);
#pragma unroll
      for (int s = 0; s < 8; s++) { mbar_init(BAR(B_EP + s), 4); mbar_init(BAR(B_AW + s), 1); }
      mbar_init(BAR(B_STAT), 4); mbar_init(BAR(B_WC), 1); mbar_init(BAR(B_CD), 2);
      mbar_init(BAR(B_HR), 1); mbar_init(BAR(B_INFO), 1); mbar_init(BAR(B_PEER), 1);
      mbar_init(BAR(B_XCH), 1); mbar_init(BAR(B_XCH + 1), 1); mbar_init(BAR(B_GUX), 1);
      asm volatile("fence.mbarrier_init.release.cluster;" ::: "memory");
      mbar_expect_tx(BAR(B_XCH), 16384); mbar_expect_tx(BAR(B_XCH + 1), 16384); mbar_expect_tx(BAR(B_GUX), 256);
    }
  } else if (tid >= 256) {
    if (START_PF) prefetch_l2(((tid & 64) ? (cid < 64 ? p.Dre : p.Dim) + (cid & 63) * 16384 : p.x + cid * 16384) + ((tid >> 2) & 15) * 1024 + (tid & 3) * 64);
    tag = ld_relaxed32(&p.sc->epoch + threadIdx.y);
    wq = ldg128(p.wr + (tid & 127) * 8);
  }
  const int warp = __shfl_sync(0xffffffffu, tid >> 5, 0);
  __syncthreads();
  asm volatile("barrier.cluster.arrive.relaxed.aligned;" ::: "memory");

  if (warp >= 8) {
    reg_dec<72>();
    cluster_wait();
    tag = __shfl_sync(0xffffffffu, tag, 0) + 1;
    const int cid0 = cid;
    const uint32_t tag0 = tag, sb0 = sb;
    int a, lane, j, cid, tau, eps, m, grp, abrow, fc, src;
    uint32_t tag, c0, c1, sb, buf, bar0;
    bool ffn;
    auto BAR = [&](int i) { return sb + OFF_BAR + 8 * i; };
    auto fresh_ids = [&]() {
      const uint32_t z = uniform_zero_here();
      uint32_t l; asm volatile("mov.u32 %0, %%laneid;" : "=r"(l));
      a = warp - 8 + z; lane = l; j = a * 32 + l;
      cid = cid0 + z; tau = cid >> 4; eps = (cid >> 1) & 7; m = cid & 1; grp = tau * 2 + m; abrow = m * 1024 + eps * 128;
      ffn = eps > 0; fc = (tau * 7 + eps - 1) * 64; src = (fc >> 5) + m;
      tag = tag0 + z; c0 = code_of(tag); c1 = c0 >> 1;
      sb = sb0 + z; buf = sb + OFF_AUX + a * 8192; bar0 = BAR(B_AW + 2 * a);
    };
    fresh_ids();
    if (a == 0 && lane < 16) pkt_clear128(&p.sc->xz[cid * 16 + lane]);
    if (lane < 2) pkt_clear128(&p.sc->dsum[cid * 16 + a * 4 + lane * 2]);
    if (a == 3 && lane < 6) pkt_clear128((lane < 4 ? &p.sc->abdone[(cid * 2 + (lane >> 1)) * 32] : &p.sc->abflag[cid * 32]) + (lane & 1) * 4);
    {
      const float s = warp_sum(((bf_lo(wq.x) + bf_hi(wq.x)) + (bf_lo(wq.y) + bf_hi(wq.y))) + ((bf_lo(wq.z) + bf_hi(wq.z)) + (bf_lo(wq.w) + bf_hi(wq.w))));
      if ((j >> 4) == eps) SM<uint4>(OFF_WR + (j & 15) * 16) = wq;
      if (lane == 0) { SM<float>(INFO_DS + a * 4) = s; SM<uint32_t>(INFO_ONES + a * 4) = 0x3F803F80u; }
    }
    const bf16* xrows = p.x + (cid * 16 + a * 4) * 1024;
    const bf16* drows = (cid < 64 ? p.Dre : p.Dim) + ((cid & 63) * 16 + a * 4) * 1024;
    if (XROW_PF) {
      wait_clk(t_entry, XROW_PF);
      prefetch_l2(xrows + lane * 64); prefetch_l2(xrows + 2048 + lane * 64);
    }
    fresh_ids();
    {
      wait_clk(t_entry, U_CLK);
      uint4 u[8]; uint32_t n = 0;
      bool more;
#pragma unroll 1
      do {
        uint32_t bad = 0;
#pragma unroll
        for (int q = 0; q < 8; q++) u[q] = pkt_ld128(&p.sc->u[a * 512 + lane * 2] + q * 64);
        if (n == 0 && lane < 2) { mbar_expect_tx(bar0 + lane * 8, 4096); bulk_load(buf + lane * 4096, xrows + lane * 2048, 4096, bar0 + lane * 8); }
#pragma unroll
        for (int q = 0; q < 8; q++) chk_code(bad, u[q], c0, c1);
        more = !(!__any_sync(0xffffffffu, bad & 1)) && ++n < SPIN_LIMIT;
        if (more) { __nanosleep(200); }
      } while (more);
      if (j == 0) TIM(96);
      if (DROW_PF) { prefetch_l2(drows + lane * 64); prefetch_l2(drows + 2048 + lane * 64); }
#pragma unroll 1
      for (int r2 = 0; r2 < 2; r2++) {
        float v8[8];
        mbar_wait(bar0 + r2 * 8, 0);
        if (lane == 0) TIM(140 + r2 * 4 + a);
#pragma unroll
        for (int r = 0; r < 2; r++) {
          float s0 = 0.f, s1 = 0.f, q0 = 0.f, q1 = 0.f;
          uint32_t zr = 0, zi = 0;
#pragma unroll
          for (int q = 0; q < 4; q++) {
            const uint4 v = lds128(buf + r2 * 4096 + r * 2048 + (q * 32 + lane) * 16);
            const uint32_t ww[4] = {v.x, v.y, v.z, v.w};
#pragma unroll
            for (int z = 0; z < 4; z++) {
              const float lo = bf_lo(ww[z]), hi = bf_hi(ww[z]);
              s0 += lo; s1 += hi; q0 = fmaf(lo, lo, q0); q1 = fmaf(hi, hi, q1);
            }
            zr = bfma2(v.x, u[2 * q].x, zr); zi = bfma2(v.x, u[2 * q].y, zi); zr = bfma2(v.y, u[2 * q].z, zr); zi = bfma2(v.y, u[2 * q].w, zi);
            zr = bfma2(v.z, u[2 * q + 1].x, zr); zi = bfma2(v.z, u[2 * q + 1].y, zi); zr = bfma2(v.w, u[2 * q + 1].z, zr); zi = bfma2(v.w, u[2 * q + 1].w, zi);
          }
          v8[4 * r] = s0 + s1; v8[4 * r + 1] = q0 + q1; v8[4 * r + 2] = bf_lo(zr) + bf_hi(zr); v8[4 * r + 3] = bf_lo(zi) + bf_hi(zi);
        }
        fold<8>(v8, 16, lane);
        if (lane == 0) { mbar_expect_tx(bar0 + r2 * 8, 4096); bulk_load(buf + r2 * 4096, drows + r2 * 2048, 4096, bar0 + r2 * 8); }
        fold<4>(v8, 8, lane); fold<2>(v8, 4, lane);
        v8[0] += __shfl_xor_sync(0xffffffffu, v8[0], 2);
        v8[0] += __shfl_xor_sync(0xffffffffu, v8[0], 1);
        SM<float>(OFF_REM + a * 64 + r2 * 32 + (lane >> 2) * 4) = v8[0];
        if (lane == 0) TIM(148 + r2 * 4 + a);
      }
    }
    bar_sync(NB_AUX, 128);
    fresh_ids();
    if (a == 0 && lane < 16) {
      const float4 v = SM<float4>(OFF_REM + lane * 16);
      const float mean = v.x * (1.f / 1024.f), rs = fast_rcp(ref_sd(fmaxf(v.y * (1.f / 1024.f) - mean * mean, 0.f)));
      pkt_st128(&p.sc->xz[cid * 16 + lane], __float_as_uint(bf16r(mean)) | (tag & 0xFFFFu), __float_as_uint(rs), pack_bf16(v.z * rs, v.w * rs), tag);
    }
    if (j == 32) { const float4 v = SM<float4>(INFO_DS); SM<float2>(INFO_WSUM) = make_float2((v.x + v.y) + (v.z + v.w), __uint_as_float(tag)); }
    if (j == 0) TIM(98);
#pragma unroll 1
    for (int r2 = 0; r2 < 2; r2++) {
      mbar_wait(bar0 + r2 * 8, 1);
      uint4 dv[8];
#pragma unroll
      for (int q = 0; q < 8; q++) dv[q] = lds128(buf + r2 * 4096 + (lane >> 4) * 2048 + q * 256 + (lane & 15) * 16);
      float s0 = __uint_as_float(zero_here()), s1 = 0.f;
#pragma unroll
      for (int q = 0; q < 8; q++) {
        const uint4 v = dv[q];
        s0 += (bf_lo(v.x) + bf_lo(v.y)) + (bf_lo(v.z) + bf_lo(v.w)); s1 += (bf_hi(v.x) + bf_hi(v.y)) + (bf_hi(v.z) + bf_hi(v.w));
      }
      s0 += s1;
#pragma unroll
      for (int o = 8; o > 0; o >>= 1) s0 += __shfl_xor_sync(0xffffffffu, s0, o);
      SM<float>(INFO_DS2 + (a * 4 + r2 * 2 + (lane >> 4)) * 4) = s0;
    }
    bar_sync(NB_AUX, 128);
    if (a == 1 && lane < 16) pkt_st64(&p.sc->dsum[cid * 16 + lane], SM<uint32_t>(INFO_DS2 + lane * 4), tag);
    if (j == 0) TIM(99);
    uint4* cpart = &p.sc->cpart[grp * 512 + eps * 64];
    pkt_clear128(cpart + (a * 8192 + lane)); pkt_clear128(cpart + (a * 8192 + lane) + 32);
    if (a == 3) { pkt_st64(&p.sc->ch[(lane >> 2) * 512 + cid * 4 + (lane & 3)], 0, 0); if (lane < 8) pkt_clear128(&p.sc->cs[cid * 8 + lane]); }
    {
      wait_clk(clk32(), XS_DELAY);
      uint2 v0, v1, cs; uint32_t n = 0;
      const uint32_t t16 = tag & 0xFFFFu;
      bool more;
#pragma unroll 1
      do {
        v0 = pkt_ld64(&p.sc->xz[tau * 256 + j]); v1 = pkt_ld64(&p.sc->xz[tau * 256 + j] + 128); cs = pkt_ld64(&p.sc->dsum[m * 1024 + eps * 128 + j]);
        more = !(__all_sync(0xffffffffu, (v0.x & 0xFFFFu) == t16 && (v1.x & 0xFFFFu) == t16 && cs.y == tag)) && ++n < SPIN_LIMIT;
        if (more) { __nanosleep(200); }
      } while (more);
      const int ro = OFF_RS + ((j & 7) >> 1) * 272 + (j >> 3) * 8 + (j & 1) * 4;
      SM<uint32_t>(ro) = v0.y ^ (m << 31); SM<uint32_t>(ro + 128) = v1.y ^ (m << 31);
      const uint32_t n0 = (v0.x >> 16) ^ 0x8000u, n1 = (v1.x >> 16) ^ 0x8000u;
      SM<uint4>(OFF_EXB + j * 16) = make_uint4(n0 | (n0 << 16), n0, 0, 0);
      SM<uint4>(OFF_EXB + 2048 + j * 16) = make_uint4(n1 | (n1 << 16), n1, 0, 0);
      const float c = 0.5f * __uint_as_float(cs.x), hi = bf16r(c), mid = bf16r(c - hi), lo = bf16r((c - hi) - mid);
      SM<uint4>(OFF_EXA + j * 16) = make_uint4((__float_as_uint(hi) >> 16) | __float_as_uint(mid), __float_as_uint(lo) >> 16, 0, 0);
      fence_async_smem();
      __syncwarp();
      if (lane == 0) mbar_arrive(BAR(B_STAT));
    }
    if (j == 0) TIM(100);
    auto set_flags = [&](int half) {
      uint32_t* fl = lane == 0 && half == 0 ? &p.sc->abflag[cid * 32] : &p.sc->abdone[(((cid & 15) + (lane & 7) * 16) * 2 + half) * 32 + tau];
      if (lane == 0) {
        asm volatile("fence.proxy.async.global;" ::: "memory");
        asm volatile("st.release.gpu.global.b32 [%0], %1;" :: "l"(fl), "r"(tag) : "memory");
        TIM(69 + half * 8);
      }
      __syncwarp();
      if (lane >= 8 && lane < 16) st_relaxed32(fl, tag);
    };
    auto all_published = [&](int half) {
      uint32_t n = 0;
#pragma unroll 1
      while (!__all_sync(0xffffffffu, ld_acquire32(&p.sc->abdone[(cid * 2 + half) * 32 + (lane & 7)]) == tag) && ++n < SPIN_LIMIT) {}
      if (lane == 0) {
        asm volatile("fence.proxy.async.global;" ::: "memory");
        mbar_arrive(BAR(B_ALL + half));
        TIM(80 + half);
      }
      __syncwarp();
    };
    if (TM_PF && j < 3) asm volatile("prefetch.tensormap [%0];" :: "l"(j == 0 ? &p.tmAbS : j == 1 ? &p.tmAbL : m ? &p.tmW1 : &p.tmW0) : "memory");
    {
      if (a == 3) {
        const uint32_t cl = poll64_warp(&p.sc->cl[cid * 16 + (lane & 3)], tag, 100);
        if (lane == 0) TIM(101);
        const bf16* wm = (m ? p.Wim : p.Wre) + tau * 256 + lane * 8;
        uint4 v[8];
#pragma unroll
        for (int i = 0; i < 8; i++) v[i] = ldg128(wm + ((__shfl_sync(0xffffffffu, cl, i >> 1) >> ((i & 1) * 16)) & 2047) * 2048);
        const int pos = cid * 4 + (lane & 3);
        const bf16* xc = p.x + ((__shfl_sync(0xffffffffu, cl, lane >> 3) >> ((lane & 4) * 4)) & 2047) * 1024 + (pos >> 3) * 16 + (pos & 7);
        const float x0 = ldbf(xc), x1 = ldbf(xc + 8), w0 = ldbf(p.wr + (pos >> 3) * 16 + (pos & 7)), w1 = ldbf(p.wr + (pos >> 3) * 16 + (pos & 7) + 8);
        if (lane < 4) SM<uint32_t>(INFO_CAND + lane * 4) = cl;
#pragma unroll
        for (int i = 0; i < 8; i++) SM<uint4>(OFF_WC + (lane >> 3) * 1024 + i * 128 + (((lane & 7) ^ i) << 4)) = v[i];
        fence_async_smem();
        __syncwarp();
        if (lane == 0) { mbar_arrive(BAR(B_WC)); TIM(102); }
        mbar_wait(BAR(B_CD), 0);
        wait_clk(clk32(), CP_DELAY);
        uint32_t n = 0;
        bool more;
#pragma unroll 1
        do {
          uint32_t bad = 0;
#pragma unroll
          for (int i = 0; i < 8; i++) v[i] = pkt_ld128(&p.sc->cpart[((lane >> 3) * 16 + ((lane >> 2) & 1)) * 512 + pos] + i * 1024);
#pragma unroll
          for (int i = 0; i < 8; i++) chk_code(bad, v[i], c0, c1);
          more = !(!__any_sync(0xffffffffu, bad & 1)) && ++n < SPIN_LIMIT;
          if (more) { __nanosleep(200); }
        } while (more);
        float y[4] = {0.f, 0.f, 0.f, 0.f};
#pragma unroll
        for (int i = 0; i < 8; i++) { y[0] += no_bit(v[i].x); y[2] += no_bit(v[i].y); y[1] += no_bit(v[i].z); y[3] += no_bit(v[i].w); }
#pragma unroll
        for (int i = 0; i < 4; i++) y[i] = bf16r(y[i]);
        __syncwarp();
        fold<4>(y, 4, lane);
        const uint32_t hp = pack_bf16(x0 + bf16r(y[0]), x1 + bf16r(y[1]));
        pkt_st64(&p.sc->ch[(lane >> 2) * 512 + pos], hp, tag);
        float st[3] = {bf_lo(hp) + bf_hi(hp), bf_lo(hp) * bf_lo(hp) + bf_hi(hp) * bf_hi(hp), bf_lo(hp) * w0 + bf_hi(hp) * w1};
#pragma unroll
        for (int o = 1; o < 4; o <<= 1) {
#pragma unroll
          for (int i = 0; i < 3; i++) st[i] += __shfl_xor_sync(0xffffffffu, st[i], o);
        }
        if ((lane & 3) == 0) pkt_st128(&p.sc->cs[cid * 8 + (lane >> 2)], with_bit(st[0], c0), with_bit(st[1], c1), __float_as_uint(st[2]), tag);
        if (lane == 0) TIM(119);
      }
      if (a < 2) {
        if (lane == 0) {
          if (a == 1) mbar_wait(BAR(B_LO), 0);
          const uint32_t t1 = clk32();
#pragma unroll 1
          for (int i = 0; i < 4; i++) {
            if (a == 1) wait_clk(t1, HI_DELAY + i * HI_PACE);
            const int w = i >> 1, c = 2 * a + (i & 1);
            mbar_wait(BAR(B_EP + w * 4 + c), 0);
            TIM(64 + a * 8 + i);
            fence_async_smem();
            tma_store_2d(&p.tmAbS, sb + c * ST_BYTES + w * 8192, tau * 256 + c * 64, abrow + w * 64);
          }
          bulk_commit();
          bulk_wait_all();
          mbar_arrive(BAR(a ? B_HR : B_LO));
          TIM(68 + a * 8);
        }
        set_flags(a);
        if (a == 0) { __nanosleep(500); all_published(0); }
      } else if (a == 2) {
        if (elect_one()) {
          const uint32_t* fl = &p.sc->abflag[((cid + 16) & 127) * 32];
          mbar_wait(BAR(B_LO), 0);
          mbar_wait(BAR(B_FULL), 0); mbar_wait(BAR(B_FULL + 1), 0);
          __nanosleep(LO_NS);
          uint32_t n = 0;
#pragma unroll 1
          while (ld_acquire32(fl) != tag && ++n < SPIN_LIMIT) {}
          asm volatile("fence.proxy.async.global;" ::: "memory");
          tma_load_2d(sb, &p.tmAbL, BAR(B_FULL), k_col(tau, 4), abrow);
          tma_load_2d(sb + ST_BYTES, &p.tmAbL, BAR(B_FULL + 1), k_col(tau, 5), abrow);
          TIM(130);
          mbar_wait(BAR(B_HR), 0); mbar_wait(BAR(B_FULL + 2), 0); mbar_wait(BAR(B_ALL), 0);
          tma_load_2d(sb + 2 * ST_BYTES, &p.tmAbL, BAR(B_FULL + 2), k_col(tau, 6), abrow);
          TIM(132);
          mbar_wait(BAR(B_EMPTY), 0);
          tma_load_2d(sb + 3 * ST_BYTES, &p.tmAbL, BAR(B_FULL + 3), k_col(tau, 7), abrow);
          TIM(133);
        }
      }
      __syncwarp();
    }
    mbar_wait(BAR(B_CD), 0);
    const uint64_t pol_ef = policy_evict_first();
    auto load_unit = [&](int v) {
      if (elect_one()) {
        const uint32_t dst = buf + (v & 1) * 4096, bar = bar0 + (v & 1) * 8;
        mbar_expect_tx(bar, 4096);
        if (v < 8) {
          LOAD_F(dst, &p.tmG, bar, fc, m * 512 + (a * 8 + v) * 16);
          LOAD_F(dst + 2048, &p.tmU, bar, fc, m * 512 + (a * 8 + v) * 16);
        } else LOAD_F(dst, &p.tmDn, bar, a * 256, src * 32 + (v - 8) * 8);
      }
    };
    if (TM_PF && j < 3) asm volatile("prefetch.tensormap [%0];" :: "l"(j == 0 ? &p.tmG : j == 1 ? &p.tmU : &p.tmDn) : "memory");
    bar_sync(NB_AUX, 128);
    if (!LU_LATE && ffn) { load_unit(0); load_unit(1); }
    wait_clk(clk32(), CS_DELAY);
    fresh_ids();
    {
      uint4 v[8], r0, r1; uint32_t n = 0;
      bool more;
#pragma unroll 1
      do {
#pragma unroll
        for (int i = 0; i < 8; i++) v[i] = CS_WEAK ? ldg128(&p.sc->cs[j] + i * 128) : pkt_ld128(&p.sc->cs[j] + i * 128);
        r0 = pkt_ld128(&p.sc->ch[m * 256 + 2 * j]); r1 = pkt_ld128(&p.sc->ch[m * 256 + 2 * j] + 512);
        if (LU_LATE && n == 0 && ffn) { load_unit(0); load_unit(1); }
        uint32_t bad = 0;
#pragma unroll
        for (int i = 0; i < 8; i++) { chk(bad, v[i].x, c0); chk(bad, v[i].y, c1); }
        bad &= 1;
#pragma unroll
        for (int i = 0; i < 8; i++) chk(bad, v[i].w, tag);
        more = __any_sync(0xffffffffu, bad) && ++n < SPIN_LIMIT;
        if (more) __nanosleep(200);
      } while (more);
      if (j == 0) TIM(97);
      float st[3] = {0.f, 0.f, 0.f};
#pragma unroll
      for (int i = 0; i < 8; i++) { st[0] += no_bit(v[i].x); st[1] += no_bit(v[i].y); st[2] += __uint_as_float(v[i].z); }
#pragma unroll
      for (int o = 8; o < 32; o <<= 1) {
#pragma unroll
        for (int i = 0; i < 3; i++) st[i] += __shfl_xor_sync(0xffffffffu, st[i], o);
      }
      if (lane < 8) SM<float4>(OFF_XS + 1536 + (a * 8 + lane) * 16) = make_float4(st[0], st[1], st[2], 0.f);
      bar_sync(NB_AUX, 128);
      const float4 f = SM<float4>(OFF_XS + 1536 + lane * 16);
      st[0] = f.x; st[1] = f.y; st[2] = f.z;
#pragma unroll
      for (int o = 8; o < 32; o <<= 1) {
#pragma unroll
        for (int i = 0; i < 3; i++) st[i] += __shfl_xor_sync(0xffffffffu, st[i], o);
      }
      const float mu = st[0] * (1.f / 1024.f);
      float mb = bf16r(mu), inv = fast_rcp(ref_sd(fmaxf(st[1] * (1.f / 1024.f) - mu * mu, 0.f)));
      const uint32_t kk = make_key(bf16r((st[2] - mb * SM<float>(INFO_WSUM)) * inv), SM<uint16_t>(INFO_CAND + (lane & 7) * 2));
      const uint32_t key = __reduce_max_sync(0xffffffffu, kk);
      const int win = __ffs(__ballot_sync(0xffffffffu, kk == key)) - 1;
      mb = __shfl_sync(0xffffffffu, mb, win); inv = __shfl_sync(0xffffffffu, inv, win);
      if (win == 1) r0 = r1;
      n = 0;
#pragma unroll 1
      while (((win > 1 && n == 0) || __any_sync(0xffffffffu, r0.y != tag || r0.w != tag)) && ++n < SPIN_LIMIT) r0 = pkt_ld128(&p.sc->ch[m * 256 + 2 * j] + win * 512);
      bar_sync(NB_AUX, 128);
      auto ln = [&](float h) { return bf16r(bf16r(h - mb) * inv); };
      const int d = (j >> 2) * 16 + (j & 3) * 2;
      SM<float2>(OFF_XS + d * 4) = make_float2(ln(bf_lo(r0.x)), ln(bf_lo(r0.z)));
      SM<float2>(OFF_XS + (d + 8) * 4) = make_float2(ln(bf_hi(r0.x)), ln(bf_hi(r0.z)));
      if (j == 0) { SM<uint2>(INFO_KEY) = make_uint2(key, win); SM<float2>(INFO_LN) = make_float2(mb, inv); }
    }
    bar_sync(NB_AUX, 128);
    if (j == 0) {
      mbar_arrive(BAR(B_INFO)); TIM(103);
      if (cid == 0) st_relaxed32(&p.sc->epoch, tag);
    }
    const uint32_t t2 = clk32();
    fresh_ids();
    if (!ffn) {
      if (a == 1) all_published(1);
      wait_clk(t2, YPART_DELAY);
    } else {
      const int r = lane >> 3;
      float acc[8] = {0.f, 0.f, 0.f, 0.f, 0.f, 0.f, 0.f, 0.f};
#pragma unroll 1
      for (int v = 0; v < 8; v++) {
        const uint4 x0 = lds128(sb + OFF_XS + ((a * 8 + v) * 16 + (r & 1) * 8) * 4), x1 = lds128(sb + OFF_XS + ((a * 8 + v) * 16 + (r & 1) * 8 + 4) * 4);
        const float xv[8] = {__uint_as_float(x0.x), __uint_as_float(x0.y), __uint_as_float(x0.z), __uint_as_float(x0.w), __uint_as_float(x1.x), __uint_as_float(x1.y), __uint_as_float(x1.z), __uint_as_float(x1.w)};
        mbar_wait(bar0 + (v & 1) * 8, (v >> 1) & 1);
        gemv8x8<128>(acc, buf + (v & 1) * 4096 + r * 1024 + (lane & 7) * 16, xv);
        fence_regs(acc);
        __syncwarp();
        wait_clk(t2, v * UNIT_PACE);
        load_unit(v + 2);
        if (v == 0 && a == 1) all_published(1);
        if (j == 0) TIM(104 + v);
      }
      pkt_clear128(&p.sc->ypart[(a * NSRC + src) * 64 + lane * 2]); pkt_clear128(&p.sc->ypart[(a * NSRC + src) * 64 + lane * 2] + 1);
      fold<8>(acc, 8, lane);
      bar_sync(NB_AUX, 128);
      SM<float4>(OFF_XS + (a * 128 + (r >> 1) * 64 + (lane & 7) * 8 + (r & 1) * 4) * 4) = make_float4(acc[0], acc[1], acc[2], acc[3]);
      bar_sync(NB_AUX, 128);
      auto psum = [&](int i) { return (SM<float>(OFF_XS + i * 4) + SM<float>(OFF_XS + (128 + i) * 4)) + (SM<float>(OFF_XS + (256 + i) * 4) + SM<float>(OFF_XS + (384 + i) * 4)); };
      if (a < 2) st_async_b32(mapa(sb + OFF_REM + j * 4, m ^ 1), mapa(BAR(B_GUX), m ^ 1), __float_as_uint(psum(a * 64 + (m ^ 1) * 32 + lane)));
      const float og = psum(m * 32 + lane), ou = psum(64 + m * 32 + lane);
      mbar_wait(BAR(B_GUX), 0);
      const float rg = SM<float>(OFF_REM + lane * 4), ru = SM<float>(OFF_REM + 128 + lane * 4);
      const float act = swiglu(m ? rg + og : og + rg, m ? ru + ou : ou + ru);
      if (j == 0) TIM(112);
      float y[8] = {0.f, 0.f, 0.f, 0.f, 0.f, 0.f, 0.f, 0.f};
#pragma unroll 1
      for (int v = 8; v < 12; v++) {
        float av[8];
#pragma unroll
        for (int i = 0; i < 8; i++) av[i] = __shfl_sync(0xffffffffu, act, (v - 8) * 8 + i);
        mbar_wait(bar0 + (v & 1) * 8, (v >> 1) & 1);
        gemv8x8<512>(y, buf + (v & 1) * 4096 + lane * 16, av);
        fence_regs(y);
        __syncwarp();
        if (v < 10) load_unit(v + 2);
        if (j == 0) TIM(105 + v);
      }
      fresh_ids();
      uint4* ypart = &p.sc->ypart[(a * NSRC + src) * 64 + lane * 2];
      pkt_st128(ypart, with_bit(y[0], c0), with_bit(y[1], c1), with_bit(y[2], c0), with_bit(y[3], c1));
      pkt_st128(ypart + 1, with_bit(y[4], c0), with_bit(y[5], c1), with_bit(y[6], c0), with_bit(y[7], c1));
      if (lane == 0) TIM(160 + a);
      __nanosleep(ROW_NS);
    }
    {
      float y[8] = {0.f, 0.f, 0.f, 0.f, 0.f, 0.f, 0.f, 0.f};
      uint32_t hh = 0;
      if ((j >> 3) == 14) hh = poll64(&p.sc->ch[SM<uint32_t>(INFO_KEY + 4) * 512 + (cid >> 1) * 8 + (j & 7)], tag, 100);
      if (j < NSRC) {
        const uint4* yp = &p.sc->ypart[((cid >> 5) * NSRC + j) * 64 + (cid & 31) * 2];
        uint4 va, vb; uint32_t n = 0;
        bool more;
#pragma unroll 1
        do {
          uint32_t bad = 0;
          va = pkt_ld128(yp); vb = pkt_ld128(yp + 1);
          chk_code(bad, va, c0, c1); chk_code(bad, vb, c0, c1);
          more = !(!(bad & 1)) && ++n < SPIN_LIMIT;
          if (more) { __nanosleep(300); }
        } while (more);
        y[0] = no_bit(va.x); y[1] = no_bit(va.y); y[2] = no_bit(va.z); y[3] = no_bit(va.w);
        y[4] = no_bit(vb.x); y[5] = no_bit(vb.y); y[6] = no_bit(vb.z); y[7] = no_bit(vb.w);
      }
      __syncwarp();
      if (lane == 0) TIM(164 + a);
      fold<8>(y, 16, lane); fold<4>(y, 8, lane); fold<2>(y, 4, lane);
      y[0] += __shfl_xor_sync(0xffffffffu, y[0], 2);
      y[0] += __shfl_xor_sync(0xffffffffu, y[0], 1);
      SM<float>(OFF_AUX + a * 8192 + (lane >> 2) * 4) = y[0];
      const float h = m ? bf_hi(hh) : bf_lo(hh), hn = bf16r(bf16r(h - SM<float>(INFO_LN)) * SM<float>(INFO_LN + 4));
      bar_sync(NB_AUX, 128);
      if ((j >> 3) == 14) {
        const uint32_t key = SM<uint32_t>(INFO_KEY);
        const int o = OFF_AUX + (j & 7) * 4;
        const float ys = (SM<float>(o) + SM<float>(o + 8192)) + (SM<float>(o + 16384) + SM<float>(o + 24576));
        st_bf16(p.out + key_row(key) * 1024 + cid * 8 + (j & 7), routed_out(h, hn, ys, key_val(key)));
        if (j == 112) TIM(118);
        __threadfence();
        if (j == 112) TIM(117);
        __syncwarp(0xFF0000);
        if (j == 112) pkt_st64(&p.sc->rdone[cid], 0, tag);
      }
    }
  } else {
    reg_inc<216>();
    cluster_wait();
    const uint32_t sb = __shfl_sync(0xffffffffu, smem_u32(smem_raw), 0);
    auto BAR = [&](int i) { return sb + OFF_BAR + 8 * i; };
    const int w = warp >> 2, wi = warp & 3, t = tid & 127;
    const int turn_me = NB_TURN0 + w, turn_other = NB_TURN1 - w;
    const uint64_t dA0 = make_desc(sb + w * 8192);
    uint64_t dA, dB;
    int tau, eps, m, grp, abrow, fc, src;
    bool ffn;
    const CUtensorMap* tmD; const CUtensorMap* tmW;
    auto new_desc = [&](int salt) {
      const uint32_t z = salt < 0 ? uniform_zero_here() : salt & blockIdx.y;
      dA = dA0 + z; dB = dA0 + (z + ((A_BYTES - w * 8192) >> 4));
      const int c = cid + z;
      tau = c >> 4; eps = (c >> 1) & 7; m = c & 1; grp = tau * 2 + m; abrow = m * 1024 + eps * 128;
      ffn = eps > 0; fc = (tau * 7 + eps - 1) * 64; src = (fc >> 5) + m;
      tmD = &p.tmD0 + m; tmW = &p.tmW0 + m;
    };
    constexpr int SL = ST_BYTES >> 4;
    float acc[128];
#pragma unroll
    for (int i = 0; i < 128; i++) acc[i] = 0.f;
    if (w == 1) bar_arrive(NB_TURN0, 256);
    auto full = [&](int k) { mbar_wait(BAR(B_FULL + (k & 3)), (k >> 2) & 1); CT(64 + k); };
    const uint64_t pol_ef = policy_evict_first();
    auto refill_g1 = [&](int k) {
      if (warp == 4) {
        if (elect_one()) {
          const int s = k & 3;
          TIM(k + 4);
          mbar_expect_tx(BAR(B_FULL + s), ST_BYTES);
          LOAD_X(sb + s * ST_BYTES + A_BYTES, &p.tmX, BAR(B_FULL + s), (k + 4) * 64, tau * 256);
          LOAD_D(sb + s * ST_BYTES, tmD, BAR(B_FULL + s), (k + 4) * 64, eps * 128);
        }
        __syncwarp();
      }
    };
    auto refill_g2 = [&](int k, int mode) {
      if (warp == 4) {
        if (elect_one()) {
          const int s = k & 3, s0 = k_col(tau, k - 12);
          TIM(k + 4);
          mbar_expect_tx(BAR(B_FULL + s), mode ? ST_BYTES : B_BYTES);
          if (k == 19) mbar_arrive(BAR(B_EMPTY));
          LOAD_W(sb + s * ST_BYTES + A_BYTES, tmW, BAR(B_FULL + s), s0, grp * 128);
          LOAD_W(sb + s * ST_BYTES + A_BYTES + 16384, tmW, BAR(B_FULL + s), s0, (grp ^ 1) * 128);
          if (mode == 2) tma_load_2d(sb + s * ST_BYTES, &p.tmAbL, BAR(B_FULL + s), s0, abrow);
        }
        __syncwarp();
      }
    };
    auto mma_ss = [&](int k) {
#pragma unroll
      for (int kk = 0; kk < 4; kk++) wgmma_n256(acc, dA + (k & 3) * SL + kk * 2, dB + (k & 3) * SL + kk * 2);
    };
    const bf16* pf; int pf_step; bool pf_on;
    auto pf_ffn = [&](int v) {
      pf_on = ffn && v >= 0 && v < 12;
      pf = v < 8 ? ((lane & 16) ? p.wup : p.wgate) + (m * 512 + (wi * 8 + v) * 16 + (lane & 15)) * 3584 + fc : p.wdown + (src * 32 + (v - 8) * 8) * 1024 + t * 64;
      pf_step = v < 8 ? 16 * 3584 : 8192;
    };
    auto prefetch = [&](int s) { if (pf_on && (wi >> 1) == (s & 1)) prefetch_l2(pf + (s >> 1) * pf_step); };
    auto kstep = [&](int k) {
      full(k);
      bar_sync(turn_me, 256);
      wgmma_fence();
      mma_ss(k);
      wgmma_commit();
      bar_arrive(turn_other, 256);
    };

#pragma unroll 1
    for (int k4 = 0; k4 < 12; k4 += 4) {
      new_desc(k4);
#pragma unroll
      for (int s = 0; s < 4; s++) {
        kstep(k4 | s);
        if (s == 0) {
          if (w == 0) pf_ffn((k4 >> 1) - 2);
          else {
            pf_on = W_PF && k4 == 8;
            pf = (m ? p.Wim : p.Wre) + (tau * 256 + eps * 32 + wi * 4 + (lane >> 3)) * 2048 + k_col(tau, lane & 7);
            pf_step = 16 * 2048;
          }
          pf += zero_here();
        }
        if (LATE_REFILL && (k4 | s)) refill_g1((k4 | s) - 1);
        prefetch(s);
        wgmma_wait<0>();
        if (!LATE_REFILL || (k4 | s) == 11) refill_g1(k4 | s);
      }
    }
    uint32_t R[64];
    auto load_rs = [&](auto gi) {
      const uint32_t rsa = sb + OFF_RS + (lane & 3) * 272;
#pragma unroll
      for (int i = 4 * decltype(gi)::value; i < 4 * decltype(gi)::value + 4; i++) { const uint4 v = lds128(rsa + i * 16); R[4 * i] = v.x; R[4 * i + 1] = v.y; R[4 * i + 2] = v.z; R[4 * i + 3] = v.w; }
    };
    new_desc(ND0);
    kstep(12);
    mbar_wait(BAR(B_STAT), 0);
    CT(1);
    load_rs(std::integral_constant<int, 0>());
    load_rs(std::integral_constant<int, 1>());
    wgmma_wait<0>(); refill_g2(12, 0);
    load_rs(std::integral_constant<int, 3>());
    auto mma_h = [&](float (&d)[64], int s, int half) {
#pragma unroll
      for (int kk = 0; kk < 4; kk++) wgmma_n128(d, dA + s * SL + kk * 2, dB + s * SL + half * 1024 + kk * 2);
    };
    const int rho = 16 * wi + (lane & 15);
    const uint32_t arow = sb + w * 8192 + rho * 128;
    auto convert = [&](auto cc, float (&d)[64]) {
      const float z = __uint_as_float(zero_here());
#pragma unroll
      for (int jj = 8 * decltype(cc)::value; jj < 8 * decltype(cc)::value + 8; jj++) {
        const float r0 = __uint_as_float(R[2 * jj]), r1 = __uint_as_float(R[2 * jj + 1]);
        const float* ac = &d[4 * (jj & 15)];
        R[2 * jj] = pack_bf16(fmaf(ac[0], r0, z), fmaf(ac[1], r1, z));
        R[2 * jj + 1] = pack_bf16(fmaf(ac[2], r0, z), fmaf(ac[3], r1, z));
      }
    };
    auto put = [&](auto cc) {
      constexpr int c = decltype(cc)::value;
#pragma unroll
      for (int jj = 8 * c; jj < 8 * c + 8; jj += 2)
        stsm_x4(arow + c * ST_BYTES + ((((jj & 7) + (lane >> 4)) ^ (rho & 7)) << 4), R[2 * jj], R[2 * jj + 1], R[2 * jj + 2], R[2 * jj + 3]);
      __syncwarp();
      if (lane == 0) mbar_arrive(BAR(B_EP + w * 4 + c));
    };
    {
      float lo[64], hi[64];
      fence_regs(acc);
#pragma unroll
      for (int i = 0; i < 64; i++) asm volatile("mov.b32 %0, %1;" : "=f"(lo[i]) : "f"(acc[i]));
#pragma unroll
      for (int i = 0; i < 64; i++) asm volatile("mov.b32 %0, %1;" : "=f"(hi[i]) : "f"(acc[64 + i]));
      const uint64_t dEA = make_desc_noswz(sb + OFF_EXA + w * 1024), dEB = make_desc_noswz(sb + OFF_EXB);
      full(13); full(14);
      bar_sync(turn_me, 256);
      wgmma_fence();
      mma_h(lo, 1, 0); mma_h(lo, 2, 0);
      wgmma_commit();
      bar_arrive(turn_other, 256);
      new_desc(ND1);
      full(15);
      bar_sync(turn_me, 256);
      wgmma_fence();
      mma_h(lo, 3, 0);
      wgmma_n128(lo, dEA, dEB);
      wgmma_commit();
      mma_h(hi, 1, 1);
      wgmma_commit();
      bar_arrive(turn_other, 256);
      new_desc(ND2);
      wgmma_wait<1>();
      fence_regs(lo);
      CT(15);
      convert(std::integral_constant<int, 0>(), lo); put(std::integral_constant<int, 0>());
      convert(std::integral_constant<int, 1>(), lo);
      wgmma_wait<0>(); refill_g2(13, 0);
      put(std::integral_constant<int, 1>());
      bar_sync(turn_me, 256);
      wgmma_fence();
      mma_h(hi, 2, 1);
      wgmma_commit();
      mma_h(hi, 3, 1);
      wgmma_n128(hi, dEA, dEB + 128);
      wgmma_commit();
      bar_arrive(turn_other, 256);
      load_rs(std::integral_constant<int, 2>());
      wgmma_wait<1>(); refill_g2(14, 0);
      wgmma_wait<0>(); refill_g2(15, 0);
      fence_regs(hi);
      CT(2);
      convert(std::integral_constant<int, 3>(), hi); put(std::integral_constant<int, 3>());
      convert(std::integral_constant<int, 2>(), hi);
    }
    CT(3);
    float cc[4];
    auto cand_mma = [&]() {
      const uint64_t dC = make_desc(sb + OFF_WC);
      wgmma_n8_rs<0>(cc, R, dC);
#pragma unroll
      for (int i = 1; i < 12; i++) wgmma_n8_rs<1>(cc, R + 4 * i, dC + (i >> 2) * 64 + (i & 3) * 2);
#pragma unroll
      for (int kk = 0; kk < 4; kk++) wgmma_n8(cc, dA + 3 * SL + kk * 2, dC + 192 + kk * 2);
      wgmma_commit();
    };
    auto cand_pub = [&]() {
      fence_regs(cc);
      const uint32_t cd = code_of(SM<uint32_t>(INFO_TAG));
      if (t == 0) mbar_arrive(BAR(B_CD));
      pkt_st128(&p.sc->cpart[((lane & 3) * 16 + grp) * 512 + eps * 64 + warp * 8 + (lane >> 2)], with_bit(cc[0], cd), with_bit(cc[1], cd >> 1), with_bit(cc[2], cd), with_bit(cc[3], cd >> 1));
      CT(5);
    };
    new_desc(ND3);
    if (CAND_EARLY) { fence_async_smem(); mbar_wait(BAR(B_WC), 0); CT(4); }
    full(16);
    if (!SPLIT17) full(17);
    bar_sync(turn_me, 256);
    wgmma_fence();
    if (CAND_EARLY) cand_mma();
    wgmma_n256_rs_init(acc, R, dB);
#pragma unroll
    for (int kk = 1; kk < 4; kk++) wgmma_n256_rs<1>(acc, R + 4 * kk, dB + kk * 2);
    wgmma_commit();
    if (SPLIT17) { full(17); wgmma_fence(); }
#pragma unroll
    for (int kk = 0; kk < 4; kk++) wgmma_n256_rs<1>(acc, R + 16 + 4 * kk, dB + SL + kk * 2);
    wgmma_commit();
    bar_arrive(turn_other, 256);
    if (CAND_EARLY) { wgmma_wait<2>(); put(std::integral_constant<int, 2>()); cand_pub(); }
    else put(std::integral_constant<int, 2>());
    wgmma_wait<1>(); refill_g2(16, 1);
    wgmma_wait<0>(); refill_g2(17, 1);
    if (!CAND_EARLY) { fence_async_smem(); mbar_wait(BAR(B_WC), 0); CT(4); }
    full(18);
    bar_sync(turn_me, 256);
    wgmma_fence();
    if (!CAND_EARLY) cand_mma();
#pragma unroll
    for (int kk = 0; kk < 4; kk++) wgmma_n256_rs<1>(acc, R + 32 + 4 * kk, dB + 2 * SL + kk * 2);
    wgmma_commit();
    bar_arrive(turn_other, 256);
    if (!CAND_EARLY) { wgmma_wait<1>(); cand_pub(); }
    wgmma_wait<0>(); refill_g2(18, 1);
    kstep(19);
    wgmma_wait<0>(); refill_g2(19, 1);
#pragma unroll 1
    for (int k4 = 20; k4 < 44; k4 += 4) {
      new_desc(k4);
#pragma unroll
      for (int s = 0; s < 4; s++) {
        kstep(k4 | s);
        if (s == 0) {
          if (w == 0) { pf_ffn((k4 >> 1) - PF2_K / 2 + 4); pf_on = pf_on && k4 >= PF2_K; }
          else {
            pf_on = k4 == XPF_K;
            pf = p.x + (grp * 128 + (t >> 1)) * 1024 + eps * 128 + (t & 1) * 64;
            pf_step = 64 * 1024;
          }
          pf += zero_here();
        }
        if (s == LATE_REFILL && k4 == 20 && warp == 4) mbar_wait(BAR(B_ALL), 0);
        if (s == 2 + LATE_REFILL && k4 == 28 && warp == 4) mbar_wait(BAR(B_ALL + 1), 0);
        if (LATE_REFILL && (k4 | s) > 20) refill_g2((k4 | s) - 1, 2);
        prefetch(s);
        wgmma_wait<0>();
        if (!LATE_REFILL) refill_g2(k4 | s, 2);
      }
    }
    new_desc(ND4);
    const int g = lane >> 2, q = lane & 3;
    const int row0 = grp * 128 + warp * 16 + g;
    uint4 ha[4], hb[4];
    kstep(44);
    if (LATE_REFILL) refill_g2(43, 2);
    uint4* hst = &p.sc->hstat[grp * 1024 + warp * 16 + g];
    if (q == (g >> 1)) { pkt_clear128(hst + eps * 128); pkt_clear128(hst + eps * 128 + 8); }
    mbar_wait(BAR(B_INFO), 0);
    uint4 wv[4];
#pragma unroll
    for (int i = 0; i < 4; i++) wv[i] = lds128(sb + ((g & 1) ? OFF_WR + (i * 4 + q) * 16 : INFO_ONES));
    const uint4 info = lds128(sb + OFF_INFO);
#pragma unroll
    for (int i = 0; i < 4; i++) { ha[i] = ldg128(p.x + (row0 * 1024 + eps * 128 + q * 8) + i * 32); hb[i] = ldg128(p.x + (row0 * 1024 + eps * 128 + q * 8) + 8192 + i * 32); }
    wgmma_wait<0>();
    if (tid == 128) mbar_arrive_remote(mapa(BAR(B_PEER), m ^ 1));
    uint32_t hp[32];
    bf16* op; uint4* hpub;
    uint32_t cd, ast, ald, zr;
    auto swz = [](int row) { return ((row & 1) << 2) | ((row >> 1) & 3); };
    {
      float as[64], ak[64];
      fence_regs(acc);
#pragma unroll
      for (int i = 0; i < 64; i++) asm volatile("mov.b32 %0, %1;" : "=f"(as[i]) : "f"(acc[64 + i]));
#pragma unroll
      for (int i = 0; i < 64; i++) asm volatile("mov.b32 %0, %1;" : "=f"(ak[i]) : "f"(acc[i]));
      full(45); full(46);
      bar_sync(turn_me, 256);
      wgmma_fence();
      mma_h(as, 1, 1); mma_h(as, 2, 1);
      wgmma_commit();
      bar_arrive(turn_other, 256);
      full(47);
      bar_sync(turn_me, 256);
      wgmma_fence();
      mma_h(as, 3, 1);
      wgmma_commit();
      mma_h(ak, 1, 0);
      wgmma_commit();
      bar_arrive(turn_other, 256);
      const uint32_t rx = mapa(sb + OFF_RECV + w * 16384 + t * 16, m ^ 1), rb = mapa(BAR(B_XCH + w), m ^ 1);
      mbar_wait(BAR(B_PEER), 0);
      wgmma_wait<1>();
      fence_regs(as);
      CT(6);
#pragma unroll
      for (int i = 0; i < 8; i++) {
        const float* ac = &as[8 * i];
        st_async_v4(rx + i * 2048, rb, pack_bf16(ac[0], ac[1]), pack_bf16(ac[2], ac[3]), pack_bf16(ac[4], ac[5]), pack_bf16(ac[6], ac[7]));
      }
      CT(7);
      bar_sync(turn_me, 256);
      wgmma_fence();
      mma_h(ak, 2, 0); mma_h(ak, 3, 0);
      wgmma_commit();
      if (w == 0) bar_arrive(turn_other, 256);
      op = p.out + row0 * 1024 + eps * 128 + q * 8;
      hpub = hst + eps * 128; hst += q * 256;
      cd = code_of(info.y);
      ast = sb + w * ST_BYTES + (8 * (lane >> 4) + (lane & 7)) * 128 + (((2 * wi + ((lane >> 3) & 1)) ^ swz(lane & 7)) << 4);
      ald = sb + (warp * 16 + g) * 128 + ((q ^ swz(g)) << 4);
      asm volatile("" : "+l"(op), "+l"(hpub), "+l"(hst), "+r"(cd), "+r"(ast), "+r"(ald));
      zr = zero_here();
#pragma unroll
      for (int i = 0; i < 4; i++) { ha[i].x += zr; hb[i].x += zr; asm volatile("" : "+r"(ha[i].x), "+r"(hb[i].x)); }
      ast += (uint32_t)(clock64() >> 32) & zr;
      mbar_wait(BAR(B_XCH + w), 0);
      CT(9);
#pragma unroll
      for (int i = 0; i < 8; i++) { const uint4 v = lds128(sb + OFF_RECV + w * 16384 + t * 16 + i * 2048); hp[4 * i] = v.x; hp[4 * i + 1] = v.y; hp[4 * i + 2] = v.z; hp[4 * i + 3] = v.w; }
      wgmma_wait<0>();
      fence_regs(ak);
      CT(10);
#pragma unroll
      for (int i = 0; i < 32; i++) hp[i] = badd2(pack_bf16(ak[2 * i], ak[2 * i + 1]), hp[i]);
    }
#pragma unroll
    for (int jj = 0; jj < 16; jj += 2) stsm_x4_t(ast + jj * 1024, hp[2 * jj], hp[2 * jj + 1], hp[2 * jj + 2], hp[2 * jj + 3]);
    tag = info.y;
    bar_sync(NB_BOTH, 256);
    CT(11);
    uint4 v[4];
    auto fetch = [&]() { v[0] = pkt_ld128(hst); v[1] = pkt_ld128(hst + 128); v[2] = pkt_ld128(hst + 8); v[3] = pkt_ld128(hst + 136); };
    float st[6];
    {
      uint4 ya[4], yb[4];
#pragma unroll
      for (int i = 0; i < 4; i++) {
        const uint32_t ad = (ald ^ ((i & 1) << 6)) + (i >> 1) * ST_BYTES;
        ya[i] = lds128(ad); yb[i] = lds128(ad + 1024);
      }
      fetch();
      const float z = __uint_as_float((uint32_t)(clock64() >> 32) & zr);
      float sw[2][4], qa[2][4], qb[2][4];
#pragma unroll
      for (int i = 0; i < 8; i++) { sw[i >> 2][i & 3] = i ? 0.f : z; qa[i >> 2][i & 3] = 0.f; qb[i >> 2][i & 3] = 0.f; }
#pragma unroll
      for (int i = 0; i < 4; i++) {
        ha[i] = make_uint4(badd2(ha[i].x, ya[i].x), badd2(ha[i].y, ya[i].y), badd2(ha[i].z, ya[i].z), badd2(ha[i].w, ya[i].w));
        hb[i] = make_uint4(badd2(hb[i].x, yb[i].x), badd2(hb[i].y, yb[i].y), badd2(hb[i].z, yb[i].z), badd2(hb[i].w, yb[i].w));
        mma16816(sw[0], ha[i].x, hb[i].x, ha[i].y, hb[i].y, wv[i].x, wv[i].y);
        mma16816(qa[0], ha[i].x, hb[i].x, ha[i].y, hb[i].y, ha[i].x, ha[i].y);
        mma16816(qb[0], ha[i].x, hb[i].x, ha[i].y, hb[i].y, hb[i].x, hb[i].y);
        mma16816(sw[1], ha[i].z, hb[i].z, ha[i].w, hb[i].w, wv[i].z, wv[i].w);
        mma16816(qa[1], ha[i].z, hb[i].z, ha[i].w, hb[i].w, ha[i].z, ha[i].w);
        mma16816(qb[1], ha[i].z, hb[i].z, ha[i].w, hb[i].w, hb[i].z, hb[i].w);
      }
      const uint32_t s0 = with_bit(sw[0][0] + sw[1][0], cd), s1 = with_bit((g & 1) ? qa[0][1] + qa[1][1] : qa[0][0] + qa[1][0], cd >> 1), s2 = __float_as_uint(sw[0][1] + sw[1][1]);
      const uint32_t s3 = with_bit(sw[0][2] + sw[1][2], cd), s4 = with_bit((g & 1) ? qb[0][3] + qb[1][3] : qb[0][2] + qb[1][2], cd >> 1), s5 = __float_as_uint(sw[0][3] + sw[1][3]);
      if (q == (g >> 1)) { pkt_st128(hpub, s0, s1, s2, tag); pkt_st128(hpub + 8, s3, s4, s5, tag); }
      CT(12);
      const uint32_t o1 = __shfl_sync(0xffffffffu, s1, (lane & 28) | (g >> 1)), o4 = __shfl_sync(0xffffffffu, s4, (lane & 28) | (g >> 1));
      uint32_t n = 0;
      bool more;
#pragma unroll 1
      do {
        if (2 * q == eps) { v[0] = make_uint4(s0, o1, s2, tag); v[2] = make_uint4(s3, o4, s5, tag); }
        if (2 * q + 1 == eps) { v[1] = make_uint4(s0, o1, s2, tag); v[3] = make_uint4(s3, o4, s5, tag); }
        uint32_t bad = 0;
#pragma unroll
        for (int i = 0; i < 4; i++) { chk(bad, v[i].x, cd); chk(bad, v[i].y, cd >> 1); }
        bad &= 1;
#pragma unroll
        for (int i = 0; i < 4; i++) chk(bad, v[i].w, tag);
        more = !(!__any_sync(0xffffffffu, bad)) && ++n < SPIN_LIMIT;
        if (more) { if (bad) fetch(); }
      } while (more);
      st[0] = no_bit(v[0].x) + no_bit(v[1].x); st[1] = no_bit(v[0].y) + no_bit(v[1].y); st[2] = __uint_as_float(v[0].z) + __uint_as_float(v[1].z);
      st[3] = no_bit(v[2].x) + no_bit(v[3].x); st[4] = no_bit(v[2].y) + no_bit(v[3].y); st[5] = __uint_as_float(v[2].z) + __uint_as_float(v[3].z);
    }
    CT(13);
#pragma unroll
    for (int o = 1; o < 4; o <<= 1) {
#pragma unroll
      for (int i = 0; i < 6; i++) st[i] += __shfl_xor_sync(0xffffffffu, st[i], o);
    }
    float mb[2], inv[2];
#pragma unroll
    for (int i = 0; i < 2; i++) {
      const float mu = st[3 * i] * (1.f / 1024.f);
      mb[i] = bf16r(mu);
      inv[i] = fast_rcp(ref_sd(fmaxf(st[3 * i + 1] * (1.f / 1024.f) - mu * mu, 0.f)));
    }
    {
      const int srow = key_row(info.z);
      auto put_out = [&](bf16* dst, const uint4& h, float sc, float of, bool on) {
        auto cvt = [&](uint32_t x) { return pack_bf16(fmaf(bf_lo(x), sc, of), fmaf(bf_hi(x), sc, of)); };
        asm volatile("{\n.reg .pred p;\nsetp.ne.b32 p, %5, 0;\n@p st.global.v4.b32 [%0], {%1, %2, %3, %4};\n}\n"
                     :: "l"(dst), "r"(cvt(h.x)), "r"(cvt(h.y)), "r"(cvt(h.z)), "r"(cvt(h.w)), "r"((int)on) : "memory");
      };
#pragma unroll
      for (int i = 0; i < 4; i++) {
        put_out(op + i * 32, ha[i], 1.f + inv[0], -mb[0] * inv[0], row0 != srow);
        put_out(op + 8192 + i * 32, hb[i], 1.f + inv[1], -mb[1] * inv[1], row0 + 8 != srow);
      }
    }
    CT(14);
    const uint4 cand = lds128(sb + INFO_CAND);
    uint32_t wkey = zero_here();
#pragma unroll
    for (int i = 0; i < 2; i++) {
      const uint32_t row = row0 + 8 * i, rr = row | (row << 16);
      const bool is_cand = __vcmpeq2(cand.x, rr) | __vcmpeq2(cand.y, rr) | __vcmpeq2(cand.z, rr) | __vcmpeq2(cand.w, rr);
      if (!is_cand) wkey = max(wkey, make_key(bf16r((st[3 * i + 2] - mb[i] * __uint_as_float(info.x)) * inv[i]), row));
    }
    wkey = __reduce_max_sync(0xffffffffu, wkey);
    if (eps == 0 && lane == 0) pkt_st64(&p.sc->key[grp * 8 + warp], wkey, tag);
    const bool beaten = (wkey >> 16) > (info.z >> 16);
    if (__builtin_expect(beaten, 0)) {
      const int br = key_row(wkey);
      if (br == row0 || br == row0 + 8) {
#pragma unroll
        for (int i = 0; i < 4; i++) {
          const uint4 h = br == row0 ? ha[i] : hb[i];
          uint2* dst = &p.sc->hrow[(grp * 8 + warp) * 512 + eps * 64 + i * 16 + q * 4];
          pkt_st128(dst, h.x, tag, h.y, tag); pkt_st128(dst + 2, h.z, tag, h.w, tag);
        }
      }
      __syncwarp();
    }
    uint32_t any;
    asm volatile("{\n.reg .pred p, q;\nsetp.ne.b32 p, %1, 0;\nbarrier.cta.red.or.aligned.pred q, %2, 256, p;\nselp.u32 %0, 1, 0, q;\n}\n" : "=r"(any) : "r"((int)beaten), "n"((int)NB_BOTH) : "memory");
    if (__builtin_expect(any, 0)) slow_path(p, grp, eps, tag, info.z, info.w, SM<float>(INFO_LN), SM<float>(INFO_LN + 4));
  }
}

__global__ void __launch_bounds__(NTHR, 1) occupancy_probe_kernel() {}

typedef CUresult (*EncodeFn)(CUtensorMap*, CUtensorMapDataType, cuuint32_t, void*, const cuuint64_t*, const cuuint64_t*, const cuuint32_t*, const cuuint32_t*,
                             CUtensorMapInterleave, CUtensorMapSwizzle, CUtensorMapL2promotion, CUtensorMapFloatOOBfill);

static void make_tm(EncodeFn enc, CUtensorMap* tm, const void* ptr, uint64_t rows, uint64_t cols, uint32_t brows, uint32_t bcols, bool swz, bool wide) {
  cuuint64_t dims[2] = {cols, rows};
  cuuint64_t strides[1] = {cols * 2};
  cuuint32_t box[2] = {bcols, brows};
  cuuint32_t es[2] = {1, 1};
  enc(tm, CU_TENSOR_MAP_DATA_TYPE_BFLOAT16, 2, const_cast<void*>(ptr), dims, strides, box, es, CU_TENSOR_MAP_INTERLEAVE_NONE,
      swz ? CU_TENSOR_MAP_SWIZZLE_128B : CU_TENSOR_MAP_SWIZZLE_NONE, wide ? CU_TENSOR_MAP_L2_PROMOTION_L2_256B : CU_TENSOR_MAP_L2_PROMOTION_L2_128B, CU_TENSOR_MAP_FLOAT_OOB_FILL_NONE);
}

extern "C" void kernel_launch(void* const* d_in, const int* in_sizes, int n_in, void* d_out, int out_size) {
  (void)in_sizes; (void)n_in; (void)out_size;
  static EncodeFn enc = nullptr;
  static void* abT = nullptr;
  static void* sc = nullptr;
  static int map = 0;
  if (!enc) {
    void* fn = nullptr; cudaDriverEntryPointQueryResult st;
    cudaGetDriverEntryPoint("cuTensorMapEncodeTiled", &fn, cudaEnableDefault, &st);
    enc = (EncodeFn)fn;
    cudaGetSymbolAddress(&abT, g_abT);
    cudaGetSymbolAddress(&sc, g_sc);
    cudaFuncSetAttribute(fnet_moe_kernel<0>, cudaFuncAttributeMaxDynamicSharedMemorySize, SMEM_TOTAL);
    cudaFuncSetAttribute(fnet_moe_kernel<1>, cudaFuncAttributeMaxDynamicSharedMemorySize, SMEM_TOTAL);
    cudaFuncSetAttribute(occupancy_probe_kernel, cudaFuncAttributeMaxDynamicSharedMemorySize, SMEM_TOTAL);
    cudaFuncSetAttribute(occupancy_probe_kernel, cudaFuncAttributeNonPortableClusterSizeAllowed, 1);
    cudaLaunchConfig_t cfg = {};
    cfg.gridDim = dim3(128); cfg.blockDim = dim3(NTHR); cfg.dynamicSmemBytes = SMEM_TOTAL;
    cudaLaunchAttribute at[1];
    at[0].id = cudaLaunchAttributeClusterDimension; at[0].val.clusterDim.x = 16; at[0].val.clusterDim.y = 1; at[0].val.clusterDim.z = 1;
    cfg.attrs = at; cfg.numAttrs = 1;
    int ncl = 0;
    if (cudaOccupancyMaxActiveClusters(&ncl, occupancy_probe_kernel, &cfg) == cudaSuccess && ncl >= 8) map = 1;
    (void)cudaGetLastError();
  }
  Params p;
  const bf16* x = (const bf16*)d_in[0];
  make_tm(enc, &p.tmD0, d_in[3], 1024, 1024, 128, 64, true, true);
  make_tm(enc, &p.tmD1, d_in[4], 1024, 1024, 128, 64, true, true);
  make_tm(enc, &p.tmX, x, 2048, 1024, 256, 64, true, true);
  make_tm(enc, &p.tmAbS, abT, 2048, 2048, 64, 64, true, false);
  make_tm(enc, &p.tmAbL, abT, 2048, 2048, 128, 64, true, false);
  make_tm(enc, &p.tmW0, d_in[1], 2048, 2048, 128, 64, true, true);
  make_tm(enc, &p.tmW1, d_in[2], 2048, 2048, 128, 64, true, true);
  make_tm(enc, &p.tmG, d_in[7], 1024, 3584, 16, 64, false, false);
  make_tm(enc, &p.tmU, d_in[8], 1024, 3584, 16, 64, false, false);
  make_tm(enc, &p.tmDn, d_in[9], 3584, 1024, 8, 256, false, false);
  p.x = x; p.Dre = (const bf16*)d_in[3]; p.Dim = (const bf16*)d_in[4];
  p.wr = (const bf16*)d_in[6]; p.wdown = (const bf16*)d_in[9]; p.wgate = (const bf16*)d_in[7]; p.wup = (const bf16*)d_in[8]; p.Wre = (const bf16*)d_in[1]; p.Wim = (const bf16*)d_in[2];
  p.out = (bf16*)d_out; p.sc = (Scratch*)sc;
  if (map == 1) fnet_moe_kernel<1><<<NGRID, NTHR, SMEM_TOTAL>>>(p);
  else fnet_moe_kernel<0><<<NGRID, NTHR, SMEM_TOTAL>>>(p);
}
```

```cpp
#include <cuda.h>
#include <cuda_runtime.h>
#include <cuda_bf16.h>
#include <stdint.h>
#include <stddef.h>
#include <type_traits>

typedef __nv_bfloat16 bf16;

constexpr int NGRID = 132, NTHR = 384;
__device__ __forceinline__ int k_col(int tau, int j) {
  const int i = j < 18 ? j - 2 : j - 16;
  return j < 4 ? tau * 256 + j * 64 : ((tau + (i >> 1)) & 7) * 256 + (i & 1) * 64 + (j < 18 ? 0 : 128);
}
constexpr int A_BYTES = 128 * 64 * 2;
constexpr int B_BYTES = 256 * 64 * 2;
constexpr int ST_BYTES = A_BYTES + B_BYTES;
constexpr int OFF_AUX = 4 * ST_BYTES;
constexpr int OFF_BAR = OFF_AUX + 32768;
constexpr int OFF_XS = OFF_BAR + 256;
constexpr int OFF_WR = OFF_XS + 2048;
constexpr int OFF_REM = OFF_WR + 256;
constexpr int OFF_INFO = OFF_REM + 256;
constexpr int SMEM_TOTAL = OFF_INFO + 256;
constexpr int INFO_WSUM = OFF_INFO, INFO_TAG = OFF_INFO + 4, INFO_KEY = OFF_INFO + 8, INFO_CAND = OFF_INFO + 16, INFO_LN = OFF_INFO + 32, INFO_ONES = OFF_INFO + 48, INFO_DS = OFF_INFO + 64, INFO_DS2 = OFF_INFO + 192;
constexpr int OFF_RS = OFF_XS;
constexpr int OFF_WC = OFF_AUX;
constexpr int OFF_EXA = OFF_AUX + 4096;
constexpr int OFF_EXB = OFF_AUX + 6144;
constexpr int OFF_RECV = A_BYTES;
__host__ __device__ constexpr int off_y(int w) { return w * ST_BYTES; }
constexpr int NSRC = 112;
enum { B_FULL = 0, B_EMPTY = 4, B_LO = 5, B_ALL = 6, B_EP = 8, B_AW = 16, B_STAT = 24, B_WC = 25, B_CD = 26, B_HR = 27, B_INFO = 28, B_PEER = 29, B_XCH = 30, B_GUX = (OFF_INFO + 128 - OFF_BAR) / 8 };
enum { NB_TURN0 = 1, NB_TURN1 = 2, NB_BOTH = 3, NB_AUX = 4, NB_H = 5 };

struct Scratch;
struct Params {
  Scratch* sc; const bf16* wr; const bf16* x; const bf16* Dre; const bf16* Dim; const bf16* Wre; const bf16* Wim;
  const bf16* wgate; const bf16* wup; const bf16* wdown; bf16* out;
  CUtensorMap tmX, tmD0, tmD1, tmW0, tmW1, tmAbS, tmAbL, tmG, tmU, tmDn, tmY;
};

__device__ __align__(1024) bf16 g_abT[2048 * 2048];
struct Scratch {
  alignas(128) uint4 xz[2048];
  alignas(128) uint2 dsum[2048];
  alignas(128) uint32_t abflag[128 * 32];
  alignas(128) uint32_t abdone[128 * 2 * 32];
  alignas(128) uint2 u[4 * 512];
  alignas(128) uint2 cl[128 * 16];
  alignas(128) uint4 cpart[4 * 16 * 512];
  alignas(128) uint2 ch[8 * 512];
  alignas(128) uint4 cs[128 * 8];
  alignas(128) uint2 rdone[128];
  alignas(128) uint4 ypart[4 * NSRC * 64];
  alignas(128) uint4 hstat[16 * 8 * 128];
  alignas(128) uint2 key[128];
  alignas(128) uint2 hrow[128 * 512];
  alignas(128) uint2 fpart[8 * 1024];
  alignas(128) uint32_t epoch;
};
__device__ Scratch g_sc;

#define SPIN_LIMIT (1u << 17)
#define PF2_K 24
#define UNIT_PACE 1500
#define XPF_K 40
#define XS_DELAY 300
#define U_CLK 3700
#define XROW_PF 0
#define DROW_PF 0
#define TM_PF 0
#define SPLIT17 1
#define LO_NS 500
#define CAND_EARLY 0
#define CHAIN1 0
#define ROW_NS 400
#define W_PF 8
#define START_PF 0
#define ND0 65
#define ND1 66
#define ND2 67
#define ND3 -1
#define ND4 69
#define HI_DELAY 0
#define HI_PACE 1200
#define LU_LATE 0
#define CS_WEAK 0
#define Z_CLK 9000
#define CP_DELAY 1500
#define CS_DELAY 800
#define YPART_DELAY 16500
__device__ __forceinline__ uint32_t smem_u32(const void* p) { return (uint32_t)__cvta_generic_to_shared(p); }
__device__ __forceinline__ uint32_t clk32() { uint32_t c; asm volatile("mov.u32 %0, %%clock;" : "=r"(c)); return c; }
__device__ __forceinline__ uint32_t zero_here() { uint64_t c; asm volatile("mov.u64 %0, %%clock64;" : "=l"(c) :: "memory"); return (uint32_t)(c >> 32) & blockIdx.y; }
__device__ __forceinline__ uint32_t uniform_zero_here() { uint32_t c; asm volatile("mov.u32 %0, %%clock;" : "=r"(c) :: "memory"); return c & blockIdx.y; }
__device__ __forceinline__ void wait_clk(uint32_t t0, uint32_t dt) {
  asm volatile("{\n.reg .pred p;\n.reg .u32 c;\nLOOP:\nmov.u32 c, %%clock;\nsub.u32 c, c, %0;\nsetp.lt.u32 p, c, %1;\n@p nanosleep.u32 100;\n@p bra LOOP;\n}\n" :: "r"(t0), "r"(dt) : "memory");
}
__device__ __forceinline__ void mbar_init(uint32_t bar, uint32_t cnt) { asm volatile("mbarrier.init.shared::cta.b64 [%0], %1;" :: "r"(bar), "r"(cnt) : "memory"); }
__device__ __forceinline__ void mbar_expect_tx(uint32_t bar, uint32_t bytes) { asm volatile("mbarrier.arrive.expect_tx.shared::cta.b64 _, [%0], %1;" :: "r"(bar), "r"(bytes) : "memory"); }
__device__ __forceinline__ void mbar_arrive(uint32_t bar) { asm volatile("mbarrier.arrive.shared::cta.b64 _, [%0];" :: "r"(bar) : "memory"); }
__device__ __forceinline__ void mbar_arrive_remote(uint32_t cluster_addr) { asm volatile("mbarrier.arrive.shared::cluster.b64 _, [%0];" :: "r"(cluster_addr) : "memory"); }
__device__ __forceinline__ void mbar_wait(uint32_t bar, uint32_t parity) {
  asm volatile("{\n.reg .pred p;\nLOOP:\nmbarrier.try_wait.parity.shared::cta.b64 p, [%0], %1;\n@!p bra LOOP;\n}\n" :: "r"(bar), "r"(parity) : "memory");
}
__device__ __forceinline__ void tma_load_2d(uint32_t dst, const CUtensorMap* tm, uint32_t bar, int c0, int c1) {
  asm volatile("cp.async.bulk.tensor.2d.shared::cluster.global.mbarrier::complete_tx::bytes [%0], [%1, {%3, %4}], [%2];"
    :: "r"(dst), "l"(tm), "r"(bar), "r"(c0), "r"(c1) : "memory");
}
__device__ __forceinline__ void tma_load_2d_hint(uint32_t dst, const CUtensorMap* tm, uint32_t bar, int c0, int c1, uint64_t pol) {
  asm volatile("cp.async.bulk.tensor.2d.shared::cluster.global.mbarrier::complete_tx::bytes.L2::cache_hint [%0], [%1, {%3, %4}], [%2], %5;"
    :: "r"(dst), "l"(tm), "r"(bar), "r"(c0), "r"(c1), "l"(pol) : "memory");
}
__device__ __forceinline__ uint64_t policy_evict_first() { uint64_t p; asm volatile("createpolicy.fractional.L2::evict_first.b64 %0, 1.0;" : "=l"(p)); return p; }
__device__ __forceinline__ void tma_store_2d(const CUtensorMap* tm, uint32_t src, int c0, int c1) {
  asm volatile("cp.async.bulk.tensor.2d.global.shared::cta.bulk_group [%0, {%2, %3}], [%1];" :: "l"(tm), "r"(src), "r"(c0), "r"(c1) : "memory");
}
__device__ __forceinline__ void bulk_load(uint32_t dst, const void* src, uint32_t bytes, uint32_t bar) {
  asm volatile("cp.async.bulk.shared::cluster.global.mbarrier::complete_tx::bytes [%0], [%1], %2, [%3];" :: "r"(dst), "l"(src), "r"(bytes), "r"(bar) : "memory");
}
__device__ __forceinline__ void prefetch_l2(const void* p) { asm volatile("prefetch.global.L2 [%0];" :: "l"(p)); }
__device__ __forceinline__ void bulk_commit() { asm volatile("cp.async.bulk.commit_group;" ::: "memory"); }
__device__ __forceinline__ void bulk_wait_all() { asm volatile("cp.async.bulk.wait_group 0;" ::: "memory"); }
__device__ __forceinline__ void fence_async_smem() { asm volatile("fence.proxy.async.shared::cta;" ::: "memory"); }
__device__ __forceinline__ void wgmma_fence() { asm volatile("wgmma.fence.sync.aligned;" ::: "memory"); }
__device__ __forceinline__ void wgmma_commit() { asm volatile("wgmma.commit_group.sync.aligned;" ::: "memory"); }
template<int N> __device__ __forceinline__ void wgmma_wait() { asm volatile("wgmma.wait_group.sync.aligned %0;" :: "n"(N) : "memory"); }
__device__ __forceinline__ void bar_sync(int id, int n) { asm volatile("bar.sync %0, %1;" :: "r"(id), "r"(n) : "memory"); }
__device__ __forceinline__ void bar_arrive(int id, int n) { asm volatile("bar.arrive %0, %1;" :: "r"(id), "r"(n) : "memory"); }
__device__ __forceinline__ void cluster_wait() { asm volatile("barrier.cluster.wait.aligned;" ::: "memory"); }
template<int R> __device__ __forceinline__ void reg_inc() { asm volatile("setmaxnreg.inc.sync.aligned.u32 %0;" :: "n"(R)); }
template<int R> __device__ __forceinline__ void reg_dec() { asm volatile("setmaxnreg.dec.sync.aligned.u32 %0;" :: "n"(R)); }
__device__ __forceinline__ bool elect_one() {
  uint32_t p;
  asm volatile("{\n.reg .pred q;\nelect.sync _|q, 0xffffffff;\nselp.u32 %0, 1, 0, q;\n}\n" : "=r"(p));
  return p != 0;
}
__device__ __forceinline__ uint32_t mapa(uint32_t addr, uint32_t cta) { uint32_t r; asm volatile("mapa.shared::cluster.u32 %0, %1, %2;" : "=r"(r) : "r"(addr), "r"(cta)); return r; }
__device__ __forceinline__ void st_async_v4(uint32_t addr, uint32_t bar, uint32_t a, uint32_t b, uint32_t c, uint32_t d) {
  asm volatile("st.async.weak.shared::cluster.mbarrier::complete_tx::bytes.v4.b32 [%0], {%2, %3, %4, %5}, [%1];" :: "r"(addr), "r"(bar), "r"(a), "r"(b), "r"(c), "r"(d) : "memory");
}
__device__ __forceinline__ void st_async_b32(uint32_t addr, uint32_t bar, uint32_t a) {
  asm volatile("st.async.weak.shared::cluster.mbarrier::complete_tx::bytes.b32 [%0], %2, [%1];" :: "r"(addr), "r"(bar), "r"(a) : "memory");
}
__device__ __forceinline__ void stsm_x4(uint32_t addr, uint32_t a, uint32_t b, uint32_t c, uint32_t d) {
  asm volatile("stmatrix.sync.aligned.m8n8.x4.shared.b16 [%0], {%1, %2, %3, %4};" :: "r"(addr), "r"(a), "r"(b), "r"(c), "r"(d) : "memory");
}
__device__ __forceinline__ void stsm_x4_t(uint32_t addr, uint32_t a, uint32_t b, uint32_t c, uint32_t d) {
  asm volatile("stmatrix.sync.aligned.m8n8.x4.trans.shared.b16 [%0], {%1, %2, %3, %4};" :: "r"(addr), "r"(a), "r"(b), "r"(c), "r"(d) : "memory");
}
__device__ __forceinline__ uint4 lds128(uint32_t addr) { uint4 v; asm volatile("ld.shared.v4.b32 {%0, %1, %2, %3}, [%4];" : "=r"(v.x), "=r"(v.y), "=r"(v.z), "=r"(v.w) : "r"(addr) : "memory"); return v; }
extern __shared__ __align__(1024) uint8_t smem_raw[];
template<class T> __device__ __forceinline__ T& SM(int off) { return *reinterpret_cast<T*>(smem_raw + off); }
__device__ __forceinline__ uint4 ldg_nc128(const void* p) { uint4 v; asm volatile("ld.global.nc.v4.b32 {%0, %1, %2, %3}, [%4];" : "=r"(v.x), "=r"(v.y), "=r"(v.z), "=r"(v.w) : "l"(p)); return v; }
__device__ __forceinline__ uint4 ldg128(const void* p) { uint4 v; asm volatile("ld.global.L1::no_allocate.v4.b32 {%0, %1, %2, %3}, [%4];" : "=r"(v.x), "=r"(v.y), "=r"(v.z), "=r"(v.w) : "l"(p) : "memory"); return v; }
__device__ __forceinline__ void pkt_st128(void* p, uint32_t a, uint32_t b, uint32_t c, uint32_t d) {
  asm volatile("{\n.reg .b128 v;\n.reg .b64 lo, hi;\nmov.b64 lo, {%1, %2};\nmov.b64 hi, {%3, %4};\nmov.b128 v, {lo, hi};\nst.relaxed.gpu.global.b128 [%0], v;\n}\n"
    :: "l"(p), "r"(a), "r"(b), "r"(c), "r"(d) : "memory");
}
__device__ __forceinline__ uint4 pkt_ld128(const void* p) {
  uint4 r;
  asm volatile("{\n.reg .b128 v;\n.reg .b64 lo, hi;\nld.relaxed.gpu.global.b128 v, [%4];\nmov.b128 {lo, hi}, v;\nmov.b64 {%0, %1}, lo;\nmov.b64 {%2, %3}, hi;\n}\n"
    : "=r"(r.x), "=r"(r.y), "=r"(r.z), "=r"(r.w) : "l"(p) : "memory");
  return r;
}
__device__ __forceinline__ void pkt_st64(void* p, uint32_t a, uint32_t b) {
  asm volatile("{\n.reg .b64 v;\nmov.b64 v, {%1, %2};\nst.relaxed.gpu.global.b64 [%0], v;\n}\n" :: "l"(p), "r"(a), "r"(b) : "memory");
}
__device__ __forceinline__ uint2 pkt_ld64(const void* p) {
  uint2 r;
  asm volatile("{\n.reg .b64 v;\nld.relaxed.gpu.global.b64 v, [%2];\nmov.b64 {%0, %1}, v;\n}\n" : "=r"(r.x), "=r"(r.y) : "l"(p) : "memory");
  return r;
}
__device__ __forceinline__ void pkt_clear128(void* p) { pkt_st128(p, 0, 0, 0, 0); }
__device__ __forceinline__ uint32_t ld_relaxed32(const void* p) { uint32_t v; asm volatile("ld.relaxed.gpu.global.b32 %0, [%1];" : "=r"(v) : "l"(p) : "memory"); return v; }
__device__ __forceinline__ uint32_t ld_acquire32(const void* p) { uint32_t v; asm volatile("ld.acquire.gpu.global.b32 %0, [%1];" : "=r"(v) : "l"(p) : "memory"); return v; }
__device__ __forceinline__ void st_relaxed32(void* p, uint32_t v) { asm volatile("st.relaxed.gpu.global.b32 [%0], %1;" :: "l"(p), "r"(v) : "memory"); }
__device__ __forceinline__ uint32_t poll64(const void* p, uint32_t tag, int ns) {
  uint2 v; uint32_t n = 0;
  bool more;
#pragma unroll 1
  do {
    v = pkt_ld64(p);
    more = !(v.y == tag) && ++n < SPIN_LIMIT;
    if (more) { __nanosleep(ns); }
  } while (more);
  return v.x;
}
__device__ __forceinline__ uint32_t poll64_warp(const void* p, uint32_t tag, int ns) {
  uint2 v; uint32_t n = 0;
  bool more;
#pragma unroll 1
  do {
    v = pkt_ld64(p);
    more = !(__all_sync(0xffffffffu, v.y == tag)) && ++n < SPIN_LIMIT;
    if (more) { __nanosleep(ns); }
  } while (more);
  return v.x;
}
__device__ __forceinline__ uint32_t code_of(uint32_t tag) { return tag % 3u + 1u; }
__device__ __forceinline__ uint32_t with_bit(uint32_t v, uint32_t bit) { return (v & ~1u) | (bit & 1u); }
__device__ __forceinline__ uint32_t with_bit(float v, uint32_t bit) { return with_bit(__float_as_uint(v), bit); }
__device__ __forceinline__ float no_bit(uint32_t v) { return __uint_as_float(v & ~1u); }
__device__ __forceinline__ void chk(uint32_t& bad, uint32_t a, uint32_t want) { bad |= a ^ want; asm("" : "+r"(bad)); }
__device__ __forceinline__ void chk_code(uint32_t& bad, const uint4& v, uint32_t c0, uint32_t c1) { chk(bad, v.x, c0); chk(bad, v.y, c1); chk(bad, v.z, c0); chk(bad, v.w, c1); }
__device__ __forceinline__ uint32_t pack_bf16(float lo, float hi) { uint32_t r; asm("cvt.rn.bf16x2.f32 %0, %1, %2;" : "=r"(r) : "f"(hi), "f"(lo)); return r; }
__device__ __forceinline__ float bf_lo(uint32_t v) { return __uint_as_float(v << 16); }
__device__ __forceinline__ float bf_hi(uint32_t v) { return __uint_as_float(v & 0xFFFF0000u); }
__device__ __forceinline__ float bf16r(float x) { return __uint_as_float(pack_bf16(0.f, x)); }
__device__ __forceinline__ void st_bf16(bf16* p, float x) { *reinterpret_cast<uint16_t*>(p) = (uint16_t)pack_bf16(x, 0.f); }
__device__ __forceinline__ float fast_rcp(float x) { float r; asm("rcp.approx.f32 %0, %1;" : "=f"(r) : "f"(x)); return r; }
__device__ __forceinline__ float ldbf(const bf16* p) { return __bfloat162float(*p); }
__device__ __forceinline__ uint32_t badd2(uint32_t a, uint32_t b) { uint32_t r; asm("add.rn.bf16x2 %0, %1, %2;" : "=r"(r) : "r"(a), "r"(b)); return r; }
__device__ __forceinline__ uint32_t bfma2(uint32_t a, uint32_t b, uint32_t c) { uint32_t r; asm("fma.rn.bf16x2 %0, %1, %2, %3;" : "=r"(r) : "r"(a), "r"(b), "r"(c)); return r; }
__device__ __forceinline__ float warp_sum(float v) {
#pragma unroll
  for (int o = 16; o > 0; o >>= 1) v += __shfl_xor_sync(0xffffffffu, v, o);
  return v;
}
template<int N> __device__ __forceinline__ void fold(float* v, int o, int lane) {
  const bool up = lane & o;
#pragma unroll
  for (int i = 0; i < N / 2; i++) {
    const float keep = up ? v[N / 2 + i] : v[i], send = up ? v[i] : v[N / 2 + i];
    v[i] = keep + __shfl_xor_sync(0xffffffffu, send, o);
  }
}
__device__ __forceinline__ uint32_t make_key(float r_bf, int row) {
  const uint32_t u = __float_as_uint(r_bf);
  return (((u & 0x80000000u) ? ~u : (u | 0x80000000u)) & 0xFFFF0000u) | (0xFFFFu - (uint32_t)row);
}
__device__ __forceinline__ int key_row(uint32_t key) { return (0xFFFF - (int)(key & 0xFFFFu)) & 2047; }
__device__ __forceinline__ float key_val(uint32_t key) { const uint32_t o = key & 0xFFFF0000u; return __uint_as_float((o & 0x80000000u) ? (o & 0x7FFFFFFFu) : (~o & 0xFFFF0000u)); }
__device__ __forceinline__ float ref_sd(float var) { float r; asm("sqrt.approx.f32 %0, %1;" : "=f"(r) : "f"(bf16r(bf16r(var) + 1e-5f))); return bf16r(r); }
__device__ __forceinline__ uint64_t make_desc(uint32_t addr) { return (uint64_t)((addr & 0x3FFFF) >> 4) | ((uint64_t)64 << 32) | ((uint64_t)1 << 62); }
__device__ __forceinline__ uint64_t make_desc_noswz(uint32_t addr) { return (uint64_t)((addr & 0x3FFFF) >> 4) | ((uint64_t)8 << 32); }
#define ACC8(d, o) "+f"(d[o]), "+f"(d[o + 1]), "+f"(d[o + 2]), "+f"(d[o + 3]), "+f"(d[o + 4]), "+f"(d[o + 5]), "+f"(d[o + 6]), "+f"(d[o + 7])
#define ACC64(d, o) ACC8(d, o), ACC8(d, o + 8), ACC8(d, o + 16), ACC8(d, o + 24), ACC8(d, o + 32), ACC8(d, o + 40), ACC8(d, o + 48), ACC8(d, o + 56)
#define REGS64 "%0, %1, %2, %3, %4, %5, %6, %7, %8, %9, %10, %11, %12, %13, %14, %15, %16, %17, %18, %19, %20, %21, %22, %23, %24, %25, %26, %27, %28, %29, %30, %31, " \
    "%32, %33, %34, %35, %36, %37, %38, %39, %40, %41, %42, %43, %44, %45, %46, %47, %48, %49, %50, %51, %52, %53, %54, %55, %56, %57, %58, %59, %60, %61, %62, %63"
#define REGS128 REGS64 ", %64, %65, %66, %67, %68, %69, %70, %71, %72, %73, %74, %75, %76, %77, %78, %79, %80, %81, %82, %83, %84, %85, %86, %87, %88, %89, %90, %91, %92, %93, %94, %95, " \
    "%96, %97, %98, %99, %100, %101, %102, %103, %104, %105, %106, %107, %108, %109, %110, %111, %112, %113, %114, %115, %116, %117, %118, %119, %120, %121, %122, %123, %124, %125, %126, %127"
__device__ __forceinline__ void wgmma_n256(float (&d)[128], uint64_t da, uint64_t db) {
  asm volatile("wgmma.mma_async.sync.aligned.m64n256k16.f32.bf16.bf16 {" REGS128 "}, %128, %129, 1, 1, 1, 0, 0;\n"
    : ACC64(d, 0), ACC64(d, 64) : "l"(da), "l"(db));
}
#define OUT8(d, o) "=f"(d[o]), "=f"(d[o + 1]), "=f"(d[o + 2]), "=f"(d[o + 3]), "=f"(d[o + 4]), "=f"(d[o + 5]), "=f"(d[o + 6]), "=f"(d[o + 7])
#define OUT64(d, o) OUT8(d, o), OUT8(d, o + 8), OUT8(d, o + 16), OUT8(d, o + 24), OUT8(d, o + 32), OUT8(d, o + 40), OUT8(d, o + 48), OUT8(d, o + 56)
__device__ __forceinline__ void wgmma_n256_rs_init(float (&d)[128], const uint32_t* a, uint64_t db) {
  asm volatile("wgmma.mma_async.sync.aligned.m64n256k16.f32.bf16.bf16 {" REGS128 "}, {%128, %129, %130, %131}, %132, 0, 1, 1, 0;\n"
    : OUT64(d, 0), OUT64(d, 64) : "r"(a[0]), "r"(a[1]), "r"(a[2]), "r"(a[3]), "l"(db));
}
template<int ACCUM> __device__ __forceinline__ void wgmma_n256_rs(float (&d)[128], const uint32_t* a, uint64_t db) {
  asm volatile("wgmma.mma_async.sync.aligned.m64n256k16.f32.bf16.bf16 {" REGS128 "}, {%128, %129, %130, %131}, %132, %133, 1, 1, 0;\n"
    : ACC64(d, 0), ACC64(d, 64) : "r"(a[0]), "r"(a[1]), "r"(a[2]), "r"(a[3]), "l"(db), "n"(ACCUM));
}
template<int ACCUM> __device__ __forceinline__ void wgmma_n8_rs(float (&d)[4], const uint32_t* a, uint64_t db) {
  asm volatile("wgmma.mma_async.sync.aligned.m64n8k16.f32.bf16.bf16 {%0, %1, %2, %3}, {%4, %5, %6, %7}, %8, %9, 1, 1, 0;\n"
    : "+f"(d[0]), "+f"(d[1]), "+f"(d[2]), "+f"(d[3]) : "r"(a[0]), "r"(a[1]), "r"(a[2]), "r"(a[3]), "l"(db), "n"(ACCUM));
}
__device__ __forceinline__ void wgmma_n8(float (&d)[4], uint64_t da, uint64_t db) {
  asm volatile("wgmma.mma_async.sync.aligned.m64n8k16.f32.bf16.bf16 {%0, %1, %2, %3}, %4, %5, 1, 1, 1, 0, 0;\n"
    : "+f"(d[0]), "+f"(d[1]), "+f"(d[2]), "+f"(d[3]) : "l"(da), "l"(db));
}
__device__ __forceinline__ void wgmma_n128(float (&d)[64], uint64_t da, uint64_t db) {
  asm volatile("wgmma.mma_async.sync.aligned.m64n128k16.f32.bf16.bf16 {" REGS64 "}, %64, %65, 1, 1, 1, 0, 0;\n" : ACC64(d, 0) : "l"(da), "l"(db));
}
template<int N> __device__ __forceinline__ void fence_regs(float (&d)[N]) {
#pragma unroll
  for (int i = 0; i < N; i++) asm volatile("" : "+f"(d[i]) :: "memory");
}
__device__ __forceinline__ void mma16816(float (&c)[4], uint32_t a0, uint32_t a1, uint32_t a2, uint32_t a3, uint32_t b0, uint32_t b1) {
  asm volatile("mma.sync.aligned.m16n8k16.row.col.f32.bf16.bf16.f32 {%0, %1, %2, %3}, {%4, %5, %6, %7}, {%8, %9}, {%0, %1, %2, %3};"
               : "+f"(c[0]), "+f"(c[1]), "+f"(c[2]), "+f"(c[3]) : "r"(a0), "r"(a1), "r"(a2), "r"(a3), "r"(b0), "r"(b1));
}
__device__ __forceinline__ void fma8(float* acc, const uint4& v, float x) {
  acc[0] = fmaf(bf_lo(v.x), x, acc[0]); acc[1] = fmaf(bf_hi(v.x), x, acc[1]); acc[2] = fmaf(bf_lo(v.y), x, acc[2]); acc[3] = fmaf(bf_hi(v.y), x, acc[3]);
  acc[4] = fmaf(bf_lo(v.z), x, acc[4]); acc[5] = fmaf(bf_hi(v.z), x, acc[5]); acc[6] = fmaf(bf_lo(v.w), x, acc[6]); acc[7] = fmaf(bf_hi(v.w), x, acc[7]);
}
template<int PITCH> __device__ __forceinline__ void gemv8x8(float (&acc)[8], uint32_t addr, const float (&x)[8]) {
  uint4 v[2][2];
  v[0][0] = lds128(addr); v[0][1] = lds128(addr + PITCH);
#pragma unroll
  for (int b = 0; b < 4; b++) {
    if (b < 3) { v[(b + 1) & 1][0] = lds128(addr + (2 * b + 2) * PITCH); v[(b + 1) & 1][1] = lds128(addr + (2 * b + 3) * PITCH); }
    acc[0] += __uint_as_float(zero_here());
    fma8(acc, v[b & 1][0], x[2 * b]); fma8(acc, v[b & 1][1], x[2 * b + 1]);
  }
}
__device__ __forceinline__ float swiglu(float g, float u) {
  g = bf16r(g); u = bf16r(u);
  return bf16r(bf16r(g * fast_rcp(1.f + __expf(-g))) * u);
}

#define CT(slot) do {} while (0)
#define TIM(slot) do {} while (0)

constexpr int H_BUF0 = 0, H_BUF1 = 16384, H_RED = 32768, H_KEYS = H_RED + 1024, H_ROW = H_KEYS + 1024, H_ACT = H_ROW + 8192, H_PART = H_ACT + 4096;
__device__ __forceinline__ void hsync() { bar_sync(NB_H, 256); }
template<int N> __device__ __forceinline__ void block_sum(float (&v)[N], int warp, int lane) {
#pragma unroll
  for (int i = 0; i < N; i++) v[i] = warp_sum(v[i]);
  hsync();
  if (lane == 0) {
#pragma unroll
    for (int i = 0; i < N; i++) SM<float>(H_RED + (i * 8 + warp) * 4) = v[i];
  }
  hsync();
#pragma unroll
  for (int i = 0; i < N; i++) {
    const float4 a = SM<float4>(H_RED + i * 32), b = SM<float4>(H_RED + i * 32 + 16);
    v[i] = ((a.x + a.y) + (a.z + a.w)) + ((b.x + b.y) + (b.z + b.w));
  }
}
__device__ __forceinline__ void fft_first(int j, float2 v0, float2 v1, float2 v2, float2 v3) {
  const float2 a = make_float2(v0.x + v2.x, v0.y + v2.y), b = make_float2(v0.x - v2.x, v0.y - v2.y);
  const float2 c = make_float2(v1.x + v3.x, v1.y + v3.y), d = make_float2(v1.y - v3.y, v3.x - v1.x);
  SM<float4>(H_BUF1 + j * 32) = make_float4(a.x + c.x, a.y + c.y, b.x + d.x, b.y + d.y);
  SM<float4>(H_BUF1 + j * 32 + 16) = make_float4(a.x - c.x, a.y - c.y, b.x - d.x, b.y - d.y);
}
template<int NB> __device__ __forceinline__ void fft_passes(int tid) {
  constexpr int q = 256 * NB;
#pragma unroll 1
  for (int ps = 1; ps < 5; ps++) {
    const int ns = 1 << (2 * ps), k = tid & (ns - 1);
    float s1, c1;
    __sincosf(-1.57079632679f * __fdividef((float)k, (float)ns), &s1, &c1);
    const float c2 = c1 * c1 - s1 * s1, s2 = 2.f * c1 * s1, c3 = c1 * c2 - s1 * s2, s3 = c1 * s2 + s1 * c2;
    hsync();
#pragma unroll
    for (int i = 0; i < NB; i++) {
      const int j = tid + 256 * i;
      const float2* in = &SM<float2>((ps & 1) ? H_BUF1 : H_BUF0);
      float2* o = &SM<float2>((ps & 1) ? H_BUF0 : H_BUF1) + (j - k) * 4 + k;
      const float2 v0 = in[j], x1 = in[j + q], x2 = in[j + 2 * q], x3 = in[j + 3 * q];
      const float2 v1 = make_float2(x1.x * c1 - x1.y * s1, x1.x * s1 + x1.y * c1);
      const float2 v2 = make_float2(x2.x * c2 - x2.y * s2, x2.x * s2 + x2.y * c2);
      const float2 v3 = make_float2(x3.x * c3 - x3.y * s3, x3.x * s3 + x3.y * c3);
      const float2 a = make_float2(v0.x + v2.x, v0.y + v2.y), b = make_float2(v0.x - v2.x, v0.y - v2.y);
      const float2 c = make_float2(v1.x + v3.x, v1.y + v3.y), d = make_float2(v1.y - v3.y, v3.x - v1.x);
      o[0] = make_float2(a.x + c.x, a.y + c.y); o[ns] = make_float2(b.x + d.x, b.y + d.y);
      o[2 * ns] = make_float2(a.x - c.x, a.y - c.y); o[3 * ns] = make_float2(b.x - d.x, b.y - d.y);
    }
  }
  hsync();
}
template<int NR> __device__ __forceinline__ void ln_rows(const float (&h)[NR][4], float (&hn)[NR][4], int warp, int lane) {
  float s[NR], q[NR];
#pragma unroll
  for (int i = 0; i < NR; i++) s[i] = (h[i][0] + h[i][1]) + (h[i][2] + h[i][3]);
  block_sum(s, warp, lane);
#pragma unroll
  for (int i = 0; i < NR; i++) {
    s[i] *= 1.f / 1024.f; q[i] = 0.f;
#pragma unroll
    for (int z = 0; z < 4; z++) q[i] = fmaf(h[i][z] - s[i], h[i][z] - s[i], q[i]);
  }
  block_sum(q, warp, lane);
#pragma unroll
  for (int i = 0; i < NR; i++) {
    const float mb = bf16r(s[i]), inv = fast_rcp(ref_sd(q[i] * (1.f / 1024.f)));
#pragma unroll
    for (int z = 0; z < 4; z++) hn[i][z] = bf16r(bf16r(h[i][z] - mb) * inv);
  }
}
__device__ __forceinline__ float routed_out(float h, float hn, float y, float r) {
  const float sig = bf16r(fast_rcp(1.f + __expf(-r)));
  return h + bf16r(hn + bf16r(bf16r(y) * sig));
}

__device__ __forceinline__ void helper_cta(const Params& p, const int hi, const uint32_t t_entry) {
  const int tid = threadIdx.x, warp = tid >> 5, lane = tid & 31;
  const float w0 = ldbf(p.wr + tid), w1 = ldbf(p.wr + tid + 256), w2 = ldbf(p.wr + tid + 512), w3 = ldbf(p.wr + tid + 768), wf = ldbf(p.wr);
  const uint32_t tag = ld_relaxed32(&p.sc->epoch) + 1;
  pkt_clear128(&p.sc->u[hi * 512 + tid * 2]);
  if (tid == 0 && w0 != 123.f) TIM(12);
  fft_first(tid, make_float2(w0, 0.f), make_float2(w1, 0.f), make_float2(w2, 0.f), make_float2(w3, 0.f));
  fft_passes<1>(tid);
  const uint32_t c0 = code_of(tag), c1 = c0 >> 1;
  {
    const float off = wf - SM<float>(H_BUF1) * (1.f / 1024.f);
    const float4 v = SM<float4>(H_BUF1 + tid * 32), u = SM<float4>(H_BUF1 + tid * 32 + 16);
    pkt_st128(&p.sc->u[hi * 512 + ((tid & 192) + (tid & 1) * 32 + ((tid >> 1) & 31)) * 2], with_bit(pack_bf16((tid ? v.x : 0.f) - off, v.z - off), c0), with_bit(pack_bf16(v.y, v.w), c1),
              with_bit(pack_bf16(u.x - off, u.z - off), c0), with_bit(pack_bf16(u.y, u.w), c1));
    if (tid < 64) pkt_clear128(&p.sc->cl[(hi * 32 + (tid >> 1)) * 16 + (tid & 1) * 2]);
    hsync();
  }
  if (tid == 0) TIM(0);
  {
    float tw[8];
#pragma unroll
    for (int i = 0; i < 4; i++) __sincosf((float)(tid + 256 * i) * (-6.28318530718f / 2048.f), &tw[2 * i], &tw[2 * i + 1]);
    wait_clk(t_entry, Z_CLK);
    uint2 z[8]; uint32_t n = 0;
    bool more;
#pragma unroll 1
    do {
      uint32_t bad = 0;
#pragma unroll
      for (int i = 0; i < 8; i++) z[i] = pkt_ld64(reinterpret_cast<const uint2*>(&p.sc->xz[tid]) + 512 * i + 1);
#pragma unroll
      for (int i = 0; i < 8; i++) chk(bad, z[i].y, tag);
      more = !(!bad) && ++n < SPIN_LIMIT;
      if (more) { __nanosleep(150); }
    } while (more);
#pragma unroll
    for (int i = 0; i < 2; i++)
      fft_first(tid + 256 * i, make_float2(bf_lo(z[i].x), bf_hi(z[i].x)), make_float2(bf_lo(z[i + 2].x), bf_hi(z[i + 2].x)),
                make_float2(bf_lo(z[i + 4].x), bf_hi(z[i + 4].x)), make_float2(bf_lo(z[i + 6].x), bf_hi(z[i + 6].x)));
    if (tid == 0) TIM(7);
    fft_passes<2>(tid);
    if (tid == 0) TIM(1);
    uint32_t k8[8];
#pragma unroll
    for (int i = 0; i < 4; i++) {
      const int k = tid + 256 * i;
      const float2 v0 = SM<float2>(H_BUF1 + k * 8), v1 = SM<float2>(H_BUF1 + (k + 1024) * 8);
      const float w = v1.x * tw[2 * i + 1] - v1.y * tw[2 * i];
      const uint32_t a = __float_as_uint(v0.x + w), b = __float_as_uint(v0.x - w);
      k8[2 * i] = (((a & 0x80000000u) ? ~a : (a | 0x80000000u)) & ~2047u) | k;
      k8[2 * i + 1] = (((b & 0x80000000u) ? ~b : (b | 0x80000000u)) & ~2047u) | (k + 1024);
    }
    uint32_t lim = 0xFFFFFFFFu;
#pragma unroll 1
    for (int r = 0; r < 4; r++) {
      uint32_t mx = 0;
#pragma unroll
      for (int i = 0; i < 8; i++) mx = max(mx, k8[i] <= lim ? k8[i] : 0u);
      mx = __reduce_max_sync(0xffffffffu, mx);
      if (lane == 0) SM<uint32_t>(H_KEYS + (warp * 4 + r) * 4) = mx;
      lim = mx - 1;
    }
    hsync();
    if (tid < 32) {
      const uint32_t me = SM<uint32_t>(H_KEYS + tid * 4);
      int rank = 0;
#pragma unroll
      for (int i = 0; i < 8; i++) { const uint4 o = SM<uint4>(H_KEYS + i * 16); rank += (o.x > me) + (o.y > me) + (o.z > me) + (o.w > me); }
      if (rank < 8) SM<uint16_t>(H_KEYS + 256 + rank * 2) = me & 2047u;
    }
    hsync();
    if (tid >= 128) pkt_st64(&p.sc->cl[(hi * 32 + ((tid - 128) >> 2)) * 16 + (tid & 3)], SM<uint32_t>(H_KEYS + 256 + (tid & 3) * 4), tag);
  }
  const uint32_t cpair = SM<uint32_t>(H_KEYS + 256 + hi * 4);
  const int ca = cpair & 0xFFFF, cb = cpair >> 16;
  if (tid < 128) prefetch_l2(((tid & 32) ? p.Wim : p.Wre) + (size_t)((tid & 64) ? cb : ca) * 2048 + lane * 64);
  if (tid == 0) TIM(2);
}

__device__ __forceinline__ void slow_path(const Params& p, int grp, int eps, uint32_t tag, uint32_t key, int win, float mb, float inv) {
  const int tid = threadIdx.x + zero_here(), warp = tid >> 5, lane = tid & 31;
  uint32_t best = __reduce_max_sync(0xffffffffu, poll64(&p.sc->key[tid & 127], tag, 200));
  if (lane == 0) SM<uint32_t>(H_KEYS + warp * 4) = best;
  hsync();
  { const uint4 b4 = SM<uint4>(H_KEYS); best = max(max(b4.x, b4.y), max(b4.z, b4.w)); }
  const int tw = key_row(best), col = eps * 128 + (tid & 127);
  if ((tw >> 7) != grp) return;
  if (tid < 128) {
    const int pos = (col >> 4) * 8 + (col & 7);
    const uint32_t a = poll64(&p.sc->ch[win * 512 + pos], tag, 100);
    const float hc = (col & 8) ? bf_hi(a) : bf_lo(a);
    poll64(&p.sc->rdone[col >> 3], tag, 100);
    st_bf16(p.out + key_row(key) * 1024 + col, hc + bf16r(bf16r(hc - mb) * inv));
  }
  const uint32_t h0 = poll64(&p.sc->hrow[(tw >> 4) * 512 + 2 * tid], tag, 100), h1 = poll64(&p.sc->hrow[(tw >> 4) * 512 + 2 * tid + 1], tag, 100);
  float h[1][4] = {{bf_lo(h0), bf_hi(h0), bf_lo(h1), bf_hi(h1)}}, hn[1][4];
  ln_rows<1>(h, hn, warp, lane);
  SM<float4>(H_ROW + tid * 16) = make_float4(hn[0][0], hn[0][1], hn[0][2], hn[0][3]);
  SM<float4>(H_ROW + 4096 + tid * 16) = make_float4(h[0][0], h[0][1], h[0][2], h[0][3]);
  hsync();
#pragma unroll 1
  for (int ph = 0; ph < 2; ph++) {
    const int part = min(tid / 56, 3), fh = tid >> 7, len = ph ? 224 : 512, ld = ph ? 1024 : 3584;
    const bf16* wp = ph ? p.wdown + (eps * 448 + fh * 224) * 1024 + (tid & 127) * 8
                        : ((part & 1) ? p.wup : p.wgate) + (part >> 1) * 512 * 3584 + eps * 448 + min(tid - part * 56, 55) * 8;
    const int xo = ph ? H_ACT + fh * 224 * 4 : H_ROW + (part >> 1) * 2048;
    float acc[8] = {0.f, 0.f, 0.f, 0.f, 0.f, 0.f, 0.f, 0.f};
#pragma unroll 8
    for (int d = 0; d < (len & ~7); d++) fma8(acc, ldg_nc128(wp + d * ld), SM<float>(xo + d * 4));
    SM<float4>(H_PART + tid * 32) = make_float4(acc[0], acc[1], acc[2], acc[3]);
    SM<float4>(H_PART + tid * 32 + 16) = make_float4(acc[4], acc[5], acc[6], acc[7]);
    hsync();
    if (ph) break;
#pragma unroll 1
    for (int f = tid; f < 448; f += 256)
      SM<float>(H_ACT + f * 4) = swiglu(SM<float>(H_PART + f * 4) + SM<float>(H_PART + (896 + f) * 4), SM<float>(H_PART + (448 + f) * 4) + SM<float>(H_PART + (1344 + f) * 4));
    hsync();
  }
#pragma unroll 1
  for (int e = tid; e < 1024; e += 256) pkt_st64(&p.sc->fpart[eps * 1024 + e], __float_as_uint(SM<float>(H_PART + e * 4) + SM<float>(H_PART + (1024 + e) * 4)), tag);
  if (tid < 128) {
    float y = 0.f;
#pragma unroll 1
    for (int q = 0; q < 8; q++) y += __uint_as_float(poll64(&p.sc->fpart[q * 1024 + col], tag, 200));
    st_bf16(p.out + tw * 1024 + col, routed_out(SM<float>(H_ROW + 4096 + col * 4), SM<float>(H_ROW + col * 4), y, key_val(best)));
  }
}

template<int MAP>
__global__ void __cluster_dims__(2, 1, 1) __launch_bounds__(NTHR, 1)
fnet_moe_kernel(const __grid_constant__ Params p) {
  const uint32_t t_entry = clk32();
  uint32_t smid;
  asm("mov.u32 %0, %%smid;" : "=r"(smid));
  const int tpc = smid >> 1, m = blockIdx.x & 1;
  if (MAP == 1 ? tpc >= 64 : (tpc >> 1) == 30) {
    if (threadIdx.x < 256) helper_cta(p, (tpc & 1) * 2 + m, t_entry);
    return;
  }
  const uint32_t sb = smem_u32(smem_raw);
  const int tid = threadIdx.x, lane = tid & 31;
  const int e7 = ((tpc - 32) * 37) >> 8;
  const int tau = MAP == 1 || tpc < 32 ? (tpc & 7) : (tpc < 60 ? tpc - 31 - 7 * e7 : 0);
  const int eps = MAP == 1 || tpc < 32 ? (tpc >> 3) : (tpc < 60 ? 4 + e7 : tpc - 58);
  const int cid = tau * 16 + eps * 2 + m;
  auto BAR = [&](int i) { return sb + OFF_BAR + 8 * i; };
  const CUtensorMap* tmD = &p.tmD0 + m;
#define LOAD_STREAM(d, tm, bar, c0, c1) tma_load_2d_hint(d, tm, bar, c0, c1, pol_ef)
#define LOAD_W tma_load_2d
#define LOAD_D tma_load_2d
#define LOAD_X tma_load_2d
#define LOAD_F LOAD_STREAM

  uint32_t tag = 0;
  uint4 wq = make_uint4(0, 0, 0, 0);
  if ((tid >> 5) == 4) {
    if (elect_one()) {
      const uint64_t pol_ef = policy_evict_first();
#pragma unroll
      for (int k = 0; k < 4; k++) mbar_init(BAR(B_FULL + k), 1);
      asm volatile("fence.mbarrier_init.release.cluster;" ::: "memory");
#pragma unroll
      for (int k = 0; k < 4; k++) {
        mbar_expect_tx(BAR(B_FULL + k), ST_BYTES);
        tma_load_2d(sb + k * ST_BYTES + A_BYTES, &p.tmX, BAR(B_FULL + k), k * 64, tau * 256);
        LOAD_D(sb + k * ST_BYTES, tmD, BAR(B_FULL + k), k * 64, eps * 128);
        TIM(k);
      }
    }
  } else if ((tid >> 5) == 1) {
    if (elect_one()) {
#pragma unroll
      for (int s = 0; s < 4; s++) mbar_init(BAR(B_EMPTY + s), 1);
#pragma unroll
      for (int s = 0; s < 8; s++) { mbar_init(BAR(B_EP + s), 4); mbar_init(BAR(B_AW + s), 1); }
      mbar_init(BAR(B_STAT), 4); mbar_init(BAR(B_WC), 1); mbar_init(BAR(B_CD), 2);
      mbar_init(BAR(B_HR), 1); mbar_init(BAR(B_INFO), 1); mbar_init(BAR(B_PEER), 1);
      mbar_init(BAR(B_XCH), 1); mbar_init(BAR(B_XCH + 1), 1); mbar_init(BAR(B_GUX), 1);
      asm volatile("fence.mbarrier_init.release.cluster;" ::: "memory");
      mbar_expect_tx(BAR(B_XCH), 16384); mbar_expect_tx(BAR(B_XCH + 1), 16384); mbar_expect_tx(BAR(B_GUX), 256);
    }
  } else if (tid >= 256) {
    if (START_PF) prefetch_l2(((tid & 64) ? (cid < 64 ? p.Dre : p.Dim) + (cid & 63) * 16384 : p.x + cid * 16384) + ((tid >> 2) & 15) * 1024 + (tid & 3) * 64);
    tag = ld_relaxed32(&p.sc->epoch + threadIdx.y);
    wq = ldg128(p.wr + (tid & 127) * 8);
  }
  const int warp = __shfl_sync(0xffffffffu, tid >> 5, 0);
  __syncthreads();
  asm volatile("barrier.cluster.arrive.relaxed.aligned;" ::: "memory");

  if (warp >= 8) {
    reg_dec<72>();
    cluster_wait();
    tag = __shfl_sync(0xffffffffu, tag, 0) + 1;
    const int cid0 = cid;
    const uint32_t tag0 = tag, sb0 = sb;
    int a, lane, j, cid, tau, eps, m, grp, abrow, fc, src;
    uint32_t tag, c0, c1, sb, buf, bar0;
    bool ffn;
    auto BAR = [&](int i) { return sb + OFF_BAR + 8 * i; };
    auto fresh_ids = [&]() {
      const uint32_t z = uniform_zero_here();
      uint32_t l; asm volatile("mov.u32 %0, %%laneid;" : "=r"(l));
      a = warp - 8 + z; lane = l; j = a * 32 + l;
      cid = cid0 + z; tau = cid >> 4; eps = (cid >> 1) & 7; m = cid & 1; grp = tau * 2 + m; abrow = m * 1024 + eps * 128;
      ffn = eps > 0; fc = (tau * 7 + eps - 1) * 64; src = (fc >> 5) + m;
      tag = tag0 + z; c0 = code_of(tag); c1 = c0 >> 1;
      sb = sb0 + z; buf = sb + OFF_AUX + a * 8192; bar0 = BAR(B_AW + 2 * a);
    };
    fresh_ids();
    if (a == 0 && lane < 16) pkt_clear128(&p.sc->xz[cid * 16 + lane]);
    if (lane < 2) pkt_clear128(&p.sc->dsum[cid * 16 + a * 4 + lane * 2]);
    if (a == 3 && lane < 6) pkt_clear128((lane < 4 ? &p.sc->abdone[(cid * 2 + (lane >> 1)) * 32] : &p.sc->abflag[cid * 32]) + (lane & 1) * 4);
    {
      const float s = warp_sum(((bf_lo(wq.x) + bf_hi(wq.x)) + (bf_lo(wq.y) + bf_hi(wq.y))) + ((bf_lo(wq.z) + bf_hi(wq.z)) + (bf_lo(wq.w) + bf_hi(wq.w))));
      if ((j >> 4) == eps) SM<uint4>(OFF_WR + (j & 15) * 16) = wq;
      if (lane == 0) { SM<float>(INFO_DS + a * 4) = s; SM<uint32_t>(INFO_ONES + a * 4) = 0x3F803F80u; }
    }
    const bf16* xrows = p.x + (cid * 16 + a * 4) * 1024;
    const bf16* drows = (cid < 64 ? p.Dre : p.Dim) + ((cid & 63) * 16 + a * 4) * 1024;
    if (XROW_PF) {
      wait_clk(t_entry, XROW_PF);
      prefetch_l2(xrows + lane * 64); prefetch_l2(xrows + 2048 + lane * 64);
    }
    fresh_ids();
    {
      wait_clk(t_entry, U_CLK);
      uint4 u[8]; uint32_t n = 0;
      bool more;
#pragma unroll 1
      do {
        uint32_t bad = 0;
#pragma unroll
        for (int q = 0; q < 8; q++) u[q] = pkt_ld128(&p.sc->u[a * 512 + lane * 2] + q * 64);
        if (n == 0 && lane < 2) { mbar_expect_tx(bar0 + lane * 8, 4096); bulk_load(buf + lane * 4096, xrows + lane * 2048, 4096, bar0 + lane * 8); }
#pragma unroll
        for (int q = 0; q < 8; q++) chk_code(bad, u[q], c0, c1);
        more = !(!__any_sync(0xffffffffu, bad & 1)) && ++n < SPIN_LIMIT;
        if (more) { __nanosleep(200); }
      } while (more);
      if (j == 0) TIM(96);
      if (DROW_PF) { prefetch_l2(drows + lane * 64); prefetch_l2(drows + 2048 + lane * 64); }
#pragma unroll 1
      for (int r2 = 0; r2 < 2; r2++) {
        float v8[8];
        mbar_wait(bar0 + r2 * 8, 0);
        if (lane == 0) TIM(140 + r2 * 4 + a);
#pragma unroll
        for (int r = 0; r < 2; r++) {
          float s0 = 0.f, s1 = 0.f, q0 = 0.f, q1 = 0.f;
          uint32_t zr = 0, zi = 0;
#pragma unroll
          for (int q = 0; q < 4; q++) {
            const uint4 v = lds128(buf + r2 * 4096 + r * 2048 + (q * 32 + lane) * 16);
            const uint32_t ww[4] = {v.x, v.y, v.z, v.w};
#pragma unroll
            for (int z = 0; z < 4; z++) {
              const float lo = bf_lo(ww[z]), hi = bf_hi(ww[z]);
              s0 += lo; s1 += hi; q0 = fmaf(lo, lo, q0); q1 = fmaf(hi, hi, q1);
            }
            zr = bfma2(v.x, u[2 * q].x, zr); zi = bfma2(v.x, u[2 * q].y, zi); zr = bfma2(v.y, u[2 * q].z, zr); zi = bfma2(v.y, u[2 * q].w, zi);
            zr = bfma2(v.z, u[2 * q + 1].x, zr); zi = bfma2(v.z, u[2 * q + 1].y, zi); zr = bfma2(v.w, u[2 * q + 1].z, zr); zi = bfma2(v.w, u[2 * q + 1].w, zi);
          }
          v8[4 * r] = s0 + s1; v8[4 * r + 1] = q0 + q1; v8[4 * r + 2] = bf_lo(zr) + bf_hi(zr); v8[4 * r + 3] = bf_lo(zi) + bf_hi(zi);
        }
        fold<8>(v8, 16, lane);
        if (lane == 0) { mbar_expect_tx(bar0 + r2 * 8, 4096); bulk_load(buf + r2 * 4096, drows + r2 * 2048, 4096, bar0 + r2 * 8); }
        fold<4>(v8, 8, lane); fold<2>(v8, 4, lane);
        v8[0] += __shfl_xor_sync(0xffffffffu, v8[0], 2);
        v8[0] += __shfl_xor_sync(0xffffffffu, v8[0], 1);
        SM<float>(OFF_REM + a * 64 + r2 * 32 + (lane >> 2) * 4) = v8[0];
        if (lane == 0) TIM(148 + r2 * 4 + a);
      }
    }
    bar_sync(NB_AUX, 128);
    fresh_ids();
    if (a == 0 && lane < 16) {
      const float4 v = SM<float4>(OFF_REM + lane * 16);
      const float mean = v.x * (1.f / 1024.f), rs = fast_rcp(ref_sd(fmaxf(v.y * (1.f / 1024.f) - mean * mean, 0.f)));
      pkt_st128(&p.sc->xz[cid * 16 + lane], __float_as_uint(bf16r(mean)) | (tag & 0xFFFFu), __float_as_uint(rs), pack_bf16(v.z * rs, v.w * rs), tag);
    }
    if (j == 32) { const float4 v = SM<float4>(INFO_DS); SM<float2>(INFO_WSUM) = make_float2((v.x + v.y) + (v.z + v.w), __uint_as_float(tag)); }
    if (j == 0) TIM(98);
#pragma unroll 1
    for (int r2 = 0; r2 < 2; r2++) {
      mbar_wait(bar0 + r2 * 8, 1);
      uint4 dv[8];
#pragma unroll
      for (int q = 0; q < 8; q++) dv[q] = lds128(buf + r2 * 4096 + (lane >> 4) * 2048 + q * 256 + (lane & 15) * 16);
      float s0 = __uint_as_float(zero_here()), s1 = 0.f;
#pragma unroll
      for (int q = 0; q < 8; q++) {
        const uint4 v = dv[q];
        s0 += (bf_lo(v.x) + bf_lo(v.y)) + (bf_lo(v.z) + bf_lo(v.w)); s1 += (bf_hi(v.x) + bf_hi(v.y)) + (bf_hi(v.z) + bf_hi(v.w));
      }
      s0 += s1;
#pragma unroll
      for (int o = 8; o > 0; o >>= 1) s0 += __shfl_xor_sync(0xffffffffu, s0, o);
      SM<float>(INFO_DS2 + (a * 4 + r2 * 2 + (lane >> 4)) * 4) = s0;
    }
    bar_sync(NB_AUX, 128);
    if (a == 1 && lane < 16) pkt_st64(&p.sc->dsum[cid * 16 + lane], SM<uint32_t>(INFO_DS2 + lane * 4), tag);
    if (j == 0) TIM(99);
    uint4* cpart = &p.sc->cpart[grp * 512 + eps * 64];
    pkt_clear128(cpart + (a * 8192 + lane)); pkt_clear128(cpart + (a * 8192 + lane) + 32);
    if (a == 3) { pkt_st64(&p.sc->ch[(lane >> 2) * 512 + cid * 4 + (lane & 3)], 0, 0); if (lane < 8) pkt_clear128(&p.sc->cs[cid * 8 + lane]); }
    {
      wait_clk(clk32(), XS_DELAY);
      uint2 v0, v1, cs; uint32_t n = 0;
      const uint32_t t16 = tag & 0xFFFFu;
      bool more;
#pragma unroll 1
      do {
        v0 = pkt_ld64(&p.sc->xz[tau * 256 + j]); v1 = pkt_ld64(&p.sc->xz[tau * 256 + j] + 128); cs = pkt_ld64(&p.sc->dsum[m * 1024 + eps * 128 + j]);
        more = !(__all_sync(0xffffffffu, (v0.x & 0xFFFFu) == t16 && (v1.x & 0xFFFFu) == t16 && cs.y == tag)) && ++n < SPIN_LIMIT;
        if (more) { __nanosleep(200); }
      } while (more);
      const int ro = OFF_RS + ((j & 7) >> 1) * 272 + (j >> 3) * 8 + (j & 1) * 4;
      SM<uint32_t>(ro) = v0.y ^ (m << 31); SM<uint32_t>(ro + 128) = v1.y ^ (m << 31);
      const uint32_t n0 = (v0.x >> 16) ^ 0x8000u, n1 = (v1.x >> 16) ^ 0x8000u;
      SM<uint4>(OFF_EXB + j * 16) = make_uint4(n0 | (n0 << 16), n0, 0, 0);
      SM<uint4>(OFF_EXB + 2048 + j * 16) = make_uint4(n1 | (n1 << 16), n1, 0, 0);
      const float c = 0.5f * __uint_as_float(cs.x), hi = bf16r(c), mid = bf16r(c - hi), lo = bf16r((c - hi) - mid);
      SM<uint4>(OFF_EXA + j * 16) = make_uint4((__float_as_uint(hi) >> 16) | __float_as_uint(mid), __float_as_uint(lo) >> 16, 0, 0);
      fence_async_smem();
      __syncwarp();
      if (lane == 0) mbar_arrive(BAR(B_STAT));
    }
    if (j == 0) TIM(100);
    auto set_flags = [&](int half) {
      uint32_t* fl = lane == 0 && half == 0 ? &p.sc->abflag[cid * 32] : &p.sc->abdone[(((cid & 15) + (lane & 7) * 16) * 2 + half) * 32 + tau];
      if (lane == 0) {
        asm volatile("fence.proxy.async.global;" ::: "memory");
        asm volatile("st.release.gpu.global.b32 [%0], %1;" :: "l"(fl), "r"(tag) : "memory");
        TIM(69 + half * 8);
      }
      __syncwarp();
      if (lane >= 8 && lane < 16) st_relaxed32(fl, tag);
    };
    auto all_published = [&](int half) {
      uint32_t n = 0;
#pragma unroll 1
      while (!__all_sync(0xffffffffu, ld_acquire32(&p.sc->abdone[(cid * 2 + half) * 32 + (lane & 7)]) == tag) && ++n < SPIN_LIMIT) {}
      if (lane == 0) {
        asm volatile("fence.proxy.async.global;" ::: "memory");
        mbar_arrive(BAR(B_ALL + half));
        TIM(80 + half);
      }
      __syncwarp();
    };
    if (TM_PF && j < 3) asm volatile("prefetch.tensormap [%0];" :: "l"(j == 0 ? &p.tmAbS : j == 1 ? &p.tmAbL : m ? &p.tmW1 : &p.tmW0) : "memory");
    {
      if (a == 3) {
        const uint32_t cl = poll64_warp(&p.sc->cl[cid * 16 + (lane & 3)], tag, 100);
        if (lane == 0) TIM(101);
        const bf16* wm = (m ? p.Wim : p.Wre) + tau * 256 + lane * 8;
        uint4 v[8];
#pragma unroll
        for (int i = 0; i < 8; i++) v[i] = ldg128(wm + ((__shfl_sync(0xffffffffu, cl, i >> 1) >> ((i & 1) * 16)) & 2047) * 2048);
        const int pos = cid * 4 + (lane & 3);
        const bf16* xc = p.x + ((__shfl_sync(0xffffffffu, cl, lane >> 3) >> ((lane & 4) * 4)) & 2047) * 1024 + (pos >> 3) * 16 + (pos & 7);
        const float x0 = ldbf(xc), x1 = ldbf(xc + 8), w0 = ldbf(p.wr + (pos >> 3) * 16 + (pos & 7)), w1 = ldbf(p.wr + (pos >> 3) * 16 + (pos & 7) + 8);
        if (lane < 4) SM<uint32_t>(INFO_CAND + lane * 4) = cl;
#pragma unroll
        for (int i = 0; i < 8; i++) SM<uint4>(OFF_WC + (lane >> 3) * 1024 + i * 128 + (((lane & 7) ^ i) << 4)) = v[i];
        fence_async_smem();
        __syncwarp();
        if (lane == 0) { mbar_arrive(BAR(B_WC)); TIM(102); }
        mbar_wait(BAR(B_CD), 0);
        wait_clk(clk32(), CP_DELAY);
        uint32_t n = 0;
        bool more;
#pragma unroll 1
        do {
          uint32_t bad = 0;
#pragma unroll
          for (int i = 0; i < 8; i++) v[i] = pkt_ld128(&p.sc->cpart[((lane >> 3) * 16 + ((lane >> 2) & 1)) * 512 + pos] + i * 1024);
#pragma unroll
          for (int i = 0; i < 8; i++) chk_code(bad, v[i], c0, c1);
          more = !(!__any_sync(0xffffffffu, bad & 1)) && ++n < SPIN_LIMIT;
          if (more) { __nanosleep(200); }
        } while (more);
        float y[4] = {0.f, 0.f, 0.f, 0.f};
#pragma unroll
        for (int i = 0; i < 8; i++) { y[0] += no_bit(v[i].x); y[2] += no_bit(v[i].y); y[1] += no_bit(v[i].z); y[3] += no_bit(v[i].w); }
#pragma unroll
        for (int i = 0; i < 4; i++) y[i] = bf16r(y[i]);
        __syncwarp();
        fold<4>(y, 4, lane);
        const uint32_t hp = pack_bf16(x0 + bf16r(y[0]), x1 + bf16r(y[1]));
        pkt_st64(&p.sc->ch[(lane >> 2) * 512 + pos], hp, tag);
        float st[3] = {bf_lo(hp) + bf_hi(hp), bf_lo(hp) * bf_lo(hp) + bf_hi(hp) * bf_hi(hp), bf_lo(hp) * w0 + bf_hi(hp) * w1};
#pragma unroll
        for (int o = 1; o < 4; o <<= 1) {
#pragma unroll
          for (int i = 0; i < 3; i++) st[i] += __shfl_xor_sync(0xffffffffu, st[i], o);
        }
        if ((lane & 3) == 0) pkt_st128(&p.sc->cs[cid * 8 + (lane >> 2)], with_bit(st[0], c0), with_bit(st[1], c1), __float_as_uint(st[2]), tag);
        if (lane == 0) TIM(119);
      }
      if (a < 2) {
        if (lane == 0) {
          if (a == 1) mbar_wait(BAR(B_LO), 0);
          const uint32_t t1 = clk32();
#pragma unroll 1
          for (int i = 0; i < 4; i++) {
            if (a == 1) wait_clk(t1, HI_DELAY + i * HI_PACE);
            const int w = i >> 1, c = 2 * a + (i & 1);
            mbar_wait(BAR(B_EP + w * 4 + c), 0);
            TIM(64 + a * 8 + i);
            fence_async_smem();
            tma_store_2d(&p.tmAbS, sb + c * ST_BYTES + w * 8192, tau * 256 + c * 64, abrow + w * 64);
          }
          bulk_commit();
          bulk_wait_all();
          mbar_arrive(BAR(a ? B_HR : B_LO));
          TIM(68 + a * 8);
        }
        set_flags(a);
        if (a == 0) { __nanosleep(500); all_published(0); }
      } else if (a == 2) {
        if (elect_one()) {
          const uint32_t* fl = &p.sc->abflag[((cid + 16) & 127) * 32];
          mbar_wait(BAR(B_LO), 0);
          mbar_wait(BAR(B_FULL), 0); mbar_wait(BAR(B_FULL + 1), 0);
          __nanosleep(LO_NS);
          uint32_t n = 0;
#pragma unroll 1
          while (ld_acquire32(fl) != tag && ++n < SPIN_LIMIT) {}
          asm volatile("fence.proxy.async.global;" ::: "memory");
          tma_load_2d(sb, &p.tmAbL, BAR(B_FULL), k_col(tau, 4), abrow);
          tma_load_2d(sb + ST_BYTES, &p.tmAbL, BAR(B_FULL + 1), k_col(tau, 5), abrow);
          TIM(130);
          mbar_wait(BAR(B_HR), 0); mbar_wait(BAR(B_FULL + 2), 0); mbar_wait(BAR(B_ALL), 0);
          tma_load_2d(sb + 2 * ST_BYTES, &p.tmAbL, BAR(B_FULL + 2), k_col(tau, 6), abrow);
          TIM(132);
          mbar_wait(BAR(B_EMPTY), 0);
          tma_load_2d(sb + 3 * ST_BYTES, &p.tmAbL, BAR(B_FULL + 3), k_col(tau, 7), abrow);
          TIM(133);
        }
      }
      __syncwarp();
    }
    mbar_wait(BAR(B_CD), 0);
    const uint64_t pol_ef = policy_evict_first();
    auto load_unit = [&](int v) {
      if (elect_one()) {
        const uint32_t dst = buf + (v & 1) * 4096, bar = bar0 + (v & 1) * 8;
        mbar_expect_tx(bar, 4096);
        if (v < 8) {
          LOAD_F(dst, &p.tmG, bar, fc, m * 512 + (a * 8 + v) * 16);
          LOAD_F(dst + 2048, &p.tmU, bar, fc, m * 512 + (a * 8 + v) * 16);
        } else LOAD_F(dst, &p.tmDn, bar, a * 256, src * 32 + (v - 8) * 8);
      }
    };
    if (TM_PF && j < 3) asm volatile("prefetch.tensormap [%0];" :: "l"(j == 0 ? &p.tmG : j == 1 ? &p.tmU : &p.tmDn) : "memory");
    bar_sync(NB_AUX, 128);
    if (!LU_LATE && ffn) { load_unit(0); load_unit(1); }
    wait_clk(clk32(), CS_DELAY);
    fresh_ids();
    {
      uint4 v[8], r0, r1; uint32_t n = 0;
      bool more;
#pragma unroll 1
      do {
#pragma unroll
        for (int i = 0; i < 8; i++) v[i] = CS_WEAK ? ldg128(&p.sc->cs[j] + i * 128) : pkt_ld128(&p.sc->cs[j] + i * 128);
        r0 = pkt_ld128(&p.sc->ch[m * 256 + 2 * j]); r1 = pkt_ld128(&p.sc->ch[m * 256 + 2 * j] + 512);
        if (LU_LATE && n == 0 && ffn) { load_unit(0); load_unit(1); }
        uint32_t bad = 0;
#pragma unroll
        for (int i = 0; i < 8; i++) { chk(bad, v[i].x, c0); chk(bad, v[i].y, c1); }
        bad &= 1;
#pragma unroll
        for (int i = 0; i < 8; i++) chk(bad, v[i].w, tag);
        more = __any_sync(0xffffffffu, bad) && ++n < SPIN_LIMIT;
        if (more) __nanosleep(200);
      } while (more);
      if (j == 0) TIM(97);
      float st[3] = {0.f, 0.f, 0.f};
#pragma unroll
      for (int i = 0; i < 8; i++) { st[0] += no_bit(v[i].x); st[1] += no_bit(v[i].y); st[2] += __uint_as_float(v[i].z); }
#pragma unroll
      for (int o = 8; o < 32; o <<= 1) {
#pragma unroll
        for (int i = 0; i < 3; i++) st[i] += __shfl_xor_sync(0xffffffffu, st[i], o);
      }
      if (lane < 8) SM<float4>(OFF_XS + 1536 + (a * 8 + lane) * 16) = make_float4(st[0], st[1], st[2], 0.f);
      bar_sync(NB_AUX, 128);
      const float4 f = SM<float4>(OFF_XS + 1536 + lane * 16);
      st[0] = f.x; st[1] = f.y; st[2] = f.z;
#pragma unroll
      for (int o = 8; o < 32; o <<= 1) {
#pragma unroll
        for (int i = 0; i < 3; i++) st[i] += __shfl_xor_sync(0xffffffffu, st[i], o);
      }
      const float mu = st[0] * (1.f / 1024.f);
      float mb = bf16r(mu), inv = fast_rcp(ref_sd(fmaxf(st[1] * (1.f / 1024.f) - mu * mu, 0.f)));
      const uint32_t kk = make_key(bf16r((st[2] - mb * SM<float>(INFO_WSUM)) * inv), SM<uint16_t>(INFO_CAND + (lane & 7) * 2));
      const uint32_t key = __reduce_max_sync(0xffffffffu, kk);
      const int win = __ffs(__ballot_sync(0xffffffffu, kk == key)) - 1;
      mb = __shfl_sync(0xffffffffu, mb, win); inv = __shfl_sync(0xffffffffu, inv, win);
      if (win == 1) r0 = r1;
      n = 0;
#pragma unroll 1
      while (((win > 1 && n == 0) || __any_sync(0xffffffffu, r0.y != tag || r0.w != tag)) && ++n < SPIN_LIMIT) r0 = pkt_ld128(&p.sc->ch[m * 256 + 2 * j] + win * 512);
      bar_sync(NB_AUX, 128);
      auto ln = [&](float h) { return bf16r(bf16r(h - mb) * inv); };
      const int d = (j >> 2) * 16 + (j & 3) * 2;
      SM<float2>(OFF_XS + d * 4) = make_float2(ln(bf_lo(r0.x)), ln(bf_lo(r0.z)));
      SM<float2>(OFF_XS + (d + 8) * 4) = make_float2(ln(bf_hi(r0.x)), ln(bf_hi(r0.z)));
      if (j == 0) { SM<uint2>(INFO_KEY) = make_uint2(key, win); SM<float2>(INFO_LN) = make_float2(mb, inv); }
    }
    bar_sync(NB_AUX, 128);
    if (j == 0) {
      mbar_arrive(BAR(B_INFO)); TIM(103);
      if (cid == 0) st_relaxed32(&p.sc->epoch, tag);
    }
    const uint32_t t2 = clk32();
    fresh_ids();
    if (!ffn) {
      if (a == 1) all_published(1);
      wait_clk(t2, YPART_DELAY);
    } else {
      const int r = lane >> 3;
      float acc[8] = {0.f, 0.f, 0.f, 0.f, 0.f, 0.f, 0.f, 0.f};
#pragma unroll 1
      for (int v = 0; v < 8; v++) {
        const uint4 x0 = lds128(sb + OFF_XS + ((a * 8 + v) * 16 + (r & 1) * 8) * 4), x1 = lds128(sb + OFF_XS + ((a * 8 + v) * 16 + (r & 1) * 8 + 4) * 4);
        const float xv[8] = {__uint_as_float(x0.x), __uint_as_float(x0.y), __uint_as_float(x0.z), __uint_as_float(x0.w), __uint_as_float(x1.x), __uint_as_float(x1.y), __uint_as_float(x1.z), __uint_as_float(x1.w)};
        mbar_wait(bar0 + (v & 1) * 8, (v >> 1) & 1);
        gemv8x8<128>(acc, buf + (v & 1) * 4096 + r * 1024 + (lane & 7) * 16, xv);
        fence_regs(acc);
        __syncwarp();
        wait_clk(t2, v * UNIT_PACE);
        load_unit(v + 2);
        if (v == 0 && a == 1) all_published(1);
        if (j == 0) TIM(104 + v);
      }
      pkt_clear128(&p.sc->ypart[(a * NSRC + src) * 64 + lane * 2]); pkt_clear128(&p.sc->ypart[(a * NSRC + src) * 64 + lane * 2] + 1);
      fold<8>(acc, 8, lane);
      bar_sync(NB_AUX, 128);
      SM<float4>(OFF_XS + (a * 128 + (r >> 1) * 64 + (lane & 7) * 8 + (r & 1) * 4) * 4) = make_float4(acc[0], acc[1], acc[2], acc[3]);
      bar_sync(NB_AUX, 128);
      auto psum = [&](int i) { return (SM<float>(OFF_XS + i * 4) + SM<float>(OFF_XS + (128 + i) * 4)) + (SM<float>(OFF_XS + (256 + i) * 4) + SM<float>(OFF_XS + (384 + i) * 4)); };
      if (a < 2) st_async_b32(mapa(sb + OFF_REM + j * 4, m ^ 1), mapa(BAR(B_GUX), m ^ 1), __float_as_uint(psum(a * 64 + (m ^ 1) * 32 + lane)));
      const float og = psum(m * 32 + lane), ou = psum(64 + m * 32 + lane);
      mbar_wait(BAR(B_GUX), 0);
      const float rg = SM<float>(OFF_REM + lane * 4), ru = SM<float>(OFF_REM + 128 + lane * 4);
      const float act = swiglu(m ? rg + og : og + rg, m ? ru + ou : ou + ru);
      if (j == 0) TIM(112);
      float y[8] = {0.f, 0.f, 0.f, 0.f, 0.f, 0.f, 0.f, 0.f};
#pragma unroll 1
      for (int v = 8; v < 12; v++) {
        float av[8];
#pragma unroll
        for (int i = 0; i < 8; i++) av[i] = __shfl_sync(0xffffffffu, act, (v - 8) * 8 + i);
        mbar_wait(bar0 + (v & 1) * 8, (v >> 1) & 1);
        gemv8x8<512>(y, buf + (v & 1) * 4096 + lane * 16, av);
        fence_regs(y);
        __syncwarp();
        if (v < 10) load_unit(v + 2);
        if (j == 0) TIM(105 + v);
      }
      fresh_ids();
      uint4* ypart = &p.sc->ypart[(a * NSRC + src) * 64 + lane * 2];
      pkt_st128(ypart, with_bit(y[0], c0), with_bit(y[1], c1), with_bit(y[2], c0), with_bit(y[3], c1));
      pkt_st128(ypart + 1, with_bit(y[4], c0), with_bit(y[5], c1), with_bit(y[6], c0), with_bit(y[7], c1));
      if (lane == 0) TIM(160 + a);
      __nanosleep(ROW_NS);
    }
    if (a == 3) {
      const uint32_t hh = poll64_warp(&p.sc->ch[SM<uint32_t>(INFO_KEY + 4) * 512 + (cid >> 1) * 8 + (lane & 7)], tag, 100);
      uint4 v[7]; uint32_t n = 0;
      bool more;
#pragma unroll 1
      do {
        if (elect_one()) { mbar_expect_tx(bar0, NSRC * 32); tma_load_2d(buf, &p.tmY, bar0, (cid & 31) * 16, (cid >> 5) * NSRC); }
        mbar_wait(bar0, n & 1);
        uint32_t bad = 0;
#pragma unroll
        for (int i = 0; i < 7; i++) { v[i] = lds128(buf + i * 512 + lane * 16); chk_code(bad, v[i], c0, c1); }
        more = __any_sync(0xffffffffu, bad & 1) && ++n < SPIN_LIMIT;
        if (more) __nanosleep(300);
      } while (more);
      if (lane == 0) TIM(164);
      float y[4] = {0.f, 0.f, 0.f, 0.f};
#pragma unroll
      for (int i = 0; i < 7; i++) { y[0] += no_bit(v[i].x); y[1] += no_bit(v[i].y); y[2] += no_bit(v[i].z); y[3] += no_bit(v[i].w); }
      fold<4>(y, 16, lane); fold<2>(y, 8, lane);
      y[0] += __shfl_xor_sync(0xffffffffu, y[0], 4);
      y[0] += __shfl_xor_sync(0xffffffffu, y[0], 2);
      const float ys = __shfl_sync(0xffffffffu, y[0], (lane & 3) * 8 + ((lane >> 2) & 1));
      const float h = m ? bf_hi(hh) : bf_lo(hh), hn = bf16r(bf16r(h - SM<float>(INFO_LN)) * SM<float>(INFO_LN + 4));
      const uint32_t key = SM<uint32_t>(INFO_KEY);
      if (lane < 8) st_bf16(p.out + key_row(key) * 1024 + cid * 8 + lane, routed_out(h, hn, ys, key_val(key)));
      if (lane == 0) TIM(118);
      __threadfence();
      __syncwarp();
      if (lane == 0) { pkt_st64(&p.sc->rdone[cid], 0, tag); TIM(117); }
    }
  } else {
    reg_inc<216>();
    cluster_wait();
    const uint32_t sb = __shfl_sync(0xffffffffu, smem_u32(smem_raw), 0);
    auto BAR = [&](int i) { return sb + OFF_BAR + 8 * i; };
    const int w = warp >> 2, wi = warp & 3, t = tid & 127;
    const int turn_me = NB_TURN0 + w, turn_other = NB_TURN1 - w;
    const uint64_t dA0 = make_desc(sb + w * 8192);
    uint64_t dA, dB;
    int tau, eps, m, grp, abrow, fc, src;
    bool ffn;
    const CUtensorMap* tmD; const CUtensorMap* tmW;
    auto new_desc = [&](int salt) {
      const uint32_t z = salt < 0 ? uniform_zero_here() : salt & blockIdx.y;
      dA = dA0 + z; dB = dA0 + (z + ((A_BYTES - w * 8192) >> 4));
      const int c = cid + z;
      tau = c >> 4; eps = (c >> 1) & 7; m = c & 1; grp = tau * 2 + m; abrow = m * 1024 + eps * 128;
      ffn = eps > 0; fc = (tau * 7 + eps - 1) * 64; src = (fc >> 5) + m;
      tmD = &p.tmD0 + m; tmW = &p.tmW0 + m;
    };
    constexpr int SL = ST_BYTES >> 4;
    float acc[128];
#pragma unroll
    for (int i = 0; i < 128; i++) acc[i] = 0.f;
    if (w == 1) bar_arrive(NB_TURN0, 256);
    auto full = [&](int k) { mbar_wait(BAR(B_FULL + (k & 3)), (k >> 2) & 1); CT(64 + k); };
    const uint64_t pol_ef = policy_evict_first();
    auto refill_g2 = [&](int k, int mode) {
      if (warp == 4) {
        if (elect_one()) {
          const int s = k & 3, s0 = k_col(tau, k - 12);
          TIM(k + 4);
          mbar_expect_tx(BAR(B_FULL + s), mode ? ST_BYTES : B_BYTES);
          if (k == 19) mbar_arrive(BAR(B_EMPTY));
          LOAD_W(sb + s * ST_BYTES + A_BYTES, tmW, BAR(B_FULL + s), s0, grp * 128);
          LOAD_W(sb + s * ST_BYTES + A_BYTES + 16384, tmW, BAR(B_FULL + s), s0, (grp ^ 1) * 128);
          if (mode == 2) tma_load_2d(sb + s * ST_BYTES, &p.tmAbL, BAR(B_FULL + s), s0, abrow);
        }
        __syncwarp();
      }
    };
    auto mma_ss = [&](int k) {
#pragma unroll
      for (int kk = 0; kk < 4; kk++) wgmma_n256(acc, dA + (k & 3) * SL + kk * 2, dB + (k & 3) * SL + kk * 2);
    };
    const CUtensorMap* rf_tm; uint32_t rf_dst; int rf_row, rf_c0 = 0, rf_c1 = 0; bool rf_on;
    auto refill = [&](int s) {
      if (rf_on) {
        if (elect_one()) tma_load_2d(rf_dst + s * ST_BYTES, rf_tm, BAR(B_FULL + s), (s < 2 ? rf_c0 : rf_c1) + (s & 1) * 64, rf_row);
        __syncwarp();
      }
      if (tid == 224) mbar_expect_tx(BAR(B_FULL + s), ST_BYTES);
    };
    const bf16* pf; int pf_step; bool pf_on;
    auto pf_ffn = [&](int v) {
      pf_on = ffn && v >= 0 && v < 12;
      pf = v < 8 ? ((lane & 16) ? p.wup : p.wgate) + (m * 512 + (wi * 8 + v) * 16 + (lane & 15)) * 3584 + fc : p.wdown + (src * 32 + (v - 8) * 8) * 1024 + t * 64;
      pf_step = v < 8 ? 16 * 3584 : 8192;
    };
    auto prefetch = [&](int s) { if (pf_on && (wi >> 1) == (s & 1)) prefetch_l2(pf + (s >> 1) * pf_step); };
    auto kstep = [&](int k) {
      full(k);
      bar_sync(turn_me, 256);
      wgmma_fence();
      mma_ss(k);
      wgmma_commit();
      bar_arrive(turn_other, 256);
    };

    new_desc(64);
    rf_on = (warp >> 1) == 2;
    rf_tm = wi ? tmD : &p.tmX; rf_dst = wi ? sb : sb + A_BYTES; rf_row = wi ? eps * 128 : tau * 256;
#pragma unroll 1
    for (int k4 = 0; k4 < 12; k4 += 4) {
#pragma unroll
      for (int s = 0; s < 4; s++) {
        kstep(k4 | s);
        if (s == 0) {
          if (w == 0) pf_ffn((k4 >> 1) - 2);
          else {
            pf_on = W_PF && k4 == 8;
            pf = (m ? p.Wim : p.Wre) + (tau * 256 + eps * 32 + wi * 4 + (lane >> 3)) * 2048 + k_col(tau, lane & 7);
            pf_step = 16 * 2048;
          }
          rf_c0 = k4 * 64 + 256; rf_c1 = rf_c0 + 128;
        }
        prefetch(s);
        if (s == 3) new_desc(k4);
        if (s == 0 || s == 3) pf += zero_here();
        wgmma_wait<0>();
        refill(s);
      }
    }
    uint32_t R[64];
    auto load_rs = [&](auto gi) {
      const uint32_t rsa = sb + OFF_RS + (lane & 3) * 272;
#pragma unroll
      for (int i = 4 * decltype(gi)::value; i < 4 * decltype(gi)::value + 4; i++) { const uint4 v = lds128(rsa + i * 16); R[4 * i] = v.x; R[4 * i + 1] = v.y; R[4 * i + 2] = v.z; R[4 * i + 3] = v.w; }
    };
    kstep(12);
    mbar_wait(BAR(B_STAT), 0);
    CT(1);
    load_rs(std::integral_constant<int, 0>());
    load_rs(std::integral_constant<int, 1>());
    wgmma_wait<0>(); refill_g2(12, 0);
    load_rs(std::integral_constant<int, 3>());
    auto mma_h = [&](float (&d)[64], int s, int half) {
#pragma unroll
      for (int kk = 0; kk < 4; kk++) wgmma_n128(d, dA + s * SL + kk * 2, dB + s * SL + half * 1024 + kk * 2);
    };
    const int rho = 16 * wi + (lane & 15);
    const uint32_t arow = sb + w * 8192 + rho * 128;
    auto convert = [&](auto cc, float (&d)[64]) {
      const float z = __uint_as_float(zero_here());
#pragma unroll
      for (int jj = 8 * decltype(cc)::value; jj < 8 * decltype(cc)::value + 8; jj++) {
        const float r0 = __uint_as_float(R[2 * jj]), r1 = __uint_as_float(R[2 * jj + 1]);
        const float* ac = &d[4 * (jj & 15)];
        R[2 * jj] = pack_bf16(fmaf(ac[0], r0, z), fmaf(ac[1], r1, z));
        R[2 * jj + 1] = pack_bf16(fmaf(ac[2], r0, z), fmaf(ac[3], r1, z));
      }
    };
    auto put = [&](auto cc) {
      constexpr int c = decltype(cc)::value;
#pragma unroll
      for (int jj = 8 * c; jj < 8 * c + 8; jj += 2)
        stsm_x4(arow + c * ST_BYTES + ((((jj & 7) + (lane >> 4)) ^ (rho & 7)) << 4), R[2 * jj], R[2 * jj + 1], R[2 * jj + 2], R[2 * jj + 3]);
      __syncwarp();
      if (lane == 0) mbar_arrive(BAR(B_EP + w * 4 + c));
    };
    {
      float lo[64], hi[64];
      fence_regs(acc);
#pragma unroll
      for (int i = 0; i < 64; i++) asm volatile("mov.b32 %0, %1;" : "=f"(lo[i]) : "f"(acc[i]));
#pragma unroll
      for (int i = 0; i < 64; i++) asm volatile("mov.b32 %0, %1;" : "=f"(hi[i]) : "f"(acc[64 + i]));
      const uint64_t dEA = make_desc_noswz(sb + OFF_EXA + w * 1024), dEB = make_desc_noswz(sb + OFF_EXB);
      full(13); full(14);
      bar_sync(turn_me, 256);
      wgmma_fence();
      mma_h(lo, 1, 0); mma_h(lo, 2, 0);
      wgmma_commit();
      bar_arrive(turn_other, 256);
      new_desc(ND1);
      full(15);
      bar_sync(turn_me, 256);
      wgmma_fence();
      mma_h(lo, 3, 0);
      wgmma_n128(lo, dEA, dEB);
      wgmma_commit();
      mma_h(hi, 1, 1);
      wgmma_commit();
      bar_arrive(turn_other, 256);
      new_desc(ND2);
      wgmma_wait<1>();
      fence_regs(lo);
      CT(15);
      convert(std::integral_constant<int, 0>(), lo); put(std::integral_constant<int, 0>());
      convert(std::integral_constant<int, 1>(), lo);
      wgmma_wait<0>(); refill_g2(13, 0);
      put(std::integral_constant<int, 1>());
      bar_sync(turn_me, 256);
      wgmma_fence();
      mma_h(hi, 2, 1);
      wgmma_commit();
      mma_h(hi, 3, 1);
      wgmma_n128(hi, dEA, dEB + 128);
      wgmma_commit();
      bar_arrive(turn_other, 256);
      load_rs(std::integral_constant<int, 2>());
      wgmma_wait<1>(); refill_g2(14, 0);
      wgmma_wait<0>(); refill_g2(15, 0);
      fence_regs(hi);
      CT(2);
      convert(std::integral_constant<int, 3>(), hi); put(std::integral_constant<int, 3>());
      convert(std::integral_constant<int, 2>(), hi);
    }
    CT(3);
    float cc[4];
    auto cand_mma = [&]() {
      const uint64_t dC = make_desc(sb + OFF_WC);
      wgmma_n8_rs<0>(cc, R, dC);
#pragma unroll
      for (int i = 1; i < 12; i++) wgmma_n8_rs<1>(cc, R + 4 * i, dC + (i >> 2) * 64 + (i & 3) * 2);
#pragma unroll
      for (int kk = 0; kk < 4; kk++) wgmma_n8(cc, dA + 3 * SL + kk * 2, dC + 192 + kk * 2);
      wgmma_commit();
    };
    auto cand_pub = [&]() {
      fence_regs(cc);
      const uint32_t cd = code_of(SM<uint32_t>(INFO_TAG));
      if (t == 0) mbar_arrive(BAR(B_CD));
      pkt_st128(&p.sc->cpart[((lane & 3) * 16 + grp) * 512 + eps * 64 + warp * 8 + (lane >> 2)], with_bit(cc[0], cd), with_bit(cc[1], cd >> 1), with_bit(cc[2], cd), with_bit(cc[3], cd >> 1));
      CT(5);
    };
    new_desc(ND3);
    if (CAND_EARLY) { fence_async_smem(); mbar_wait(BAR(B_WC), 0); CT(4); }
    full(16);
    if (!SPLIT17) full(17);
    bar_sync(turn_me, 256);
    wgmma_fence();
    if (CAND_EARLY) cand_mma();
    wgmma_n256_rs_init(acc, R, dB);
#pragma unroll
    for (int kk = 1; kk < 4; kk++) wgmma_n256_rs<1>(acc, R + 4 * kk, dB + kk * 2);
    wgmma_commit();
    if (SPLIT17) { full(17); wgmma_fence(); }
#pragma unroll
    for (int kk = 0; kk < 4; kk++) wgmma_n256_rs<1>(acc, R + 16 + 4 * kk, dB + SL + kk * 2);
    wgmma_commit();
    bar_arrive(turn_other, 256);
    if (CAND_EARLY) { wgmma_wait<2>(); put(std::integral_constant<int, 2>()); cand_pub(); }
    else put(std::integral_constant<int, 2>());
    wgmma_wait<1>(); refill_g2(16, 1);
    wgmma_wait<0>(); refill_g2(17, 1);
    if (!CAND_EARLY) { fence_async_smem(); mbar_wait(BAR(B_WC), 0); CT(4); }
    full(18);
    bar_sync(turn_me, 256);
    wgmma_fence();
    if (!CAND_EARLY) cand_mma();
#pragma unroll
    for (int kk = 0; kk < 4; kk++) wgmma_n256_rs<1>(acc, R + 32 + 4 * kk, dB + 2 * SL + kk * 2);
    wgmma_commit();
    bar_arrive(turn_other, 256);
    if (!CAND_EARLY) { wgmma_wait<1>(); cand_pub(); }
    wgmma_wait<0>(); refill_g2(18, 1);
    kstep(19);
    new_desc(68);
    wgmma_wait<0>(); refill_g2(19, 1);
    const int g = lane >> 2, q = lane & 3;
    uint4 ha[4], hb[4];

    rf_on = w == 1 && wi < 3;
    rf_tm = wi == 2 ? &p.tmAbL : tmW; rf_dst = wi == 2 ? sb : sb + A_BYTES + wi * 16384; rf_row = wi == 2 ? abrow : (grp ^ wi) * 128;
#pragma unroll 1
    for (int k4 = 20; k4 < 44; k4 += 4) {
#pragma unroll
      for (int s = 0; s < 4; s++) {
        kstep(k4 | s);
        if (s == 0) {
          if (w == 0) { pf_ffn((k4 >> 1) - PF2_K / 2 + 4); pf_on = pf_on && k4 >= PF2_K; }
          else {
            pf_on = k4 == XPF_K;
            pf = p.x + (grp * 128 + (t >> 1)) * 1024 + eps * 128 + (t & 1) * 64;
            pf_step = 64 * 1024;
          }
          rf_c0 = k_col(tau, k4 - 12); rf_c1 = k_col(tau, k4 - 10);
        }
        if (s == 0 && k4 == 20 && warp == 6) mbar_wait(BAR(B_ALL), 0);
        if (s == 2 && k4 == 28 && warp == 6) mbar_wait(BAR(B_ALL + 1), 0);
        prefetch(s);
        if (s == 3) new_desc(k4);
        if (s == 0 || s == 3) pf += zero_here();
        wgmma_wait<0>();
        refill(s);
      }
    }
    const int row0 = grp * 128 + warp * 16 + g;
    kstep(44);
    uint4* hst = &p.sc->hstat[grp * 1024 + warp * 16 + g];
    if (q == (g >> 1)) { pkt_clear128(hst + eps * 128); pkt_clear128(hst + eps * 128 + 8); }
    mbar_wait(BAR(B_INFO), 0);
    uint4 wv[4];
#pragma unroll
    for (int i = 0; i < 4; i++) wv[i] = lds128(sb + ((g & 1) ? OFF_WR + (i * 4 + q) * 16 : INFO_ONES));
    const uint4 info = lds128(sb + OFF_INFO);
#pragma unroll
    for (int i = 0; i < 4; i++) { ha[i] = ldg128(p.x + (row0 * 1024 + eps * 128 + q * 8) + i * 32); hb[i] = ldg128(p.x + (row0 * 1024 + eps * 128 + q * 8) + 8192 + i * 32); }
    wgmma_wait<0>();
    if (tid == 128) mbar_arrive_remote(mapa(BAR(B_PEER), m ^ 1));
    uint32_t hp[32];
    bf16* op; uint4* hpub;
    uint32_t cd, ast, ald, zr;
    auto swz = [](int row) { return ((row & 1) << 2) | ((row >> 1) & 3); };
    {
      float as[64], ak[64];
      fence_regs(acc);
#pragma unroll
      for (int i = 0; i < 64; i++) asm volatile("mov.b32 %0, %1;" : "=f"(as[i]) : "f"(acc[64 + i]));
#pragma unroll
      for (int i = 0; i < 64; i++) asm volatile("mov.b32 %0, %1;" : "=f"(ak[i]) : "f"(acc[i]));
      full(45); full(46);
      bar_sync(turn_me, 256);
      wgmma_fence();
      mma_h(as, 1, 1); mma_h(as, 2, 1);
      wgmma_commit();
      bar_arrive(turn_other, 256);
      full(47);
      bar_sync(turn_me, 256);
      wgmma_fence();
      mma_h(as, 3, 1);
      wgmma_commit();
      mma_h(ak, 1, 0);
      wgmma_commit();
      bar_arrive(turn_other, 256);
      const uint32_t rx = mapa(sb + OFF_RECV + w * 16384 + t * 16, m ^ 1), rb = mapa(BAR(B_XCH + w), m ^ 1);
      mbar_wait(BAR(B_PEER), 0);
      wgmma_wait<1>();
      fence_regs(as);
      CT(6);
#pragma unroll
      for (int i = 0; i < 8; i++) {
        const float* ac = &as[8 * i];
        st_async_v4(rx + i * 2048, rb, pack_bf16(ac[0], ac[1]), pack_bf16(ac[2], ac[3]), pack_bf16(ac[4], ac[5]), pack_bf16(ac[6], ac[7]));
      }
      CT(7);
      bar_sync(turn_me, 256);
      wgmma_fence();
      mma_h(ak, 2, 0); mma_h(ak, 3, 0);
      wgmma_commit();
      if (w == 0) bar_arrive(turn_other, 256);
      op = p.out + row0 * 1024 + eps * 128 + q * 8;
      hpub = hst + eps * 128; hst += q * 256;
      cd = code_of(info.y);
      ast = sb + w * ST_BYTES + (8 * (lane >> 4) + (lane & 7)) * 128 + (((2 * wi + ((lane >> 3) & 1)) ^ swz(lane & 7)) << 4);
      ald = sb + (warp * 16 + g) * 128 + ((q ^ swz(g)) << 4);
      asm volatile("" : "+l"(op), "+l"(hpub), "+l"(hst), "+r"(cd), "+r"(ast), "+r"(ald));
      zr = zero_here();
#pragma unroll
      for (int i = 0; i < 4; i++) { ha[i].x += zr; hb[i].x += zr; asm volatile("" : "+r"(ha[i].x), "+r"(hb[i].x)); }
      ast += (uint32_t)(clock64() >> 32) & zr;
      mbar_wait(BAR(B_XCH + w), 0);
      CT(9);
#pragma unroll
      for (int i = 0; i < 8; i++) { const uint4 v = lds128(sb + OFF_RECV + w * 16384 + t * 16 + i * 2048); hp[4 * i] = v.x; hp[4 * i + 1] = v.y; hp[4 * i + 2] = v.z; hp[4 * i + 3] = v.w; }
      wgmma_wait<0>();
      fence_regs(ak);
      CT(10);
#pragma unroll
      for (int i = 0; i < 32; i++) hp[i] = badd2(pack_bf16(ak[2 * i], ak[2 * i + 1]), hp[i]);
    }
#pragma unroll
    for (int jj = 0; jj < 16; jj += 2) stsm_x4_t(ast + jj * 1024, hp[2 * jj], hp[2 * jj + 1], hp[2 * jj + 2], hp[2 * jj + 3]);
    tag = info.y;
    bar_sync(NB_BOTH, 256);
    CT(11);
    uint4 v[4];
    auto fetch = [&]() { v[0] = pkt_ld128(hst); v[1] = pkt_ld128(hst + 128); v[2] = pkt_ld128(hst + 8); v[3] = pkt_ld128(hst + 136); };
    float st[6];
    {
      uint4 ya[4], yb[4];
#pragma unroll
      for (int i = 0; i < 4; i++) {
        const uint32_t ad = (ald ^ ((i & 1) << 6)) + (i >> 1) * ST_BYTES;
        ya[i] = lds128(ad); yb[i] = lds128(ad + 1024);
      }
      fetch();
      const float z = __uint_as_float((uint32_t)(clock64() >> 32) & zr);
      float sw[2][4], qa[2][4], qb[2][4];
#pragma unroll
      for (int i = 0; i < 8; i++) { sw[i >> 2][i & 3] = i ? 0.f : z; qa[i >> 2][i & 3] = 0.f; qb[i >> 2][i & 3] = 0.f; }
#pragma unroll
      for (int i = 0; i < 4; i++) {
        ha[i] = make_uint4(badd2(ha[i].x, ya[i].x), badd2(ha[i].y, ya[i].y), badd2(ha[i].z, ya[i].z), badd2(ha[i].w, ya[i].w));
        hb[i] = make_uint4(badd2(hb[i].x, yb[i].x), badd2(hb[i].y, yb[i].y), badd2(hb[i].z, yb[i].z), badd2(hb[i].w, yb[i].w));
        mma16816(sw[0], ha[i].x, hb[i].x, ha[i].y, hb[i].y, wv[i].x, wv[i].y);
        mma16816(qa[0], ha[i].x, hb[i].x, ha[i].y, hb[i].y, ha[i].x, ha[i].y);
        mma16816(qb[0], ha[i].x, hb[i].x, ha[i].y, hb[i].y, hb[i].x, hb[i].y);
        mma16816(sw[1], ha[i].z, hb[i].z, ha[i].w, hb[i].w, wv[i].z, wv[i].w);
        mma16816(qa[1], ha[i].z, hb[i].z, ha[i].w, hb[i].w, ha[i].z, ha[i].w);
        mma16816(qb[1], ha[i].z, hb[i].z, ha[i].w, hb[i].w, hb[i].z, hb[i].w);
      }
      const uint32_t s0 = with_bit(sw[0][0] + sw[1][0], cd), s1 = with_bit((g & 1) ? qa[0][1] + qa[1][1] : qa[0][0] + qa[1][0], cd >> 1), s2 = __float_as_uint(sw[0][1] + sw[1][1]);
      const uint32_t s3 = with_bit(sw[0][2] + sw[1][2], cd), s4 = with_bit((g & 1) ? qb[0][3] + qb[1][3] : qb[0][2] + qb[1][2], cd >> 1), s5 = __float_as_uint(sw[0][3] + sw[1][3]);
      if (q == (g >> 1)) { pkt_st128(hpub, s0, s1, s2, tag); pkt_st128(hpub + 8, s3, s4, s5, tag); }
      CT(12);
      const uint32_t o1 = __shfl_sync(0xffffffffu, s1, (lane & 28) | (g >> 1)), o4 = __shfl_sync(0xffffffffu, s4, (lane & 28) | (g >> 1));
      uint32_t n = 0;
      bool more;
#pragma unroll 1
      do {
        if (2 * q == eps) { v[0] = make_uint4(s0, o1, s2, tag); v[2] = make_uint4(s3, o4, s5, tag); }
        if (2 * q + 1 == eps) { v[1] = make_uint4(s0, o1, s2, tag); v[3] = make_uint4(s3, o4, s5, tag); }
        uint32_t bad = 0;
#pragma unroll
        for (int i = 0; i < 4; i++) { chk(bad, v[i].x, cd); chk(bad, v[i].y, cd >> 1); }
        bad &= 1;
#pragma unroll
        for (int i = 0; i < 4; i++) chk(bad, v[i].w, tag);
        more = !(!__any_sync(0xffffffffu, bad)) && ++n < SPIN_LIMIT;
        if (more) { if (bad) fetch(); }
      } while (more);
      st[0] = no_bit(v[0].x) + no_bit(v[1].x); st[1] = no_bit(v[0].y) + no_bit(v[1].y); st[2] = __uint_as_float(v[0].z) + __uint_as_float(v[1].z);
      st[3] = no_bit(v[2].x) + no_bit(v[3].x); st[4] = no_bit(v[2].y) + no_bit(v[3].y); st[5] = __uint_as_float(v[2].z) + __uint_as_float(v[3].z);
    }
    CT(13);
#pragma unroll
    for (int o = 1; o < 4; o <<= 1) {
#pragma unroll
      for (int i = 0; i < 6; i++) st[i] += __shfl_xor_sync(0xffffffffu, st[i], o);
    }
    float mb[2], inv[2];
#pragma unroll
    for (int i = 0; i < 2; i++) {
      const float mu = st[3 * i] * (1.f / 1024.f);
      mb[i] = bf16r(mu);
      inv[i] = fast_rcp(ref_sd(fmaxf(st[3 * i + 1] * (1.f / 1024.f) - mu * mu, 0.f)));
    }
    {
      const int srow = key_row(info.z);
      auto put_out = [&](bf16* dst, const uint4& h, float sc, float of, bool on) {
        auto cvt = [&](uint32_t x) { return pack_bf16(fmaf(bf_lo(x), sc, of), fmaf(bf_hi(x), sc, of)); };
        asm volatile("{\n.reg .pred p;\nsetp.ne.b32 p, %5, 0;\n@p st.global.v4.b32 [%0], {%1, %2, %3, %4};\n}\n"
                     :: "l"(dst), "r"(cvt(h.x)), "r"(cvt(h.y)), "r"(cvt(h.z)), "r"(cvt(h.w)), "r"((int)on) : "memory");
      };
#pragma unroll
      for (int i = 0; i < 4; i++) {
        put_out(op + i * 32, ha[i], 1.f + inv[0], -mb[0] * inv[0], row0 != srow);
        put_out(op + 8192 + i * 32, hb[i], 1.f + inv[1], -mb[1] * inv[1], row0 + 8 != srow);
      }
    }
    CT(14);
    const uint4 cand = lds128(sb + INFO_CAND);
    uint32_t wkey = zero_here();
#pragma unroll
    for (int i = 0; i < 2; i++) {
      const uint32_t row = row0 + 8 * i, rr = row | (row << 16);
      const bool is_cand = __vcmpeq2(cand.x, rr) | __vcmpeq2(cand.y, rr) | __vcmpeq2(cand.z, rr) | __vcmpeq2(cand.w, rr);
      if (!is_cand) wkey = max(wkey, make_key(bf16r((st[3 * i + 2] - mb[i] * __uint_as_float(info.x)) * inv[i]), row));
    }
    wkey = __reduce_max_sync(0xffffffffu, wkey);
    if (eps == 0 && lane == 0) pkt_st64(&p.sc->key[grp * 8 + warp], wkey, tag);
    const bool beaten = (wkey >> 16) > (info.z >> 16);
    if (__builtin_expect(beaten, 0)) {
      const int br = key_row(wkey);
      if (br == row0 || br == row0 + 8) {
#pragma unroll
        for (int i = 0; i < 4; i++) {
          const uint4 h = br == row0 ? ha[i] : hb[i];
          uint2* dst = &p.sc->hrow[(grp * 8 + warp) * 512 + eps * 64 + i * 16 + q * 4];
          pkt_st128(dst, h.x, tag, h.y, tag); pkt_st128(dst + 2, h.z, tag, h.w, tag);
        }
      }
      __syncwarp();
    }
    uint32_t any;
    asm volatile("{\n.reg .pred p, q;\nsetp.ne.b32 p, %1, 0;\nbarrier.cta.red.or.aligned.pred q, %2, 256, p;\nselp.u32 %0, 1, 0, q;\n}\n" : "=r"(any) : "r"((int)beaten), "n"((int)NB_BOTH) : "memory");
    if (__builtin_expect(any, 0)) slow_path(p, grp, eps, tag, info.z, info.w, SM<float>(INFO_LN), SM<float>(INFO_LN + 4));
  }
}

__global__ void __launch_bounds__(NTHR, 1) occupancy_probe_kernel() {}

typedef CUresult (*EncodeFn)(CUtensorMap*, CUtensorMapDataType, cuuint32_t, void*, const cuuint64_t*, const cuuint64_t*, const cuuint32_t*, const cuuint32_t*,
                             CUtensorMapInterleave, CUtensorMapSwizzle, CUtensorMapL2promotion, CUtensorMapFloatOOBfill);

static void make_tm(EncodeFn enc, CUtensorMap* tm, const void* ptr, uint64_t rows, uint64_t cols, uint32_t brows, uint32_t bcols, bool swz, bool wide) {
  cuuint64_t dims[2] = {cols, rows};
  cuuint64_t strides[1] = {cols * 2};
  cuuint32_t box[2] = {bcols, brows};
  cuuint32_t es[2] = {1, 1};
  enc(tm, CU_TENSOR_MAP_DATA_TYPE_BFLOAT16, 2, const_cast<void*>(ptr), dims, strides, box, es, CU_TENSOR_MAP_INTERLEAVE_NONE,
      swz ? CU_TENSOR_MAP_SWIZZLE_128B : CU_TENSOR_MAP_SWIZZLE_NONE, wide ? CU_TENSOR_MAP_L2_PROMOTION_L2_256B : CU_TENSOR_MAP_L2_PROMOTION_L2_128B, CU_TENSOR_MAP_FLOAT_OOB_FILL_NONE);
}

extern "C" void kernel_launch(void* const* d_in, const int* in_sizes, int n_in, void* d_out, int out_size) {
  (void)in_sizes; (void)n_in; (void)out_size;
  static EncodeFn enc = nullptr;
  static void* abT = nullptr;
  static void* sc = nullptr;
  static int map = 0;
  if (!enc) {
    void* fn = nullptr; cudaDriverEntryPointQueryResult st;
    cudaGetDriverEntryPoint("cuTensorMapEncodeTiled", &fn, cudaEnableDefault, &st);
    enc = (EncodeFn)fn;
    cudaGetSymbolAddress(&abT, g_abT);
    cudaGetSymbolAddress(&sc, g_sc);
    cudaFuncSetAttribute(fnet_moe_kernel<0>, cudaFuncAttributeMaxDynamicSharedMemorySize, SMEM_TOTAL);
    cudaFuncSetAttribute(fnet_moe_kernel<1>, cudaFuncAttributeMaxDynamicSharedMemorySize, SMEM_TOTAL);
    cudaFuncSetAttribute(occupancy_probe_kernel, cudaFuncAttributeMaxDynamicSharedMemorySize, SMEM_TOTAL);
    cudaFuncSetAttribute(occupancy_probe_kernel, cudaFuncAttributeNonPortableClusterSizeAllowed, 1);
    cudaLaunchConfig_t cfg = {};
    cfg.gridDim = dim3(128); cfg.blockDim = dim3(NTHR); cfg.dynamicSmemBytes = SMEM_TOTAL;
    cudaLaunchAttribute at[1];
    at[0].id = cudaLaunchAttributeClusterDimension; at[0].val.clusterDim.x = 16; at[0].val.clusterDim.y = 1; at[0].val.clusterDim.z = 1;
    cfg.attrs = at; cfg.numAttrs = 1;
    int ncl = 0;
    if (cudaOccupancyMaxActiveClusters(&ncl, occupancy_probe_kernel, &cfg) == cudaSuccess && ncl >= 8) map = 1;
    (void)cudaGetLastError();
  }
  Params p;
  const bf16* x = (const bf16*)d_in[0];
  make_tm(enc, &p.tmD0, d_in[3], 1024, 1024, 128, 64, true, true);
  make_tm(enc, &p.tmD1, d_in[4], 1024, 1024, 128, 64, true, true);
  make_tm(enc, &p.tmX, x, 2048, 1024, 256, 64, true, true);
  make_tm(enc, &p.tmAbS, abT, 2048, 2048, 64, 64, true, false);
  make_tm(enc, &p.tmAbL, abT, 2048, 2048, 128, 64, true, false);
  make_tm(enc, &p.tmW0, d_in[1], 2048, 2048, 128, 64, true, true);
  make_tm(enc, &p.tmW1, d_in[2], 2048, 2048, 128, 64, true, true);
  make_tm(enc, &p.tmG, d_in[7], 1024, 3584, 16, 64, false, false);
  make_tm(enc, &p.tmU, d_in[8], 1024, 3584, 16, 64, false, false);
  make_tm(enc, &p.tmDn, d_in[9], 3584, 1024, 8, 256, false, false);
  make_tm(enc, &p.tmY, (char*)sc + offsetof(Scratch, ypart), 4 * NSRC, 512, NSRC, 16, false, false);
  p.x = x; p.Dre = (const bf16*)d_in[3]; p.Dim = (const bf16*)d_in[4];
  p.wr = (const bf16*)d_in[6]; p.wdown = (const bf16*)d_in[9]; p.wgate = (const bf16*)d_in[7]; p.wup = (const bf16*)d_in[8]; p.Wre = (const bf16*)d_in[1]; p.Wim = (const bf16*)d_in[2];
  p.out = (bf16*)d_out; p.sc = (Scratch*)sc;
  if (map == 1) fnet_moe_kernel<1><<<NGRID, NTHR, SMEM_TOTAL>>>(p);
  else fnet_moe_kernel<0><<<NGRID, NTHR, SMEM_TOTAL>>>(p);
}
```

```cpp
#include <cuda.h>
#include <cuda_runtime.h>
#include <cuda_bf16.h>
#include <stdint.h>
#include <stddef.h>
#include <type_traits>

typedef __nv_bfloat16 bf16;

constexpr int NGRID = 132, NTHR = 384;
__device__ __forceinline__ int k_col(int tau, int j) { return (tau * 256 + (j < 4 ? j * 64 : (j - 3) * 256)) & 2047; }
__device__ __forceinline__ int k_next(int c, int j) { return (c + (j < 11 ? 256 : j == 11 ? 576 : (c & 192) == 192 ? 128 : 64)) & 2047; }
constexpr int A_BYTES = 128 * 64 * 2;
constexpr int B_BYTES = 256 * 64 * 2;
constexpr int ST_BYTES = A_BYTES + B_BYTES;
constexpr int OFF_AUX = 4 * ST_BYTES;
constexpr int OFF_BAR = OFF_AUX + 32768;
constexpr int OFF_XS = OFF_BAR + 256;
constexpr int OFF_WR = OFF_XS + 2048;
constexpr int OFF_REM = OFF_WR + 256;
constexpr int OFF_INFO = OFF_REM + 256;
constexpr int SMEM_TOTAL = OFF_INFO + 256;
constexpr int INFO_WSUM = OFF_INFO, INFO_TAG = OFF_INFO + 4, INFO_KEY = OFF_INFO + 8, INFO_CAND = OFF_INFO + 16, INFO_LN = OFF_INFO + 32, INFO_ONES = OFF_INFO + 48, INFO_DS = OFF_INFO + 64, INFO_DS2 = OFF_INFO + 192;
constexpr int OFF_RS = OFF_XS;
constexpr int OFF_WC = OFF_AUX;
constexpr int OFF_EXA = OFF_AUX + 4096;
constexpr int OFF_EXB = OFF_AUX + 6144;
constexpr int OFF_RECV = A_BYTES;
__host__ __device__ constexpr int off_y(int w) { return w * ST_BYTES; }
constexpr int NSRC = 112;
enum { B_FULL = 0, B_EMPTY = 4, B_E23 = 5, B_E24 = 27, B_ALL = 6, B_EP = 8, B_AW = 16, B_STAT = 24, B_WC = 25, B_CD = 26, B_INFO = 28, B_PEER = 29, B_XCH = 30, B_GUX = (OFF_INFO + 128 - OFF_BAR) / 8, B_SD = B_GUX + 1, B_CH = B_GUX + 5 };
enum { NB_TURN0 = 1, NB_TURN1 = 2, NB_BOTH = 3, NB_AUX = 4, NB_H = 5, NB_SEL = 6 };

struct Scratch;
struct Params {
  Scratch* sc; const bf16* wr; const bf16* x; const bf16* Dre; const bf16* Dim; const bf16* Wre; const bf16* Wim;
  const bf16* wgate; const bf16* wup; const bf16* wdown; bf16* out;
  CUtensorMap tmX, tmD0, tmD1, tmW0, tmW1, tmAbS, tmAbL, tmG, tmU, tmDn, tmY;
};

__device__ __align__(1024) bf16 g_abT[2048 * 2048];
struct Scratch {
  alignas(128) uint4 xz[2048];
  alignas(128) uint2 dsum[2048];
  alignas(128) uint32_t abflag[128 * 2 * 32];
  alignas(128) uint32_t abdone[128 * 2 * 32];
  alignas(128) uint2 u[4 * 512];
  alignas(128) uint2 cl[128 * 16];
  alignas(128) uint4 cpart[4 * 16 * 512];
  alignas(128) uint2 ch[8 * 512];
  alignas(128) uint4 cs[128 * 8];
  alignas(128) uint2 rdone[128];
  alignas(128) uint4 ypart[4 * NSRC * 64];
  alignas(128) uint4 hstat[16 * 8 * 128];
  alignas(128) uint2 key[128];
  alignas(128) uint2 hrow[128 * 512];
  alignas(128) uint2 fpart[8 * 1024];
  alignas(128) uint32_t epoch;
};
__device__ Scratch g_sc;

#define SPIN_LIMIT (1u << 17)
#define PF2_K 24
#define UNIT_PACE 1500
#define XPF_K 40
#define XS_DELAY 300
#define U_CLK 3700
#define XROW_PF 0
#define DROW_PF 0
#define TM_PF 0
#define SPLIT17 1
#define LO_NS 250
#define CAND_EARLY 0
#define CHAIN1 0
#define ROW_NS 400
#define W_PF 2
#define START_PF 0
#define ND0 65
#define ND1 66
#define ND2 67
#define ND3 -1
#define ND4 69
#define HI_DELAY 0
#define HI_PACE 850
#define ALL_NS 400
#define PUT3_LATE 0
#define PUT1_LATE 0
#define DELEG 1
#define LU0_LATE 0
#define Z_CLK 9000
#define CP_DELAY 1500
#define CS_DELAY 800
#define YPART_DELAY 16500
__device__ __forceinline__ uint32_t smem_u32(const void* p) { return (uint32_t)__cvta_generic_to_shared(p); }
__device__ __forceinline__ uint32_t clk32() { uint32_t c; asm volatile("mov.u32 %0, %%clock;" : "=r"(c)); return c; }
__device__ __forceinline__ uint32_t zero_here() { uint64_t c; asm volatile("mov.u64 %0, %%clock64;" : "=l"(c) :: "memory"); return (uint32_t)(c >> 32) & blockIdx.y; }
__device__ __forceinline__ uint32_t uniform_zero_here() { uint32_t c; asm volatile("mov.u32 %0, %%clock;" : "=r"(c) :: "memory"); return c & blockIdx.y; }
__device__ __forceinline__ void wait_clk(uint32_t t0, uint32_t dt) {
  asm volatile("{\n.reg .pred p;\n.reg .u32 c;\nLOOP:\nmov.u32 c, %%clock;\nsub.u32 c, c, %0;\nsetp.lt.u32 p, c, %1;\n@p nanosleep.u32 100;\n@p bra LOOP;\n}\n" :: "r"(t0), "r"(dt) : "memory");
}
__device__ __forceinline__ void mbar_init(uint32_t bar, uint32_t cnt) { asm volatile("mbarrier.init.shared::cta.b64 [%0], %1;" :: "r"(bar), "r"(cnt) : "memory"); }
__device__ __forceinline__ void mbar_expect_tx(uint32_t bar, uint32_t bytes) { asm volatile("mbarrier.arrive.expect_tx.shared::cta.b64 _, [%0], %1;" :: "r"(bar), "r"(bytes) : "memory"); }
__device__ __forceinline__ void mbar_arrive(uint32_t bar) { asm volatile("mbarrier.arrive.shared::cta.b64 _, [%0];" :: "r"(bar) : "memory"); }
__device__ __forceinline__ void mbar_arrive_remote(uint32_t cluster_addr) { asm volatile("mbarrier.arrive.shared::cluster.b64 _, [%0];" :: "r"(cluster_addr) : "memory"); }
__device__ __forceinline__ void mbar_wait(uint32_t bar, uint32_t parity) {
  asm volatile("{\n.reg .pred p;\nLOOP:\nmbarrier.try_wait.parity.shared::cta.b64 p, [%0], %1;\n@!p bra LOOP;\n}\n" :: "r"(bar), "r"(parity) : "memory");
}
__device__ __forceinline__ void tma_load_2d(uint32_t dst, const CUtensorMap* tm, uint32_t bar, int c0, int c1) {
  asm volatile("cp.async.bulk.tensor.2d.shared::cluster.global.mbarrier::complete_tx::bytes [%0], [%1, {%3, %4}], [%2];"
    :: "r"(dst), "l"(tm), "r"(bar), "r"(c0), "r"(c1) : "memory");
}
__device__ __forceinline__ void tma_load_2d_hint(uint32_t dst, const CUtensorMap* tm, uint32_t bar, int c0, int c1, uint64_t pol) {
  asm volatile("cp.async.bulk.tensor.2d.shared::cluster.global.mbarrier::complete_tx::bytes.L2::cache_hint [%0], [%1, {%3, %4}], [%2], %5;"
    :: "r"(dst), "l"(tm), "r"(bar), "r"(c0), "r"(c1), "l"(pol) : "memory");
}
__device__ __forceinline__ uint64_t policy_evict_first() { uint64_t p; asm volatile("createpolicy.fractional.L2::evict_first.b64 %0, 1.0;" : "=l"(p)); return p; }
__device__ __forceinline__ void tma_store_2d(const CUtensorMap* tm, uint32_t src, int c0, int c1) {
  asm volatile("cp.async.bulk.tensor.2d.global.shared::cta.bulk_group [%0, {%2, %3}], [%1];" :: "l"(tm), "r"(src), "r"(c0), "r"(c1) : "memory");
}
__device__ __forceinline__ void bulk_load(uint32_t dst, const void* src, uint32_t bytes, uint32_t bar) {
  asm volatile("cp.async.bulk.shared::cluster.global.mbarrier::complete_tx::bytes [%0], [%1], %2, [%3];" :: "r"(dst), "l"(src), "r"(bytes), "r"(bar) : "memory");
}
__device__ __forceinline__ void prefetch_l2(const void* p) { asm volatile("prefetch.global.L2 [%0];" :: "l"(p)); }
__device__ __forceinline__ void bulk_commit() { asm volatile("cp.async.bulk.commit_group;" ::: "memory"); }
__device__ __forceinline__ void bulk_wait_all() { asm volatile("cp.async.bulk.wait_group 0;" ::: "memory"); }
__device__ __forceinline__ void fence_async_smem() { asm volatile("fence.proxy.async.shared::cta;" ::: "memory"); }
__device__ __forceinline__ void wgmma_fence() { asm volatile("wgmma.fence.sync.aligned;" ::: "memory"); }
__device__ __forceinline__ void wgmma_commit() { asm volatile("wgmma.commit_group.sync.aligned;" ::: "memory"); }
template<int N> __device__ __forceinline__ void wgmma_wait() { asm volatile("wgmma.wait_group.sync.aligned %0;" :: "n"(N) : "memory"); }
__device__ __forceinline__ void bar_sync(int id, int n) { asm volatile("bar.sync %0, %1;" :: "r"(id), "r"(n) : "memory"); }
__device__ __forceinline__ void bar_arrive(int id, int n) { asm volatile("bar.arrive %0, %1;" :: "r"(id), "r"(n) : "memory"); }
__device__ __forceinline__ void cluster_wait() { asm volatile("barrier.cluster.wait.aligned;" ::: "memory"); }
template<int R> __device__ __forceinline__ void reg_inc() { asm volatile("setmaxnreg.inc.sync.aligned.u32 %0;" :: "n"(R)); }
template<int R> __device__ __forceinline__ void reg_dec() { asm volatile("setmaxnreg.dec.sync.aligned.u32 %0;" :: "n"(R)); }
__device__ __forceinline__ bool elect_one() {
  uint32_t p;
  asm volatile("{\n.reg .pred q;\nelect.sync _|q, 0xffffffff;\nselp.u32 %0, 1, 0, q;\n}\n" : "=r"(p));
  return p != 0;
}
__device__ __forceinline__ uint32_t mapa(uint32_t addr, uint32_t cta) { uint32_t r; asm volatile("mapa.shared::cluster.u32 %0, %1, %2;" : "=r"(r) : "r"(addr), "r"(cta)); return r; }
__device__ __forceinline__ void st_async_v4(uint32_t addr, uint32_t bar, uint32_t a, uint32_t b, uint32_t c, uint32_t d) {
  asm volatile("st.async.weak.shared::cluster.mbarrier::complete_tx::bytes.v4.b32 [%0], {%2, %3, %4, %5}, [%1];" :: "r"(addr), "r"(bar), "r"(a), "r"(b), "r"(c), "r"(d) : "memory");
}
__device__ __forceinline__ void st_async_b32(uint32_t addr, uint32_t bar, uint32_t a) {
  asm volatile("st.async.weak.shared::cluster.mbarrier::complete_tx::bytes.b32 [%0], %2, [%1];" :: "r"(addr), "r"(bar), "r"(a) : "memory");
}
__device__ __forceinline__ void stsm_x4(uint32_t addr, uint32_t a, uint32_t b, uint32_t c, uint32_t d) {
  asm volatile("stmatrix.sync.aligned.m8n8.x4.shared.b16 [%0], {%1, %2, %3, %4};" :: "r"(addr), "r"(a), "r"(b), "r"(c), "r"(d) : "memory");
}
__device__ __forceinline__ void stsm_x4_t(uint32_t addr, uint32_t a, uint32_t b, uint32_t c, uint32_t d) {
  asm volatile("stmatrix.sync.aligned.m8n8.x4.trans.shared.b16 [%0], {%1, %2, %3, %4};" :: "r"(addr), "r"(a), "r"(b), "r"(c), "r"(d) : "memory");
}
__device__ __forceinline__ uint4 lds128(uint32_t addr) { uint4 v; asm volatile("ld.shared.v4.b32 {%0, %1, %2, %3}, [%4];" : "=r"(v.x), "=r"(v.y), "=r"(v.z), "=r"(v.w) : "r"(addr) : "memory"); return v; }
extern __shared__ __align__(1024) uint8_t smem_raw[];
template<class T> __device__ __forceinline__ T& SM(int off) { return *reinterpret_cast<T*>(smem_raw + off); }
__device__ __forceinline__ uint4 ldg_nc128(const void* p) { uint4 v; asm volatile("ld.global.nc.v4.b32 {%0, %1, %2, %3}, [%4];" : "=r"(v.x), "=r"(v.y), "=r"(v.z), "=r"(v.w) : "l"(p)); return v; }
__device__ __forceinline__ uint4 ldg128(const void* p) { uint4 v; asm volatile("ld.global.L1::no_allocate.v4.b32 {%0, %1, %2, %3}, [%4];" : "=r"(v.x), "=r"(v.y), "=r"(v.z), "=r"(v.w) : "l"(p) : "memory"); return v; }
__device__ __forceinline__ void pkt_st128(void* p, uint32_t a, uint32_t b, uint32_t c, uint32_t d) {
  asm volatile("{\n.reg .b128 v;\n.reg .b64 lo, hi;\nmov.b64 lo, {%1, %2};\nmov.b64 hi, {%3, %4};\nmov.b128 v, {lo, hi};\nst.relaxed.gpu.global.b128 [%0], v;\n}\n"
    :: "l"(p), "r"(a), "r"(b), "r"(c), "r"(d) : "memory");
}
__device__ __forceinline__ uint4 pkt_ld128(const void* p) {
  uint4 r;
  asm volatile("{\n.reg .b128 v;\n.reg .b64 lo, hi;\nld.relaxed.gpu.global.b128 v, [%4];\nmov.b128 {lo, hi}, v;\nmov.b64 {%0, %1}, lo;\nmov.b64 {%2, %3}, hi;\n}\n"
    : "=r"(r.x), "=r"(r.y), "=r"(r.z), "=r"(r.w) : "l"(p) : "memory");
  return r;
}
__device__ __forceinline__ void pkt_st64(void* p, uint32_t a, uint32_t b) {
  asm volatile("{\n.reg .b64 v;\nmov.b64 v, {%1, %2};\nst.relaxed.gpu.global.b64 [%0], v;\n}\n" :: "l"(p), "r"(a), "r"(b) : "memory");
}
__device__ __forceinline__ uint2 pkt_ld64(const void* p) {
  uint2 r;
  asm volatile("{\n.reg .b64 v;\nld.relaxed.gpu.global.b64 v, [%2];\nmov.b64 {%0, %1}, v;\n}\n" : "=r"(r.x), "=r"(r.y) : "l"(p) : "memory");
  return r;
}
__device__ __forceinline__ void pkt_clear128(void* p) { pkt_st128(p, 0, 0, 0, 0); }
__device__ __forceinline__ uint32_t ld_relaxed32(const void* p) { uint32_t v; asm volatile("ld.relaxed.gpu.global.b32 %0, [%1];" : "=r"(v) : "l"(p) : "memory"); return v; }
__device__ __forceinline__ uint32_t ld_acquire32(const void* p) { uint32_t v; asm volatile("ld.acquire.gpu.global.b32 %0, [%1];" : "=r"(v) : "l"(p) : "memory"); return v; }
__device__ __forceinline__ void st_relaxed32(void* p, uint32_t v) { asm volatile("st.relaxed.gpu.global.b32 [%0], %1;" :: "l"(p), "r"(v) : "memory"); }
__device__ __forceinline__ uint32_t poll64(const void* p, uint32_t tag, int ns) {
  uint2 v; uint32_t n = 0;
  bool more;
#pragma unroll 1
  do {
    v = pkt_ld64(p);
    more = !(v.y == tag) && ++n < SPIN_LIMIT;
    if (more) { __nanosleep(ns); }
  } while (more);
  return v.x;
}
__device__ __forceinline__ uint32_t poll64_warp(const void* p, uint32_t tag, int ns) {
  uint2 v; uint32_t n = 0;
  bool more;
#pragma unroll 1
  do {
    v = pkt_ld64(p);
    more = !(__all_sync(0xffffffffu, v.y == tag)) && ++n < SPIN_LIMIT;
    if (more) { __nanosleep(ns); }
  } while (more);
  return v.x;
}
__device__ __forceinline__ uint32_t code_of(uint32_t tag) { return tag % 3u + 1u; }
__device__ __forceinline__ uint32_t with_bit(uint32_t v, uint32_t bit) { return (v & ~1u) | (bit & 1u); }
__device__ __forceinline__ uint32_t with_bit(float v, uint32_t bit) { return with_bit(__float_as_uint(v), bit); }
__device__ __forceinline__ float no_bit(uint32_t v) { return __uint_as_float(v & ~1u); }
__device__ __forceinline__ void chk(uint32_t& bad, uint32_t a, uint32_t want) { bad |= a ^ want; asm("" : "+r"(bad)); }
__device__ __forceinline__ void chk_code(uint32_t& bad, const uint4& v, uint32_t c0, uint32_t c1) { chk(bad, v.x, c0); chk(bad, v.y, c1); chk(bad, v.z, c0); chk(bad, v.w, c1); }
__device__ __forceinline__ uint32_t pack_bf16(float lo, float hi) { uint32_t r; asm("cvt.rn.bf16x2.f32 %0, %1, %2;" : "=r"(r) : "f"(hi), "f"(lo)); return r; }
__device__ __forceinline__ float bf_lo(uint32_t v) { return __uint_as_float(v << 16); }
__device__ __forceinline__ float bf_hi(uint32_t v) { return __uint_as_float(v & 0xFFFF0000u); }
__device__ __forceinline__ float bf16r(float x) { return __uint_as_float(pack_bf16(0.f, x)); }
__device__ __forceinline__ void st_bf16(bf16* p, float x) { *reinterpret_cast<uint16_t*>(p) = (uint16_t)pack_bf16(x, 0.f); }
__device__ __forceinline__ float fast_rcp(float x) { float r; asm("rcp.approx.f32 %0, %1;" : "=f"(r) : "f"(x)); return r; }
__device__ __forceinline__ float ldbf(const bf16* p) { return __bfloat162float(*p); }
__device__ __forceinline__ uint32_t badd2(uint32_t a, uint32_t b) { uint32_t r; asm("add.rn.bf16x2 %0, %1, %2;" : "=r"(r) : "r"(a), "r"(b)); return r; }
__device__ __forceinline__ uint32_t bfma2(uint32_t a, uint32_t b, uint32_t c) { uint32_t r; asm("fma.rn.bf16x2 %0, %1, %2, %3;" : "=r"(r) : "r"(a), "r"(b), "r"(c)); return r; }
__device__ __forceinline__ float warp_sum(float v) {
#pragma unroll
  for (int o = 16; o > 0; o >>= 1) v += __shfl_xor_sync(0xffffffffu, v, o);
  return v;
}
template<int N> __device__ __forceinline__ void fold(float* v, int o, int lane) {
  const bool up = lane & o;
#pragma unroll
  for (int i = 0; i < N / 2; i++) {
    const float keep = up ? v[N / 2 + i] : v[i], send = up ? v[i] : v[N / 2 + i];
    v[i] = keep + __shfl_xor_sync(0xffffffffu, send, o);
  }
}
__device__ __forceinline__ uint32_t make_key(float r_bf, int row) {
  const uint32_t u = __float_as_uint(r_bf);
  return (((u & 0x80000000u) ? ~u : (u | 0x80000000u)) & 0xFFFF0000u) | (0xFFFFu - (uint32_t)row);
}
__device__ __forceinline__ int key_row(uint32_t key) { return (0xFFFF - (int)(key & 0xFFFFu)) & 2047; }
__device__ __forceinline__ float key_val(uint32_t key) { const uint32_t o = key & 0xFFFF0000u; return __uint_as_float((o & 0x80000000u) ? (o & 0x7FFFFFFFu) : (~o & 0xFFFF0000u)); }
__device__ __forceinline__ float ref_sd(float var) { float r; asm("sqrt.approx.f32 %0, %1;" : "=f"(r) : "f"(bf16r(bf16r(var) + 1e-5f))); return bf16r(r); }
__device__ __forceinline__ uint64_t make_desc(uint32_t addr) { return (uint64_t)((addr & 0x3FFFF) >> 4) | ((uint64_t)64 << 32) | ((uint64_t)1 << 62); }
__device__ __forceinline__ uint64_t make_desc_noswz(uint32_t addr) { return (uint64_t)((addr & 0x3FFFF) >> 4) | ((uint64_t)8 << 32); }
#define ACC8(d, o) "+f"(d[o]), "+f"(d[o + 1]), "+f"(d[o + 2]), "+f"(d[o + 3]), "+f"(d[o + 4]), "+f"(d[o + 5]), "+f"(d[o + 6]), "+f"(d[o + 7])
#define ACC64(d, o) ACC8(d, o), ACC8(d, o + 8), ACC8(d, o + 16), ACC8(d, o + 24), ACC8(d, o + 32), ACC8(d, o + 40), ACC8(d, o + 48), ACC8(d, o + 56)
#define REGS64 "%0, %1, %2, %3, %4, %5, %6, %7, %8, %9, %10, %11, %12, %13, %14, %15, %16, %17, %18, %19, %20, %21, %22, %23, %24, %25, %26, %27, %28, %29, %30, %31, " \
    "%32, %33, %34, %35, %36, %37, %38, %39, %40, %41, %42, %43, %44, %45, %46, %47, %48, %49, %50, %51, %52, %53, %54, %55, %56, %57, %58, %59, %60, %61, %62, %63"
#define REGS128 REGS64 ", %64, %65, %66, %67, %68, %69, %70, %71, %72, %73, %74, %75, %76, %77, %78, %79, %80, %81, %82, %83, %84, %85, %86, %87, %88, %89, %90, %91, %92, %93, %94, %95, " \
    "%96, %97, %98, %99, %100, %101, %102, %103, %104, %105, %106, %107, %108, %109, %110, %111, %112, %113, %114, %115, %116, %117, %118, %119, %120, %121, %122, %123, %124, %125, %126, %127"
__device__ __forceinline__ void wgmma_n256(float (&d)[128], uint64_t da, uint64_t db) {
  asm volatile("wgmma.mma_async.sync.aligned.m64n256k16.f32.bf16.bf16 {" REGS128 "}, %128, %129, 1, 1, 1, 0, 0;\n"
    : ACC64(d, 0), ACC64(d, 64) : "l"(da), "l"(db));
}
#define OUT8(d, o) "=f"(d[o]), "=f"(d[o + 1]), "=f"(d[o + 2]), "=f"(d[o + 3]), "=f"(d[o + 4]), "=f"(d[o + 5]), "=f"(d[o + 6]), "=f"(d[o + 7])
#define OUT64(d, o) OUT8(d, o), OUT8(d, o + 8), OUT8(d, o + 16), OUT8(d, o + 24), OUT8(d, o + 32), OUT8(d, o + 40), OUT8(d, o + 48), OUT8(d, o + 56)
__device__ __forceinline__ void wgmma_n256_rs_init(float (&d)[128], const uint32_t* a, uint64_t db) {
  asm volatile("wgmma.mma_async.sync.aligned.m64n256k16.f32.bf16.bf16 {" REGS128 "}, {%128, %129, %130, %131}, %132, 0, 1, 1, 0;\n"
    : OUT64(d, 0), OUT64(d, 64) : "r"(a[0]), "r"(a[1]), "r"(a[2]), "r"(a[3]), "l"(db));
}
template<int ACCUM> __device__ __forceinline__ void wgmma_n256_rs(float (&d)[128], const uint32_t* a, uint64_t db) {
  asm volatile("wgmma.mma_async.sync.aligned.m64n256k16.f32.bf16.bf16 {" REGS128 "}, {%128, %129, %130, %131}, %132, %133, 1, 1, 0;\n"
    : ACC64(d, 0), ACC64(d, 64) : "r"(a[0]), "r"(a[1]), "r"(a[2]), "r"(a[3]), "l"(db), "n"(ACCUM));
}
template<int ACCUM> __device__ __forceinline__ void wgmma_n8_rs(float (&d)[4], const uint32_t* a, uint64_t db) {
  asm volatile("wgmma.mma_async.sync.aligned.m64n8k16.f32.bf16.bf16 {%0, %1, %2, %3}, {%4, %5, %6, %7}, %8, %9, 1, 1, 0;\n"
    : "+f"(d[0]), "+f"(d[1]), "+f"(d[2]), "+f"(d[3]) : "r"(a[0]), "r"(a[1]), "r"(a[2]), "r"(a[3]), "l"(db), "n"(ACCUM));
}
__device__ __forceinline__ void wgmma_n8(float (&d)[4], uint64_t da, uint64_t db) {
  asm volatile("wgmma.mma_async.sync.aligned.m64n8k16.f32.bf16.bf16 {%0, %1, %2, %3}, %4, %5, 1, 1, 1, 0, 0;\n"
    : "+f"(d[0]), "+f"(d[1]), "+f"(d[2]), "+f"(d[3]) : "l"(da), "l"(db));
}
__device__ __forceinline__ void wgmma_n128(float (&d)[64], uint64_t da, uint64_t db) {
  asm volatile("wgmma.mma_async.sync.aligned.m64n128k16.f32.bf16.bf16 {" REGS64 "}, %64, %65, 1, 1, 1, 0, 0;\n" : ACC64(d, 0) : "l"(da), "l"(db));
}
template<int N> __device__ __forceinline__ void fence_regs(float (&d)[N]) {
#pragma unroll
  for (int i = 0; i < N; i++) asm volatile("" : "+f"(d[i]) :: "memory");
}
__device__ __forceinline__ void mma16816(float (&c)[4], uint32_t a0, uint32_t a1, uint32_t a2, uint32_t a3, uint32_t b0, uint32_t b1) {
  asm volatile("mma.sync.aligned.m16n8k16.row.col.f32.bf16.bf16.f32 {%0, %1, %2, %3}, {%4, %5, %6, %7}, {%8, %9}, {%0, %1, %2, %3};"
               : "+f"(c[0]), "+f"(c[1]), "+f"(c[2]), "+f"(c[3]) : "r"(a0), "r"(a1), "r"(a2), "r"(a3), "r"(b0), "r"(b1));
}
__device__ __forceinline__ void fma8(float* acc, const uint4& v, float x) {
  acc[0] = fmaf(bf_lo(v.x), x, acc[0]); acc[1] = fmaf(bf_hi(v.x), x, acc[1]); acc[2] = fmaf(bf_lo(v.y), x, acc[2]); acc[3] = fmaf(bf_hi(v.y), x, acc[3]);
  acc[4] = fmaf(bf_lo(v.z), x, acc[4]); acc[5] = fmaf(bf_hi(v.z), x, acc[5]); acc[6] = fmaf(bf_lo(v.w), x, acc[6]); acc[7] = fmaf(bf_hi(v.w), x, acc[7]);
}
template<int PITCH> __device__ __forceinline__ void gemv8x8(float (&acc)[8], uint32_t addr, const float (&x)[8]) {
  uint4 v[2][2];
  v[0][0] = lds128(addr); v[0][1] = lds128(addr + PITCH);
#pragma unroll
  for (int b = 0; b < 4; b++) {
    if (b < 3) { v[(b + 1) & 1][0] = lds128(addr + (2 * b + 2) * PITCH); v[(b + 1) & 1][1] = lds128(addr + (2 * b + 3) * PITCH); }
    acc[0] += __uint_as_float(zero_here());
    fma8(acc, v[b & 1][0], x[2 * b]); fma8(acc, v[b & 1][1], x[2 * b + 1]);
  }
}
__device__ __forceinline__ float swiglu(float g, float u) {
  g = bf16r(g); u = bf16r(u);
  return bf16r(bf16r(g * fast_rcp(1.f + __expf(-g))) * u);
}

#define CT(slot) do {} while (0)
#define TIM(slot) do {} while (0)

constexpr int H_BUF0 = 0, H_BUF1 = 16384, H_RED = 32768, H_KEYS = H_RED + 1024, H_ROW = H_KEYS + 1024, H_ACT = H_ROW + 8192, H_PART = H_ACT + 4096;
__device__ __forceinline__ void hsync() { bar_sync(NB_H, 256); }
template<int N> __device__ __forceinline__ void block_sum(float (&v)[N], int warp, int lane) {
#pragma unroll
  for (int i = 0; i < N; i++) v[i] = warp_sum(v[i]);
  hsync();
  if (lane == 0) {
#pragma unroll
    for (int i = 0; i < N; i++) SM<float>(H_RED + (i * 8 + warp) * 4) = v[i];
  }
  hsync();
#pragma unroll
  for (int i = 0; i < N; i++) {
    const float4 a = SM<float4>(H_RED + i * 32), b = SM<float4>(H_RED + i * 32 + 16);
    v[i] = ((a.x + a.y) + (a.z + a.w)) + ((b.x + b.y) + (b.z + b.w));
  }
}
__device__ __forceinline__ void fft_first(int j, float2 v0, float2 v1, float2 v2, float2 v3) {
  const float2 a = make_float2(v0.x + v2.x, v0.y + v2.y), b = make_float2(v0.x - v2.x, v0.y - v2.y);
  const float2 c = make_float2(v1.x + v3.x, v1.y + v3.y), d = make_float2(v1.y - v3.y, v3.x - v1.x);
  SM<float4>(H_BUF1 + j * 32) = make_float4(a.x + c.x, a.y + c.y, b.x + d.x, b.y + d.y);
  SM<float4>(H_BUF1 + j * 32 + 16) = make_float4(a.x - c.x, a.y - c.y, b.x - d.x, b.y - d.y);
}
template<int NB> __device__ __forceinline__ void fft_passes(int tid) {
  constexpr int q = 256 * NB;
#pragma unroll 1
  for (int ps = 1; ps < 5; ps++) {
    const int ns = 1 << (2 * ps), k = tid & (ns - 1);
    float s1, c1;
    __sincosf(-1.57079632679f * __fdividef((float)k, (float)ns), &s1, &c1);
    const float c2 = c1 * c1 - s1 * s1, s2 = 2.f * c1 * s1, c3 = c1 * c2 - s1 * s2, s3 = c1 * s2 + s1 * c2;
    hsync();
#pragma unroll
    for (int i = 0; i < NB; i++) {
      const int j = tid + 256 * i;
      const float2* in = &SM<float2>((ps & 1) ? H_BUF1 : H_BUF0);
      float2* o = &SM<float2>((ps & 1) ? H_BUF0 : H_BUF1) + (j - k) * 4 + k;
      const float2 v0 = in[j], x1 = in[j + q], x2 = in[j + 2 * q], x3 = in[j + 3 * q];
      const float2 v1 = make_float2(x1.x * c1 - x1.y * s1, x1.x * s1 + x1.y * c1);
      const float2 v2 = make_float2(x2.x * c2 - x2.y * s2, x2.x * s2 + x2.y * c2);
      const float2 v3 = make_float2(x3.x * c3 - x3.y * s3, x3.x * s3 + x3.y * c3);
      const float2 a = make_float2(v0.x + v2.x, v0.y + v2.y), b = make_float2(v0.x - v2.x, v0.y - v2.y);
      const float2 c = make_float2(v1.x + v3.x, v1.y + v3.y), d = make_float2(v1.y - v3.y, v3.x - v1.x);
      o[0] = make_float2(a.x + c.x, a.y + c.y); o[ns] = make_float2(b.x + d.x, b.y + d.y);
      o[2 * ns] = make_float2(a.x - c.x, a.y - c.y); o[3 * ns] = make_float2(b.x - d.x, b.y - d.y);
    }
  }
  hsync();
}
template<int NR> __device__ __forceinline__ void ln_rows(const float (&h)[NR][4], float (&hn)[NR][4], int warp, int lane) {
  float s[NR], q[NR];
#pragma unroll
  for (int i = 0; i < NR; i++) s[i] = (h[i][0] + h[i][1]) + (h[i][2] + h[i][3]);
  block_sum(s, warp, lane);
#pragma unroll
  for (int i = 0; i < NR; i++) {
    s[i] *= 1.f / 1024.f; q[i] = 0.f;
#pragma unroll
    for (int z = 0; z < 4; z++) q[i] = fmaf(h[i][z] - s[i], h[i][z] - s[i], q[i]);
  }
  block_sum(q, warp, lane);
#pragma unroll
  for (int i = 0; i < NR; i++) {
    const float mb = bf16r(s[i]), inv = fast_rcp(ref_sd(q[i] * (1.f / 1024.f)));
#pragma unroll
    for (int z = 0; z < 4; z++) hn[i][z] = bf16r(bf16r(h[i][z] - mb) * inv);
  }
}
__device__ __forceinline__ float routed_out(float h, float hn, float y, float r) {
  const float sig = bf16r(fast_rcp(1.f + __expf(-r)));
  return h + bf16r(hn + bf16r(bf16r(y) * sig));
}

__device__ __forceinline__ void helper_cta(const Params& p, const int hi, const uint32_t t_entry) {
  const int tid = threadIdx.x, warp = tid >> 5, lane = tid & 31;
  const float w0 = ldbf(p.wr + tid), w1 = ldbf(p.wr + tid + 256), w2 = ldbf(p.wr + tid + 512), w3 = ldbf(p.wr + tid + 768), wf = ldbf(p.wr);
  const uint32_t tag = ld_relaxed32(&p.sc->epoch) + 1;
  pkt_clear128(&p.sc->u[hi * 512 + tid * 2]);
  if (tid == 0 && w0 != 123.f) TIM(12);
  fft_first(tid, make_float2(w0, 0.f), make_float2(w1, 0.f), make_float2(w2, 0.f), make_float2(w3, 0.f));
  fft_passes<1>(tid);
  const uint32_t c0 = code_of(tag), c1 = c0 >> 1;
  {
    const float off = wf - SM<float>(H_BUF1) * (1.f / 1024.f);
    const float4 v = SM<float4>(H_BUF1 + tid * 32), u = SM<float4>(H_BUF1 + tid * 32 + 16);
    pkt_st128(&p.sc->u[hi * 512 + ((tid & 192) + (tid & 1) * 32 + ((tid >> 1) & 31)) * 2], with_bit(pack_bf16((tid ? v.x : 0.f) - off, v.z - off), c0), with_bit(pack_bf16(v.y, v.w), c1),
              with_bit(pack_bf16(u.x - off, u.z - off), c0), with_bit(pack_bf16(u.y, u.w), c1));
    if (tid < 64) pkt_clear128(&p.sc->cl[(hi * 32 + (tid >> 1)) * 16 + (tid & 1) * 2]);
    hsync();
  }
  if (tid == 0) TIM(0);
  {
    float tw[8];
#pragma unroll
    for (int i = 0; i < 4; i++) __sincosf((float)(tid + 256 * i) * (-6.28318530718f / 2048.f), &tw[2 * i], &tw[2 * i + 1]);
    wait_clk(t_entry, Z_CLK);
    uint2 z[8]; uint32_t n = 0;
    bool more;
#pragma unroll 1
    do {
      uint32_t bad = 0;
#pragma unroll
      for (int i = 0; i < 8; i++) z[i] = pkt_ld64(reinterpret_cast<const uint2*>(&p.sc->xz[tid]) + 512 * i + 1);
#pragma unroll
      for (int i = 0; i < 8; i++) chk(bad, z[i].y, tag);
      more = !(!bad) && ++n < SPIN_LIMIT;
      if (more) { __nanosleep(150); }
    } while (more);
#pragma unroll
    for (int i = 0; i < 2; i++)
      fft_first(tid + 256 * i, make_float2(bf_lo(z[i].x), bf_hi(z[i].x)), make_float2(bf_lo(z[i + 2].x), bf_hi(z[i + 2].x)),
                make_float2(bf_lo(z[i + 4].x), bf_hi(z[i + 4].x)), make_float2(bf_lo(z[i + 6].x), bf_hi(z[i + 6].x)));
    if (tid == 0) TIM(7);
    fft_passes<2>(tid);
    if (tid == 0) TIM(1);
    uint32_t k8[8];
#pragma unroll
    for (int i = 0; i < 4; i++) {
      const int k = tid + 256 * i;
      const float2 v0 = SM<float2>(H_BUF1 + k * 8), v1 = SM<float2>(H_BUF1 + (k + 1024) * 8);
      const float w = v1.x * tw[2 * i + 1] - v1.y * tw[2 * i];
      const uint32_t a = __float_as_uint(v0.x + w), b = __float_as_uint(v0.x - w);
      k8[2 * i] = (((a & 0x80000000u) ? ~a : (a | 0x80000000u)) & ~2047u) | k;
      k8[2 * i + 1] = (((b & 0x80000000u) ? ~b : (b | 0x80000000u)) & ~2047u) | (k + 1024);
    }
    uint32_t lim = 0xFFFFFFFFu;
#pragma unroll 1
    for (int r = 0; r < 4; r++) {
      uint32_t mx = 0;
#pragma unroll
      for (int i = 0; i < 8; i++) mx = max(mx, k8[i] <= lim ? k8[i] : 0u);
      mx = __reduce_max_sync(0xffffffffu, mx);
      if (lane == 0) SM<uint32_t>(H_KEYS + (warp * 4 + r) * 4) = mx;
      lim = mx - 1;
    }
    hsync();
    if (tid < 32) {
      const uint32_t me = SM<uint32_t>(H_KEYS + tid * 4);
      int rank = 0;
#pragma unroll
      for (int i = 0; i < 8; i++) { const uint4 o = SM<uint4>(H_KEYS + i * 16); rank += (o.x > me) + (o.y > me) + (o.z > me) + (o.w > me); }
      if (rank < 8) SM<uint16_t>(H_KEYS + 256 + rank * 2) = me & 2047u;
    }
    hsync();
    if (tid >= 128) pkt_st64(&p.sc->cl[(hi * 32 + ((tid - 128) >> 2)) * 16 + (tid & 3)], SM<uint32_t>(H_KEYS + 256 + (tid & 3) * 4), tag);
  }
  const uint32_t cpair = SM<uint32_t>(H_KEYS + 256 + hi * 4);
  const int ca = cpair & 0xFFFF, cb = cpair >> 16;
  if (tid < 128) prefetch_l2(((tid & 32) ? p.Wim : p.Wre) + (size_t)((tid & 64) ? cb : ca) * 2048 + lane * 64);
  if (tid == 0) TIM(2);
}

__device__ __forceinline__ void slow_path(const Params& p, int grp, int eps, uint32_t tag, uint32_t key, int win, float mb, float inv) {
  const int tid = threadIdx.x + zero_here(), warp = tid >> 5, lane = tid & 31;
  uint32_t best = __reduce_max_sync(0xffffffffu, poll64(&p.sc->key[tid & 127], tag, 200));
  if (lane == 0) SM<uint32_t>(H_KEYS + warp * 4) = best;
  hsync();
  { const uint4 b4 = SM<uint4>(H_KEYS); best = max(max(b4.x, b4.y), max(b4.z, b4.w)); }
  const int tw = key_row(best), col = eps * 128 + (tid & 127);
  if ((tw >> 7) != grp) return;
  if (tid < 128) {
    const int pos = (col >> 4) * 8 + (col & 7);
    const uint32_t a = poll64(&p.sc->ch[win * 512 + pos], tag, 100);
    const float hc = (col & 8) ? bf_hi(a) : bf_lo(a);
    poll64(&p.sc->rdone[col >> 3], tag, 100);
    st_bf16(p.out + key_row(key) * 1024 + col, hc + bf16r(bf16r(hc - mb) * inv));
  }
  const uint32_t h0 = poll64(&p.sc->hrow[(tw >> 4) * 512 + 2 * tid], tag, 100), h1 = poll64(&p.sc->hrow[(tw >> 4) * 512 + 2 * tid + 1], tag, 100);
  float h[1][4] = {{bf_lo(h0), bf_hi(h0), bf_lo(h1), bf_hi(h1)}}, hn[1][4];
  ln_rows<1>(h, hn, warp, lane);
  SM<float4>(H_ROW + tid * 16) = make_float4(hn[0][0], hn[0][1], hn[0][2], hn[0][3]);
  SM<float4>(H_ROW + 4096 + tid * 16) = make_float4(h[0][0], h[0][1], h[0][2], h[0][3]);
  hsync();
#pragma unroll 1
  for (int ph = 0; ph < 2; ph++) {
    const int part = min(tid / 56, 3), fh = tid >> 7, len = ph ? 224 : 512, ld = ph ? 1024 : 3584;
    const bf16* wp = ph ? p.wdown + (eps * 448 + fh * 224) * 1024 + (tid & 127) * 8
                        : ((part & 1) ? p.wup : p.wgate) + (part >> 1) * 512 * 3584 + eps * 448 + min(tid - part * 56, 55) * 8;
    const int xo = ph ? H_ACT + fh * 224 * 4 : H_ROW + (part >> 1) * 2048;
    float acc[8] = {0.f, 0.f, 0.f, 0.f, 0.f, 0.f, 0.f, 0.f};
#pragma unroll 8
    for (int d = 0; d < (len & ~7); d++) fma8(acc, ldg_nc128(wp + d * ld), SM<float>(xo + d * 4));
    SM<float4>(H_PART + tid * 32) = make_float4(acc[0], acc[1], acc[2], acc[3]);
    SM<float4>(H_PART + tid * 32 + 16) = make_float4(acc[4], acc[5], acc[6], acc[7]);
    hsync();
    if (ph) break;
#pragma unroll 1
    for (int f = tid; f < 448; f += 256)
      SM<float>(H_ACT + f * 4) = swiglu(SM<float>(H_PART + f * 4) + SM<float>(H_PART + (896 + f) * 4), SM<float>(H_PART + (448 + f) * 4) + SM<float>(H_PART + (1344 + f) * 4));
    hsync();
  }
#pragma unroll 1
  for (int e = tid; e < 1024; e += 256) pkt_st64(&p.sc->fpart[eps * 1024 + e], __float_as_uint(SM<float>(H_PART + e * 4) + SM<float>(H_PART + (1024 + e) * 4)), tag);
  if (tid < 128) {
    float y = 0.f;
#pragma unroll 1
    for (int q = 0; q < 8; q++) y += __uint_as_float(poll64(&p.sc->fpart[q * 1024 + col], tag, 200));
    st_bf16(p.out + tw * 1024 + col, routed_out(SM<float>(H_ROW + 4096 + col * 4), SM<float>(H_ROW + col * 4), y, key_val(best)));
  }
}

template<int MAP>
__global__ void __cluster_dims__(2, 1, 1) __launch_bounds__(NTHR, 1)
fnet_moe_kernel(const __grid_constant__ Params p) {
  const uint32_t t_entry = clk32();
  uint32_t smid;
  asm("mov.u32 %0, %%smid;" : "=r"(smid));
  const int tpc = smid >> 1, m = blockIdx.x & 1;
  if (MAP == 1 ? tpc >= 64 : (tpc >> 1) == 30) {
    if (threadIdx.x < 256) helper_cta(p, (tpc & 1) * 2 + m, t_entry);
    return;
  }
  const uint32_t sb = smem_u32(smem_raw);
  const int tid = threadIdx.x, lane = tid & 31;
  const int e7 = ((tpc - 32) * 37) >> 8;
  const int tau = MAP == 1 || tpc < 32 ? (tpc & 7) : (tpc < 60 ? tpc - 31 - 7 * e7 : 0);
  const int eps = MAP == 1 || tpc < 32 ? (tpc >> 3) : (tpc < 60 ? 4 + e7 : tpc - 58);
  const int cid = tau * 16 + eps * 2 + m;
  auto BAR = [&](int i) { return sb + OFF_BAR + 8 * i; };
  const CUtensorMap* tmD = &p.tmD0 + m;
#define LOAD_STREAM(d, tm, bar, c0, c1) tma_load_2d_hint(d, tm, bar, c0, c1, pol_ef)
#define LOAD_W tma_load_2d
#define LOAD_D tma_load_2d
#define LOAD_X tma_load_2d
#define LOAD_F LOAD_STREAM

  uint32_t tag = 0;
  uint4 wq = make_uint4(0, 0, 0, 0);
  if ((tid >> 5) == 4) {
    if (elect_one()) {
      const uint64_t pol_ef = policy_evict_first();
#pragma unroll
      for (int k = 0; k < 4; k++) mbar_init(BAR(B_FULL + k), 1);
      asm volatile("fence.mbarrier_init.release.cluster;" ::: "memory");
#pragma unroll
      for (int k = 0; k < 4; k++) {
        mbar_expect_tx(BAR(B_FULL + k), ST_BYTES);
        tma_load_2d(sb + k * ST_BYTES + A_BYTES, &p.tmX, BAR(B_FULL + k), k * 64, tau * 256);
        LOAD_D(sb + k * ST_BYTES, tmD, BAR(B_FULL + k), k * 64, eps * 128);
        TIM(k);
      }
    }
  } else if ((tid >> 5) == 1) {
    if (elect_one()) {
#pragma unroll
      for (int s = 0; s < 4; s++) { mbar_init(BAR(B_EMPTY + s), 1); mbar_init(BAR(B_SD + s), 1); }
#pragma unroll
      for (int s = 0; s < 8; s++) { mbar_init(BAR(B_EP + s), 4); mbar_init(BAR(B_AW + s), 1); }
      mbar_init(BAR(B_STAT), 4); mbar_init(BAR(B_WC), 1); mbar_init(BAR(B_CD), 2);
      mbar_init(BAR(B_E24), 1); mbar_init(BAR(B_CH), 1); mbar_init(BAR(B_INFO), 1); mbar_init(BAR(B_PEER), 1);
      mbar_init(BAR(B_XCH), 1); mbar_init(BAR(B_XCH + 1), 1); mbar_init(BAR(B_GUX), 1);
      asm volatile("fence.mbarrier_init.release.cluster;" ::: "memory");
      mbar_expect_tx(BAR(B_XCH), 16384); mbar_expect_tx(BAR(B_XCH + 1), 16384); mbar_expect_tx(BAR(B_GUX), 256);
    }
  } else if (tid >= 256) {
    if (START_PF) prefetch_l2(((tid & 64) ? (cid < 64 ? p.Dre : p.Dim) + (cid & 63) * 16384 : p.x + cid * 16384) + ((tid >> 2) & 15) * 1024 + (tid & 3) * 64);
    tag = ld_relaxed32(&p.sc->epoch + threadIdx.y);
    wq = ldg128(p.wr + (tid & 127) * 8);
  }
  const int warp = __shfl_sync(0xffffffffu, tid >> 5, 0);
  __syncthreads();
  asm volatile("barrier.cluster.arrive.relaxed.aligned;" ::: "memory");

  if (warp >= 8) {
    reg_dec<72>();
    cluster_wait();
    tag = __shfl_sync(0xffffffffu, tag, 0) + 1;
    const int cid0 = cid;
    const uint32_t tag0 = tag, sb0 = sb;
    int a, lane, j, cid, tau, eps, m, grp, abrow, fc, src;
    uint32_t tag, c0, c1, sb, buf, bar0;
    bool ffn;
    auto BAR = [&](int i) { return sb + OFF_BAR + 8 * i; };
    auto fresh_ids = [&]() {
      const uint32_t z = uniform_zero_here();
      uint32_t l; asm volatile("mov.u32 %0, %%laneid;" : "=r"(l));
      a = warp - 8 + z; lane = l; j = a * 32 + l;
      cid = cid0 + z; tau = cid >> 4; eps = (cid >> 1) & 7; m = cid & 1; grp = tau * 2 + m; abrow = m * 1024 + eps * 128;
      ffn = eps > 0; fc = (tau * 7 + eps - 1) * 64; src = (fc >> 5) + m;
      tag = tag0 + z; c0 = code_of(tag); c1 = c0 >> 1;
      sb = sb0 + z; buf = sb + OFF_AUX + a * 8192; bar0 = BAR(B_AW + 2 * a);
    };
    fresh_ids();
    if (a == 0 && lane < 16) pkt_clear128(&p.sc->xz[cid * 16 + lane]);
    if (lane < 2) pkt_clear128(&p.sc->dsum[cid * 16 + a * 4 + lane * 2]);
    if (a == 3 && lane < 8) pkt_clear128((lane < 4 ? p.sc->abdone : p.sc->abflag) + (cid * 2 + ((lane >> 1) & 1)) * 32 + (lane & 1) * 4);
    {
      const float s = warp_sum(((bf_lo(wq.x) + bf_hi(wq.x)) + (bf_lo(wq.y) + bf_hi(wq.y))) + ((bf_lo(wq.z) + bf_hi(wq.z)) + (bf_lo(wq.w) + bf_hi(wq.w))));
      if ((j >> 4) == eps) SM<uint4>(OFF_WR + (j & 15) * 16) = wq;
      if (lane == 0) { SM<float>(INFO_DS + a * 4) = s; SM<uint32_t>(INFO_ONES + a * 4) = 0x3F803F80u; }
    }
    const bf16* xrows = p.x + (cid * 16 + a * 4) * 1024;
    const bf16* drows = (cid < 64 ? p.Dre : p.Dim) + ((cid & 63) * 16 + a * 4) * 1024;
    if (XROW_PF) {
      wait_clk(t_entry, XROW_PF);
      prefetch_l2(xrows + lane * 64); prefetch_l2(xrows + 2048 + lane * 64);
    }
    fresh_ids();
    {
      wait_clk(t_entry, U_CLK);
      uint4 u[8]; uint32_t n = 0;
      bool more;
#pragma unroll 1
      do {
        uint32_t bad = 0;
#pragma unroll
        for (int q = 0; q < 8; q++) u[q] = pkt_ld128(&p.sc->u[a * 512 + lane * 2] + q * 64);
        if (n == 0 && lane < 2) { mbar_expect_tx(bar0 + lane * 8, 4096); bulk_load(buf + lane * 4096, xrows + lane * 2048, 4096, bar0 + lane * 8); }
#pragma unroll
        for (int q = 0; q < 8; q++) chk_code(bad, u[q], c0, c1);
        more = !(!__any_sync(0xffffffffu, bad & 1)) && ++n < SPIN_LIMIT;
        if (more) { __nanosleep(200); }
      } while (more);
      if (j == 0) TIM(96);
      if (DROW_PF) { prefetch_l2(drows + lane * 64); prefetch_l2(drows + 2048 + lane * 64); }
#pragma unroll 1
      for (int r2 = 0; r2 < 2; r2++) {
        float v8[8];
        mbar_wait(bar0 + r2 * 8, 0);
        if (lane == 0) TIM(140 + r2 * 4 + a);
#pragma unroll
        for (int r = 0; r < 2; r++) {
          float s0 = 0.f, s1 = 0.f, q0 = 0.f, q1 = 0.f;
          uint32_t zr = 0, zi = 0;
#pragma unroll
          for (int q = 0; q < 4; q++) {
            const uint4 v = lds128(buf + r2 * 4096 + r * 2048 + (q * 32 + lane) * 16);
            const uint32_t ww[4] = {v.x, v.y, v.z, v.w};
#pragma unroll
            for (int z = 0; z < 4; z++) {
              const float lo = bf_lo(ww[z]), hi = bf_hi(ww[z]);
              s0 += lo; s1 += hi; q0 = fmaf(lo, lo, q0); q1 = fmaf(hi, hi, q1);
            }
            zr = bfma2(v.x, u[2 * q].x, zr); zi = bfma2(v.x, u[2 * q].y, zi); zr = bfma2(v.y, u[2 * q].z, zr); zi = bfma2(v.y, u[2 * q].w, zi);
            zr = bfma2(v.z, u[2 * q + 1].x, zr); zi = bfma2(v.z, u[2 * q + 1].y, zi); zr = bfma2(v.w, u[2 * q + 1].z, zr); zi = bfma2(v.w, u[2 * q + 1].w, zi);
          }
          v8[4 * r] = s0 + s1; v8[4 * r + 1] = q0 + q1; v8[4 * r + 2] = bf_lo(zr) + bf_hi(zr); v8[4 * r + 3] = bf_lo(zi) + bf_hi(zi);
        }
        fold<8>(v8, 16, lane);
        if (lane == 0) { mbar_expect_tx(bar0 + r2 * 8, 4096); bulk_load(buf + r2 * 4096, drows + r2 * 2048, 4096, bar0 + r2 * 8); }
        fold<4>(v8, 8, lane); fold<2>(v8, 4, lane);
        v8[0] += __shfl_xor_sync(0xffffffffu, v8[0], 2);
        v8[0] += __shfl_xor_sync(0xffffffffu, v8[0], 1);
        SM<float>(OFF_REM + a * 64 + r2 * 32 + (lane >> 2) * 4) = v8[0];
        if (lane == 0) TIM(148 + r2 * 4 + a);
      }
    }
    bar_sync(NB_AUX, 128);
    fresh_ids();
    if (a == 0 && lane < 16) {
      const float4 v = SM<float4>(OFF_REM + lane * 16);
      const float mean = v.x * (1.f / 1024.f), rs = fast_rcp(ref_sd(fmaxf(v.y * (1.f / 1024.f) - mean * mean, 0.f)));
      pkt_st128(&p.sc->xz[cid * 16 + lane], __float_as_uint(bf16r(mean)) | (tag & 0xFFFFu), __float_as_uint(rs), pack_bf16(v.z * rs, v.w * rs), tag);
    }
    if (j == 32) { const float4 v = SM<float4>(INFO_DS); SM<float2>(INFO_WSUM) = make_float2((v.x + v.y) + (v.z + v.w), __uint_as_float(tag)); }
    if (j == 0) TIM(98);
#pragma unroll 1
    for (int r2 = 0; r2 < 2; r2++) {
      mbar_wait(bar0 + r2 * 8, 1);
      uint4 dv[8];
#pragma unroll
      for (int q = 0; q < 8; q++) dv[q] = lds128(buf + r2 * 4096 + (lane >> 4) * 2048 + q * 256 + (lane & 15) * 16);
      float s0 = __uint_as_float(zero_here()), s1 = 0.f;
#pragma unroll
      for (int q = 0; q < 8; q++) {
        const uint4 v = dv[q];
        s0 += (bf_lo(v.x) + bf_lo(v.y)) + (bf_lo(v.z) + bf_lo(v.w)); s1 += (bf_hi(v.x) + bf_hi(v.y)) + (bf_hi(v.z) + bf_hi(v.w));
      }
      s0 += s1;
#pragma unroll
      for (int o = 8; o > 0; o >>= 1) s0 += __shfl_xor_sync(0xffffffffu, s0, o);
      SM<float>(INFO_DS2 + (a * 4 + r2 * 2 + (lane >> 4)) * 4) = s0;
    }
    bar_sync(NB_AUX, 128);
    if (a == 1 && lane < 16) pkt_st64(&p.sc->dsum[cid * 16 + lane], SM<uint32_t>(INFO_DS2 + lane * 4), tag);
    if (j == 0) TIM(99);
    uint4* cpart = &p.sc->cpart[grp * 512 + eps * 64];
    pkt_clear128(cpart + (a * 8192 + lane)); pkt_clear128(cpart + (a * 8192 + lane) + 32);
    if (a == 3) { pkt_st64(&p.sc->ch[(lane >> 2) * 512 + cid * 4 + (lane & 3)], 0, 0); if (lane < 8) pkt_clear128(&p.sc->cs[cid * 8 + lane]); }
    {
      wait_clk(clk32(), XS_DELAY);
      uint2 v0, v1, cs; uint32_t n = 0;
      const uint32_t t16 = tag & 0xFFFFu;
      bool more;
#pragma unroll 1
      do {
        v0 = pkt_ld64(&p.sc->xz[tau * 256 + j]); v1 = pkt_ld64(&p.sc->xz[tau * 256 + j] + 128); cs = pkt_ld64(&p.sc->dsum[m * 1024 + eps * 128 + j]);
        more = !(__all_sync(0xffffffffu, (v0.x & 0xFFFFu) == t16 && (v1.x & 0xFFFFu) == t16 && cs.y == tag)) && ++n < SPIN_LIMIT;
        if (more) { __nanosleep(200); }
      } while (more);
      const int ro = OFF_RS + ((j & 7) >> 1) * 272 + (j >> 3) * 8 + (j & 1) * 4;
      SM<uint32_t>(ro) = v0.y ^ (m << 31); SM<uint32_t>(ro + 128) = v1.y ^ (m << 31);
      const uint32_t n0 = (v0.x >> 16) ^ 0x8000u, n1 = (v1.x >> 16) ^ 0x8000u;
      SM<uint4>(OFF_EXB + j * 16) = make_uint4(n0 | (n0 << 16), n0, 0, 0);
      SM<uint4>(OFF_EXB + 2048 + j * 16) = make_uint4(n1 | (n1 << 16), n1, 0, 0);
      const float c = 0.5f * __uint_as_float(cs.x), hi = bf16r(c), mid = bf16r(c - hi), lo = bf16r((c - hi) - mid);
      SM<uint4>(OFF_EXA + j * 16) = make_uint4((__float_as_uint(hi) >> 16) | __float_as_uint(mid), __float_as_uint(lo) >> 16, 0, 0);
      fence_async_smem();
      __syncwarp();
      if (lane == 0) mbar_arrive(BAR(B_STAT));
    }
    if (j == 0) TIM(100);
    auto all_published = [&](int half) {
      uint32_t n = 0;
#pragma unroll 1
      while (!__all_sync(0xffffffffu, ld_acquire32(&p.sc->abdone[(cid * 2 + half) * 32 + (lane & 7)]) == tag) && ++n < SPIN_LIMIT) {}
      if (lane == 0) {
        asm volatile("fence.proxy.async.global;" ::: "memory");
        mbar_arrive(BAR(B_ALL + half));
        TIM(80 + half);
      }
      __syncwarp();
    };
    if (TM_PF && j < 3) asm volatile("prefetch.tensormap [%0];" :: "l"(j == 0 ? &p.tmAbS : j == 1 ? &p.tmAbL : m ? &p.tmW1 : &p.tmW0) : "memory");
    {
      if (a == 3) {
        const uint32_t cl = poll64_warp(&p.sc->cl[cid * 16 + (lane & 3)], tag, 100);
        if (lane == 0) TIM(101);
        const bf16* wm = (m ? p.Wim : p.Wre) + tau * 256 + lane * 8;
        uint4 v[8];
#pragma unroll
        for (int i = 0; i < 8; i++) v[i] = ldg128(wm + ((__shfl_sync(0xffffffffu, cl, i >> 1) >> ((i & 1) * 16)) & 2047) * 2048);
        const int pos = cid * 4 + (lane & 3);
        const bf16* xc = p.x + ((__shfl_sync(0xffffffffu, cl, lane >> 3) >> ((lane & 4) * 4)) & 2047) * 1024 + (pos >> 3) * 16 + (pos & 7);
        const float x0 = ldbf(xc), x1 = ldbf(xc + 8), w0 = ldbf(p.wr + (pos >> 3) * 16 + (pos & 7)), w1 = ldbf(p.wr + (pos >> 3) * 16 + (pos & 7) + 8);
        if (lane < 4) SM<uint32_t>(INFO_CAND + lane * 4) = cl;
#pragma unroll
        for (int i = 0; i < 8; i++) SM<uint4>(OFF_WC + (lane >> 3) * 1024 + i * 128 + (((lane & 7) ^ i) << 4)) = v[i];
        fence_async_smem();
        __syncwarp();
        if (lane == 0) { mbar_arrive(BAR(B_WC)); TIM(102); }
        mbar_wait(BAR(B_CD), 0);
        wait_clk(clk32(), CP_DELAY);
        uint32_t n = 0;
        bool more;
#pragma unroll 1
        do {
          uint32_t bad = 0;
#pragma unroll
          for (int i = 0; i < 8; i++) v[i] = pkt_ld128(&p.sc->cpart[((lane >> 3) * 16 + ((lane >> 2) & 1)) * 512 + pos] + i * 1024);
#pragma unroll
          for (int i = 0; i < 8; i++) chk_code(bad, v[i], c0, c1);
          more = !(!__any_sync(0xffffffffu, bad & 1)) && ++n < SPIN_LIMIT;
          if (more) { __nanosleep(200); }
        } while (more);
        float y[4] = {0.f, 0.f, 0.f, 0.f};
#pragma unroll
        for (int i = 0; i < 8; i++) { y[0] += no_bit(v[i].x); y[2] += no_bit(v[i].y); y[1] += no_bit(v[i].z); y[3] += no_bit(v[i].w); }
#pragma unroll
        for (int i = 0; i < 4; i++) y[i] = bf16r(y[i]);
        __syncwarp();
        fold<4>(y, 4, lane);
        const uint32_t hp = pack_bf16(x0 + bf16r(y[0]), x1 + bf16r(y[1]));
        pkt_st64(&p.sc->ch[(lane >> 2) * 512 + pos], hp, tag);
        float st[3] = {bf_lo(hp) + bf_hi(hp), bf_lo(hp) * bf_lo(hp) + bf_hi(hp) * bf_hi(hp), bf_lo(hp) * w0 + bf_hi(hp) * w1};
#pragma unroll
        for (int o = 1; o < 4; o <<= 1) {
#pragma unroll
          for (int i = 0; i < 3; i++) st[i] += __shfl_xor_sync(0xffffffffu, st[i], o);
        }
        if ((lane & 3) == 0) pkt_st128(&p.sc->cs[cid * 8 + (lane >> 2)], with_bit(st[0], c0), with_bit(st[1], c1), __float_as_uint(st[2]), tag);
        if (lane == 0) TIM(119);
      }
      if (a < 2) {
        uint32_t* fl = a == 0 && lane < 2 ? &p.sc->abflag[(cid * 2 + lane) * 32] : &p.sc->abdone[(((cid & 15) + (lane & 7) * 16) * 2 + a) * 32 + tau];
        if (lane == 0) {
          if (a == 1) mbar_wait(BAR(B_SD), 0);
          const uint32_t t1 = clk32();
#pragma unroll 1
          for (int i = 2 * a; i < 2 + 6 * a; i++) {
            const int w = i & 1, c = i >> 1;
            if (a == 1) wait_clk(t1, HI_DELAY + (i - 2) * HI_PACE);
            mbar_wait(BAR(B_EP + w * 4 + c), 0);
            TIM(64 + i);
            fence_async_smem();
            tma_store_2d(&p.tmAbS, sb + c * ST_BYTES + w * 8192, tau * 256 + c * 64, abrow + w * 64);
            if (w) { bulk_commit(); bulk_wait_all(); mbar_arrive(BAR(B_SD + c)); }
          }
          TIM(72 + a * 2);
          asm volatile("fence.proxy.async.global;" ::: "memory");
          asm volatile("st.release.gpu.global.b32 [%0], %1;" :: "l"(fl), "r"(tag) : "memory");
          TIM(73 + a * 2);
        }
        __syncwarp();
        if (lane == 1 || (lane >> 3) == 1) st_relaxed32(fl, tag);
        __nanosleep(ALL_NS);
        all_published(a);
        if (DELEG && a == 1 && elect_one()) {
#pragma unroll 1
          for (int i = 0; i < 2; i++) {
            mbar_wait(BAR(i ? B_E24 : B_E23), 0);
            tma_load_2d(sb + (3 - 3 * i) * ST_BYTES, &p.tmAbL, BAR(B_FULL + 3 - 3 * i), (tau * 256 + 320 + i * 64) & 2047, abrow);
          }
        }
      } else if (a == 2) {
        const uint32_t* fl = &p.sc->abflag[(((cid + 16 + 16 * (lane & 1)) & 127) * 2 + (lane & 1)) * 32];
        mbar_wait(BAR(B_SD), 0);
        __nanosleep(LO_NS);
        uint32_t n = 0, seen = 0;
#pragma unroll 1
        for (int c = 0; c < 4; c++) {
#pragma unroll 1
          while (c < 2 && !((seen >> c) & 1) && ++n < SPIN_LIMIT) seen = __ballot_sync(0xffffffffu, ld_acquire32(fl) == tag);
          if (elect_one()) {
            mbar_wait(BAR(B_SD + c), 0); mbar_wait(BAR(c < 3 ? B_FULL + c : B_EMPTY), 0);
            if (c == 2) mbar_wait(BAR(B_ALL), 0);
            asm volatile("fence.proxy.async.global;" ::: "memory");
            tma_load_2d(sb + c * ST_BYTES, &p.tmAbL, BAR(B_FULL + c), k_col(tau, 4 + c), abrow);
            TIM(130 + c);
          }
          __syncwarp();
        }
      }
      __syncwarp();
    }
    mbar_wait(BAR(B_CD), 0);
    const uint64_t pol_ef = policy_evict_first();
    auto load_unit = [&](int v) {
      if (elect_one()) {
        const uint32_t dst = buf + (v & 1) * 4096, bar = bar0 + (v & 1) * 8;
        mbar_expect_tx(bar, 4096);
        if (v < 8) {
          LOAD_F(dst, &p.tmG, bar, fc, m * 512 + (a * 8 + v) * 16);
          LOAD_F(dst + 2048, &p.tmU, bar, fc, m * 512 + (a * 8 + v) * 16);
        } else LOAD_F(dst, &p.tmDn, bar, a * 256, src * 32 + (v - 8) * 8);
      }
    };
    if (TM_PF && j < 3) asm volatile("prefetch.tensormap [%0];" :: "l"(j == 0 ? &p.tmG : j == 1 ? &p.tmU : &p.tmDn) : "memory");
    if (ffn && (!LU0_LATE || a == 1)) load_unit(0);
    if (a != 1) {
      bar_sync(NB_SEL, 96);
      wait_clk(clk32(), CS_DELAY);
      fresh_ids();
      if (a == 0 && lane < 8) {
        if (lane == 0) mbar_expect_tx(BAR(B_CH), 16384);
        bulk_load(sb + OFF_AUX + 4096 + (lane >> 1) * 8192 + (lane & 1) * 2048, &p.sc->ch[lane * 512 + m * 256], 2048, BAR(B_CH));
      }
      const int j3 = a ? j - 32 : j;
      uint4 v[11]; uint32_t n = 0;
      bool more;
#pragma unroll 1
      do {
#pragma unroll
        for (int i = 0; i < 11; i++) v[i] = pkt_ld128(&p.sc->cs[j3] + (i < 10 || a < 3 ? i * 96 : 0));
        uint32_t bad = 0;
#pragma unroll
        for (int i = 0; i < 11; i++) { chk(bad, v[i].x, c0); chk(bad, v[i].y, c1); }
        bad &= 1;
#pragma unroll
        for (int i = 0; i < 11; i++) chk(bad, v[i].w, tag);
        more = __any_sync(0xffffffffu, bad) && ++n < SPIN_LIMIT;
        if (more) __nanosleep(200);
      } while (more);
      if (j == 0) TIM(97);
      if (ffn && LU0_LATE) load_unit(0);
      float st[3] = {0.f, 0.f, 0.f};
      if (a < 3) { st[0] = no_bit(v[10].x); st[1] = no_bit(v[10].y); st[2] = __uint_as_float(v[10].z); }
#pragma unroll
      for (int i = 0; i < 10; i++) { st[0] += no_bit(v[i].x); st[1] += no_bit(v[i].y); st[2] += __uint_as_float(v[i].z); }
#pragma unroll
      for (int o = 8; o < 32; o <<= 1) {
#pragma unroll
        for (int i = 0; i < 3; i++) st[i] += __shfl_xor_sync(0xffffffffu, st[i], o);
      }
      if (lane < 8) SM<float4>(OFF_XS + ((j3 >> 5) * 8 + lane) * 16) = make_float4(st[0], st[1], st[2], 0.f);
      bar_sync(NB_SEL, 96);
      const float4 f0 = SM<float4>(OFF_XS + (lane & 7) * 16), f1 = SM<float4>(OFF_XS + 128 + (lane & 7) * 16), f2 = SM<float4>(OFF_XS + 256 + (lane & 7) * 16);
      const float mu = ((f0.x + f1.x) + f2.x) * (1.f / 1024.f);
      float mb = bf16r(mu), inv = fast_rcp(ref_sd(fmaxf(((f0.y + f1.y) + f2.y) * (1.f / 1024.f) - mu * mu, 0.f)));
      const uint32_t kk = make_key(bf16r((((f0.z + f1.z) + f2.z) - mb * SM<float>(INFO_WSUM)) * inv), SM<uint16_t>(INFO_CAND + (lane & 7) * 2));
      const uint32_t key = __reduce_max_sync(0xffffffffu, kk);
      const int win = __ffs(__ballot_sync(0xffffffffu, kk == key)) - 1;
      mb = __shfl_sync(0xffffffffu, mb, win); inv = __shfl_sync(0xffffffffu, inv, win);
      if (j == 0) { SM<uint2>(INFO_KEY) = make_uint2(key, win); SM<float2>(INFO_LN) = make_float2(mb, inv); }
      mbar_wait(BAR(B_CH), 0);
      bar_sync(NB_SEL, 96);
#pragma unroll 1
      for (int i = j3; i < 128; i += 96) {
        uint4 r = lds128(sb + OFF_AUX + 4096 + (win >> 1) * 8192 + (win & 1) * 2048 + i * 16);
#pragma unroll 1
        while ((r.y != tag || r.w != tag) && ++n < SPIN_LIMIT) r = pkt_ld128(&p.sc->ch[win * 512 + m * 256 + 2 * i]);
        auto ln = [&](float h) { return bf16r(bf16r(h - mb) * inv); };
        const int d = (i >> 2) * 16 + (i & 3) * 2;
        SM<float2>(OFF_XS + d * 4) = make_float2(ln(bf_lo(r.x)), ln(bf_lo(r.z)));
        SM<float2>(OFF_XS + (d + 8) * 4) = make_float2(ln(bf_hi(r.x)), ln(bf_hi(r.z)));
      }
      __syncwarp();
    }
    bar_sync(NB_AUX, 128);
    if (j == 0) {
      mbar_arrive(BAR(B_INFO)); TIM(103);
      if (cid == 0) st_relaxed32(&p.sc->epoch, tag);
    }
    const uint32_t t2 = clk32();
    fresh_ids();
    if (!ffn) {
      wait_clk(t2, YPART_DELAY);
    } else {
      load_unit(1);
      const int r = lane >> 3;
      float acc[8] = {0.f, 0.f, 0.f, 0.f, 0.f, 0.f, 0.f, 0.f};
#pragma unroll 1
      for (int v = 0; v < 8; v++) {
        const uint4 x0 = lds128(sb + OFF_XS + ((a * 8 + v) * 16 + (r & 1) * 8) * 4), x1 = lds128(sb + OFF_XS + ((a * 8 + v) * 16 + (r & 1) * 8 + 4) * 4);
        const float xv[8] = {__uint_as_float(x0.x), __uint_as_float(x0.y), __uint_as_float(x0.z), __uint_as_float(x0.w), __uint_as_float(x1.x), __uint_as_float(x1.y), __uint_as_float(x1.z), __uint_as_float(x1.w)};
        mbar_wait(bar0 + (v & 1) * 8, (v >> 1) & 1);
        gemv8x8<128>(acc, buf + (v & 1) * 4096 + r * 1024 + (lane & 7) * 16, xv);
        fence_regs(acc);
        __syncwarp();
        wait_clk(t2, v * UNIT_PACE);
        load_unit(v + 2);
        if (j == 0) TIM(104 + v);
      }
      pkt_clear128(&p.sc->ypart[(a * NSRC + src) * 64 + lane * 2]); pkt_clear128(&p.sc->ypart[(a * NSRC + src) * 64 + lane * 2] + 1);
      fold<8>(acc, 8, lane);
      bar_sync(NB_AUX, 128);
      SM<float4>(OFF_XS + (a * 128 + (r >> 1) * 64 + (lane & 7) * 8 + (r & 1) * 4) * 4) = make_float4(acc[0], acc[1], acc[2], acc[3]);
      bar_sync(NB_AUX, 128);
      auto psum = [&](int i) { return (SM<float>(OFF_XS + i * 4) + SM<float>(OFF_XS + (128 + i) * 4)) + (SM<float>(OFF_XS + (256 + i) * 4) + SM<float>(OFF_XS + (384 + i) * 4)); };
      if (a < 2) st_async_b32(mapa(sb + OFF_REM + j * 4, m ^ 1), mapa(BAR(B_GUX), m ^ 1), __float_as_uint(psum(a * 64 + (m ^ 1) * 32 + lane)));
      const float og = psum(m * 32 + lane), ou = psum(64 + m * 32 + lane);
      mbar_wait(BAR(B_GUX), 0);
      const float rg = SM<float>(OFF_REM + lane * 4), ru = SM<float>(OFF_REM + 128 + lane * 4);
      const float act = swiglu(m ? rg + og : og + rg, m ? ru + ou : ou + ru);
      if (j == 0) TIM(112);
      float y[8] = {0.f, 0.f, 0.f, 0.f, 0.f, 0.f, 0.f, 0.f};
#pragma unroll 1
      for (int v = 8; v < 12; v++) {
        float av[8];
#pragma unroll
        for (int i = 0; i < 8; i++) av[i] = __shfl_sync(0xffffffffu, act, (v - 8) * 8 + i);
        mbar_wait(bar0 + (v & 1) * 8, (v >> 1) & 1);
        gemv8x8<512>(y, buf + (v & 1) * 4096 + lane * 16, av);
        fence_regs(y);
        __syncwarp();
        if (v < 10) load_unit(v + 2);
        if (j == 0) TIM(105 + v);
      }
      fresh_ids();
      uint4* ypart = &p.sc->ypart[(a * NSRC + src) * 64 + lane * 2];
      pkt_st128(ypart, with_bit(y[0], c0), with_bit(y[1], c1), with_bit(y[2], c0), with_bit(y[3], c1));
      pkt_st128(ypart + 1, with_bit(y[4], c0), with_bit(y[5], c1), with_bit(y[6], c0), with_bit(y[7], c1));
      if (lane == 0) TIM(160 + a);
      __nanosleep(ROW_NS);
    }
    if (a == 3) {
      const uint32_t hh = poll64_warp(&p.sc->ch[SM<uint32_t>(INFO_KEY + 4) * 512 + (cid >> 1) * 8 + (lane & 7)], tag, 100);
      uint4 v[7]; uint32_t n = 0;
      bool more;
#pragma unroll 1
      do {
        if (elect_one()) { mbar_expect_tx(bar0, NSRC * 32); tma_load_2d(buf, &p.tmY, bar0, (cid & 31) * 16, (cid >> 5) * NSRC); }
        mbar_wait(bar0, n & 1);
        uint32_t bad = 0;
#pragma unroll
        for (int i = 0; i < 7; i++) { v[i] = lds128(buf + i * 512 + lane * 16); chk_code(bad, v[i], c0, c1); }
        more = __any_sync(0xffffffffu, bad & 1) && ++n < SPIN_LIMIT;
        if (more) __nanosleep(300);
      } while (more);
      if (lane == 0) TIM(164);
      float y[4] = {0.f, 0.f, 0.f, 0.f};
#pragma unroll
      for (int i = 0; i < 7; i++) { y[0] += no_bit(v[i].x); y[1] += no_bit(v[i].y); y[2] += no_bit(v[i].z); y[3] += no_bit(v[i].w); }
      fold<4>(y, 16, lane); fold<2>(y, 8, lane);
      y[0] += __shfl_xor_sync(0xffffffffu, y[0], 4);
      y[0] += __shfl_xor_sync(0xffffffffu, y[0], 2);
      const float ys = __shfl_sync(0xffffffffu, y[0], (lane & 3) * 8 + ((lane >> 2) & 1));
      const float h = m ? bf_hi(hh) : bf_lo(hh), hn = bf16r(bf16r(h - SM<float>(INFO_LN)) * SM<float>(INFO_LN + 4));
      const uint32_t key = SM<uint32_t>(INFO_KEY);
      if (lane < 8) st_bf16(p.out + key_row(key) * 1024 + cid * 8 + lane, routed_out(h, hn, ys, key_val(key)));
      if (lane == 0) TIM(118);
      __threadfence();
      __syncwarp();
      if (lane == 0) { pkt_st64(&p.sc->rdone[cid], 0, tag); TIM(117); }
    }
  } else {
    reg_inc<216>();
    cluster_wait();
    const uint32_t sb = __shfl_sync(0xffffffffu, smem_u32(smem_raw), 0);
    auto BAR = [&](int i) { return sb + OFF_BAR + 8 * i; };
    const int w = warp >> 2, wi = warp & 3, t = tid & 127;
    const int turn_me = NB_TURN0 + w, turn_other = NB_TURN1 - w;
    const uint64_t dA0 = make_desc(sb + w * 8192);
    uint64_t dA, dB;
    int tau, eps, m, grp, abrow, fc, src;
    bool ffn;
    const CUtensorMap* tmD; const CUtensorMap* tmW;
    auto new_desc = [&](int salt) {
      const uint32_t z = salt < 0 ? uniform_zero_here() : salt & blockIdx.y;
      dA = dA0 + z; dB = dA0 + (z + ((A_BYTES - w * 8192) >> 4));
      const int c = cid + z;
      tau = c >> 4; eps = (c >> 1) & 7; m = c & 1; grp = tau * 2 + m; abrow = m * 1024 + eps * 128;
      ffn = eps > 0; fc = (tau * 7 + eps - 1) * 64; src = (fc >> 5) + m;
      tmD = &p.tmD0 + m; tmW = &p.tmW0 + m;
    };
    constexpr int SL = ST_BYTES >> 4;
    float acc[128];
#pragma unroll
    for (int i = 0; i < 128; i++) acc[i] = 0.f;
    if (w == 1) bar_arrive(NB_TURN0, 256);
    auto full = [&](int k) { mbar_wait(BAR(B_FULL + (k & 3)), (k >> 2) & 1); CT(64 + k); };
    const uint64_t pol_ef = policy_evict_first();
    auto refill_g2 = [&](int k, int mode) {
      if (warp == 4) {
        if (elect_one()) {
          const int s = k & 3, s0 = k_col(tau, k - 12);
          TIM(k + 4);
          mbar_expect_tx(BAR(B_FULL + s), mode ? ST_BYTES : B_BYTES);
          if (k == 19) mbar_arrive(BAR(B_EMPTY));
          LOAD_W(sb + s * ST_BYTES + A_BYTES, tmW, BAR(B_FULL + s), s0, grp * 128);
          LOAD_W(sb + s * ST_BYTES + A_BYTES + 16384, tmW, BAR(B_FULL + s), s0, (grp ^ 1) * 128);
          if (mode == 2) tma_load_2d(sb + s * ST_BYTES, &p.tmAbL, BAR(B_FULL + s), s0, abrow);
        }
        __syncwarp();
      }
    };
    auto mma_ss = [&](int k) {
#pragma unroll
      for (int kk = 0; kk < 4; kk++) wgmma_n256(acc, dA + (k & 3) * SL + kk * 2, dB + (k & 3) * SL + kk * 2);
    };
    const CUtensorMap* rf_tm; uint32_t rf_dst; int rf_row, rf_c; bool rf_on;
    auto refill = [&](int s) {
      if (rf_on) {
        if (elect_one()) tma_load_2d(rf_dst + s * ST_BYTES, rf_tm, BAR(B_FULL + s), rf_c, rf_row);
        __syncwarp();
      }
      if (tid == 224) mbar_expect_tx(BAR(B_FULL + s), ST_BYTES);
    };
    const bf16* pf; int pf_step; bool pf_on;
    auto pf_ffn = [&](int v) {
      pf_on = ffn && v >= 0 && v < 12;
      pf = v < 8 ? ((lane & 16) ? p.wup : p.wgate) + (m * 512 + (wi * 8 + v) * 16 + (lane & 15)) * 3584 + fc : p.wdown + (src * 32 + (v - 8) * 8) * 1024 + t * 64;
      pf_step = v < 8 ? 16 * 3584 : 8192;
    };
    auto prefetch = [&](int s) { if (pf_on && (wi >> 1) == (s & 1)) prefetch_l2(pf + (s >> 1) * pf_step); };
    auto kstep = [&](int k) {
      full(k);
      bar_sync(turn_me, 256);
      wgmma_fence();
      mma_ss(k);
      wgmma_commit();
      bar_arrive(turn_other, 256);
    };

    new_desc(64);
    rf_on = (warp >> 1) == 2;
    rf_tm = wi ? tmD : &p.tmX; rf_dst = wi ? sb : sb + A_BYTES; rf_row = wi ? eps * 128 : tau * 256;
#pragma unroll 1
    for (int k4 = 0; k4 < 12; k4 += 4) {
#pragma unroll
      for (int s = 0; s < 4; s++) {
        kstep(k4 | s);
        if (s == 0) {
          if (w == 0) pf_ffn((k4 >> 1) - 2);
          else {
            pf_on = W_PF && (k4 == 8 || (W_PF > 1 && k4 == 4 && (lane & 7) < 3));
            pf = (m ? p.Wim : p.Wre) + (tau * 256 + eps * 32 + wi * 4 + (lane >> 3)) * 2048 + k_col(tau, (lane & 7) + (W_PF > 1 && k4 == 8 ? 3 : 0));
            pf_step = 16 * 2048;
          }
        }
        rf_c = (k4 + s + 4) * 64;
        prefetch(s);
        if (s == 3) new_desc(k4);
        if (s == 0 || s == 3) pf += zero_here();
        wgmma_wait<0>();
        refill(s);
      }
    }
    uint32_t R[64];
    auto load_rs = [&](auto gi) {
      const uint32_t rsa = sb + OFF_RS + (lane & 3) * 272;
#pragma unroll
      for (int i = 4 * decltype(gi)::value; i < 4 * decltype(gi)::value + 4; i++) { const uint4 v = lds128(rsa + i * 16); R[4 * i] = v.x; R[4 * i + 1] = v.y; R[4 * i + 2] = v.z; R[4 * i + 3] = v.w; }
    };
    kstep(12);
    mbar_wait(BAR(B_STAT), 0);
    CT(1);
    load_rs(std::integral_constant<int, 0>());
    load_rs(std::integral_constant<int, 1>());
    wgmma_wait<0>(); refill_g2(12, 0);
    load_rs(std::integral_constant<int, 3>());
    auto mma_h = [&](float (&d)[64], int s, int half) {
#pragma unroll
      for (int kk = 0; kk < 4; kk++) wgmma_n128(d, dA + s * SL + kk * 2, dB + s * SL + half * 1024 + kk * 2);
    };
    const int rho = 16 * wi + (lane & 15);
    const uint32_t arow = sb + w * 8192 + rho * 128;
    auto convert = [&](auto cc, float (&d)[64]) {
      const float z = __uint_as_float(zero_here());
#pragma unroll
      for (int jj = 8 * decltype(cc)::value; jj < 8 * decltype(cc)::value + 8; jj++) {
        const float r0 = __uint_as_float(R[2 * jj]), r1 = __uint_as_float(R[2 * jj + 1]);
        const float* ac = &d[4 * (jj & 15)];
        R[2 * jj] = pack_bf16(fmaf(ac[0], r0, z), fmaf(ac[1], r1, z));
        R[2 * jj + 1] = pack_bf16(fmaf(ac[2], r0, z), fmaf(ac[3], r1, z));
      }
    };
    auto put = [&](auto cc) {
      constexpr int c = decltype(cc)::value;
#pragma unroll
      for (int jj = 8 * c; jj < 8 * c + 8; jj += 2)
        stsm_x4(arow + c * ST_BYTES + ((((jj & 7) + (lane >> 4)) ^ (rho & 7)) << 4), R[2 * jj], R[2 * jj + 1], R[2 * jj + 2], R[2 * jj + 3]);
      __syncwarp();
      if (lane == 0) mbar_arrive(BAR(B_EP + w * 4 + c));
    };
    {
      float lo[64], hi[64];
      fence_regs(acc);
#pragma unroll
      for (int i = 0; i < 64; i++) asm volatile("mov.b32 %0, %1;" : "=f"(lo[i]) : "f"(acc[i]));
#pragma unroll
      for (int i = 0; i < 64; i++) asm volatile("mov.b32 %0, %1;" : "=f"(hi[i]) : "f"(acc[64 + i]));
      const uint64_t dEA = make_desc_noswz(sb + OFF_EXA + w * 1024), dEB = make_desc_noswz(sb + OFF_EXB);
      full(13); full(14);
      bar_sync(turn_me, 256);
      wgmma_fence();
      mma_h(lo, 1, 0); mma_h(lo, 2, 0);
      wgmma_commit();
      bar_arrive(turn_other, 256);
      new_desc(ND1);
      full(15);
      bar_sync(turn_me, 256);
      wgmma_fence();
      mma_h(lo, 3, 0);
      wgmma_n128(lo, dEA, dEB);
      wgmma_commit();
      mma_h(hi, 1, 1);
      wgmma_commit();
      bar_arrive(turn_other, 256);
      new_desc(ND2);
      wgmma_wait<1>();
      fence_regs(lo);
      CT(15);
      convert(std::integral_constant<int, 0>(), lo); put(std::integral_constant<int, 0>());
      convert(std::integral_constant<int, 1>(), lo);
      wgmma_wait<0>(); refill_g2(13, 0);
      if (!PUT1_LATE) put(std::integral_constant<int, 1>());
      bar_sync(turn_me, 256);
      wgmma_fence();
      mma_h(hi, 2, 1);
      wgmma_commit();
      mma_h(hi, 3, 1);
      wgmma_n128(hi, dEA, dEB + 128);
      wgmma_commit();
      bar_arrive(turn_other, 256);
      load_rs(std::integral_constant<int, 2>());
      if (PUT1_LATE) put(std::integral_constant<int, 1>());
      wgmma_wait<1>(); refill_g2(14, 0);
      wgmma_wait<0>(); refill_g2(15, 0);
      fence_regs(hi);
      CT(2);
      convert(std::integral_constant<int, 3>(), hi);
      if (!PUT3_LATE) put(std::integral_constant<int, 3>());
      convert(std::integral_constant<int, 2>(), hi);
    }
    CT(3);
    float cc[4];
    auto cand_mma = [&]() {
      const uint64_t dC = make_desc(sb + OFF_WC);
      wgmma_n8_rs<0>(cc, R, dC);
#pragma unroll
      for (int i = 1; i < 12; i++) wgmma_n8_rs<1>(cc, R + 4 * i, dC + (i >> 2) * 64 + (i & 3) * 2);
#pragma unroll
      for (int kk = 0; kk < 4; kk++) wgmma_n8(cc, dA + 3 * SL + kk * 2, dC + 192 + kk * 2);
      wgmma_commit();
    };
    auto cand_pub = [&]() {
      fence_regs(cc);
      const uint32_t cd = code_of(SM<uint32_t>(INFO_TAG));
      if (t == 0) mbar_arrive(BAR(B_CD));
      pkt_st128(&p.sc->cpart[((lane & 3) * 16 + grp) * 512 + eps * 64 + warp * 8 + (lane >> 2)], with_bit(cc[0], cd), with_bit(cc[1], cd >> 1), with_bit(cc[2], cd), with_bit(cc[3], cd >> 1));
      CT(5);
    };
    new_desc(ND3);
    if (CAND_EARLY) { fence_async_smem(); mbar_wait(BAR(B_WC), 0); CT(4); }
    full(16);
    if (!SPLIT17) full(17);
    bar_sync(turn_me, 256);
    wgmma_fence();
    if (CAND_EARLY) cand_mma();
    wgmma_n256_rs_init(acc, R, dB);
#pragma unroll
    for (int kk = 1; kk < 4; kk++) wgmma_n256_rs<1>(acc, R + 4 * kk, dB + kk * 2);
    wgmma_commit();
    if (PUT3_LATE) put(std::integral_constant<int, 3>());
    if (SPLIT17) { full(17); wgmma_fence(); }
#pragma unroll
    for (int kk = 0; kk < 4; kk++) wgmma_n256_rs<1>(acc, R + 16 + 4 * kk, dB + SL + kk * 2);
    wgmma_commit();
    bar_arrive(turn_other, 256);
    if (CAND_EARLY) { wgmma_wait<2>(); put(std::integral_constant<int, 2>()); cand_pub(); }
    else put(std::integral_constant<int, 2>());
    wgmma_wait<1>(); refill_g2(16, 1);
    wgmma_wait<0>(); refill_g2(17, 1);
    if (!CAND_EARLY) { fence_async_smem(); mbar_wait(BAR(B_WC), 0); CT(4); }
    full(18);
    bar_sync(turn_me, 256);
    wgmma_fence();
    if (!CAND_EARLY) cand_mma();
#pragma unroll
    for (int kk = 0; kk < 4; kk++) wgmma_n256_rs<1>(acc, R + 32 + 4 * kk, dB + 2 * SL + kk * 2);
    wgmma_commit();
    bar_arrive(turn_other, 256);
    if (!CAND_EARLY) { wgmma_wait<1>(); cand_pub(); }
    wgmma_wait<0>(); refill_g2(18, 1);
    kstep(19);
    new_desc(68);
    wgmma_wait<0>(); refill_g2(19, 1);
    const int g = lane >> 2, q = lane & 3;
    uint4 ha[4], hb[4];

    rf_on = w == 1 && wi < 3;
    rf_tm = wi == 2 ? &p.tmAbL : tmW; rf_dst = wi == 2 ? sb : sb + A_BYTES + wi * 16384; rf_row = wi == 2 ? abrow : (grp ^ wi) * 128;
    rf_c = k_col(tau, 7);
#pragma unroll 1
    for (int k4 = 20; k4 < 44; k4 += 4) {
#pragma unroll
      for (int s = 0; s < 4; s++) {
        kstep(k4 | s);
        if (s == 0) {
          if (w == 0) { pf_ffn((k4 >> 1) - PF2_K / 2 + 4); pf_on = pf_on && k4 >= PF2_K; }
          else {
            pf_on = k4 == XPF_K;
            pf = p.x + (grp * 128 + (t >> 1)) * 1024 + eps * 128 + (t & 1) * 64;
            pf_step = 64 * 1024;
          }
        }
        rf_c = k_next(rf_c, k4 + s - 12);
        if (s == 0 && k4 == 20 && warp == 6) mbar_wait(BAR(B_ALL), 0);
        if (s == (DELEG ? 1 : 3) && k4 == (DELEG ? 24 : 20) && warp == 6) mbar_wait(BAR(B_ALL + 1), 0);
        prefetch(s);
        if (s == 3) new_desc(k4);
        if (s == 0 || s == 3) pf += zero_here();
        wgmma_wait<0>();
        if (DELEG && ((s == 3 && k4 == 20) || (s == 0 && k4 == 24)) && warp == 6) { if (lane == 0) mbar_arrive(BAR(s == 0 ? B_E24 : B_E23)); }
        else refill(s);
      }
    }
    const int row0 = grp * 128 + warp * 16 + g;
    kstep(44);
    uint4* hst = &p.sc->hstat[grp * 1024 + warp * 16 + g];
    if (q == (g >> 1)) { pkt_clear128(hst + eps * 128); pkt_clear128(hst + eps * 128 + 8); }
    mbar_wait(BAR(B_INFO), 0);
    uint4 wv[4];
#pragma unroll
    for (int i = 0; i < 4; i++) wv[i] = lds128(sb + ((g & 1) ? OFF_WR + (i * 4 + q) * 16 : INFO_ONES));
    const uint4 info = lds128(sb + OFF_INFO);
#pragma unroll
    for (int i = 0; i < 4; i++) { ha[i] = ldg128(p.x + (row0 * 1024 + eps * 128 + q * 8) + i * 32); hb[i] = ldg128(p.x + (row0 * 1024 + eps * 128 + q * 8) + 8192 + i * 32); }
    wgmma_wait<0>();
    if (tid == 128) mbar_arrive_remote(mapa(BAR(B_PEER), m ^ 1));
    uint32_t hp[32];
    bf16* op; uint4* hpub;
    uint32_t cd, ast, ald, zr;
    auto swz = [](int row) { return ((row & 1) << 2) | ((row >> 1) & 3); };
    {
      float as[64], ak[64];
      fence_regs(acc);
#pragma unroll
      for (int i = 0; i < 64; i++) asm volatile("mov.b32 %0, %1;" : "=f"(as[i]) : "f"(acc[64 + i]));
#pragma unroll
      for (int i = 0; i < 64; i++) asm volatile("mov.b32 %0, %1;" : "=f"(ak[i]) : "f"(acc[i]));
      full(45); full(46);
      bar_sync(turn_me, 256);
      wgmma_fence();
      mma_h(as, 1, 1); mma_h(as, 2, 1);
      wgmma_commit();
      bar_arrive(turn_other, 256);
      full(47);
      bar_sync(turn_me, 256);
      wgmma_fence();
      mma_h(as, 3, 1);
      wgmma_commit();
      mma_h(ak, 1, 0);
      wgmma_commit();
      bar_arrive(turn_other, 256);
      const uint32_t rx = mapa(sb + OFF_RECV + w * 16384 + t * 16, m ^ 1), rb = mapa(BAR(B_XCH + w), m ^ 1);
      mbar_wait(BAR(B_PEER), 0);
      wgmma_wait<1>();
      fence_regs(as);
      CT(6);
#pragma unroll
      for (int i = 0; i < 8; i++) {
        const float* ac = &as[8 * i];
        st_async_v4(rx + i * 2048, rb, pack_bf16(ac[0], ac[1]), pack_bf16(ac[2], ac[3]), pack_bf16(ac[4], ac[5]), pack_bf16(ac[6], ac[7]));
      }
      CT(7);
      bar_sync(turn_me, 256);
      wgmma_fence();
      mma_h(ak, 2, 0); mma_h(ak, 3, 0);
      wgmma_commit();
      if (w == 0) bar_arrive(turn_other, 256);
      op = p.out + row0 * 1024 + eps * 128 + q * 8;
      hpub = hst + eps * 128; hst += q * 256;
      cd = code_of(info.y);
      ast = sb + w * ST_BYTES + (8 * (lane >> 4) + (lane & 7)) * 128 + (((2 * wi + ((lane >> 3) & 1)) ^ swz(lane & 7)) << 4);
      ald = sb + (warp * 16 + g) * 128 + ((q ^ swz(g)) << 4);
      asm volatile("" : "+l"(op), "+l"(hpub), "+l"(hst), "+r"(cd), "+r"(ast), "+r"(ald));
      zr = zero_here();
#pragma unroll
      for (int i = 0; i < 4; i++) { ha[i].x += zr; hb[i].x += zr; asm volatile("" : "+r"(ha[i].x), "+r"(hb[i].x)); }
      ast += (uint32_t)(clock64() >> 32) & zr;
      mbar_wait(BAR(B_XCH + w), 0);
      CT(9);
#pragma unroll
      for (int i = 0; i < 8; i++) { const uint4 v = lds128(sb + OFF_RECV + w * 16384 + t * 16 + i * 2048); hp[4 * i] = v.x; hp[4 * i + 1] = v.y; hp[4 * i + 2] = v.z; hp[4 * i + 3] = v.w; }
      wgmma_wait<0>();
      fence_regs(ak);
      CT(10);
#pragma unroll
      for (int i = 0; i < 32; i++) hp[i] = badd2(pack_bf16(ak[2 * i], ak[2 * i + 1]), hp[i]);
    }
#pragma unroll
    for (int jj = 0; jj < 16; jj += 2) stsm_x4_t(ast + jj * 1024, hp[2 * jj], hp[2 * jj + 1], hp[2 * jj + 2], hp[2 * jj + 3]);
    tag = info.y;
    bar_sync(NB_BOTH, 256);
    CT(11);
    uint4 v[4];
    auto fetch = [&]() { v[0] = pkt_ld128(hst); v[1] = pkt_ld128(hst + 128); v[2] = pkt_ld128(hst + 8); v[3] = pkt_ld128(hst + 136); };
    float st[6];
    {
      uint4 ya[4], yb[4];
#pragma unroll
      for (int i = 0; i < 4; i++) {
        const uint32_t ad = (ald ^ ((i & 1) << 6)) + (i >> 1) * ST_BYTES;
        ya[i] = lds128(ad); yb[i] = lds128(ad + 1024);
      }
      fetch();
      const float z = __uint_as_float((uint32_t)(clock64() >> 32) & zr);
      float sw[2][4], qa[2][4], qb[2][4];
#pragma unroll
      for (int i = 0; i < 8; i++) { sw[i >> 2][i & 3] = i ? 0.f : z; qa[i >> 2][i & 3] = 0.f; qb[i >> 2][i & 3] = 0.f; }
#pragma unroll
      for (int i = 0; i < 4; i++) {
        ha[i] = make_uint4(badd2(ha[i].x, ya[i].x), badd2(ha[i].y, ya[i].y), badd2(ha[i].z, ya[i].z), badd2(ha[i].w, ya[i].w));
        hb[i] = make_uint4(badd2(hb[i].x, yb[i].x), badd2(hb[i].y, yb[i].y), badd2(hb[i].z, yb[i].z), badd2(hb[i].w, yb[i].w));
        mma16816(sw[0], ha[i].x, hb[i].x, ha[i].y, hb[i].y, wv[i].x, wv[i].y);
        mma16816(qa[0], ha[i].x, hb[i].x, ha[i].y, hb[i].y, ha[i].x, ha[i].y);
        mma16816(qb[0], ha[i].x, hb[i].x, ha[i].y, hb[i].y, hb[i].x, hb[i].y);
        mma16816(sw[1], ha[i].z, hb[i].z, ha[i].w, hb[i].w, wv[i].z, wv[i].w);
        mma16816(qa[1], ha[i].z, hb[i].z, ha[i].w, hb[i].w, ha[i].z, ha[i].w);
        mma16816(qb[1], ha[i].z, hb[i].z, ha[i].w, hb[i].w, hb[i].z, hb[i].w);
      }
      const uint32_t s0 = with_bit(sw[0][0] + sw[1][0], cd), s1 = with_bit((g & 1) ? qa[0][1] + qa[1][1] : qa[0][0] + qa[1][0], cd >> 1), s2 = __float_as_uint(sw[0][1] + sw[1][1]);
      const uint32_t s3 = with_bit(sw[0][2] + sw[1][2], cd), s4 = with_bit((g & 1) ? qb[0][3] + qb[1][3] : qb[0][2] + qb[1][2], cd >> 1), s5 = __float_as_uint(sw[0][3] + sw[1][3]);
      if (q == (g >> 1)) { pkt_st128(hpub, s0, s1, s2, tag); pkt_st128(hpub + 8, s3, s4, s5, tag); }
      CT(12);
      const uint32_t o1 = __shfl_sync(0xffffffffu, s1, (lane & 28) | (g >> 1)), o4 = __shfl_sync(0xffffffffu, s4, (lane & 28) | (g >> 1));
      uint32_t n = 0;
      bool more;
#pragma unroll 1
      do {
        if (2 * q == eps) { v[0] = make_uint4(s0, o1, s2, tag); v[2] = make_uint4(s3, o4, s5, tag); }
        if (2 * q + 1 == eps) { v[1] = make_uint4(s0, o1, s2, tag); v[3] = make_uint4(s3, o4, s5, tag); }
        uint32_t bad = 0;
#pragma unroll
        for (int i = 0; i < 4; i++) { chk(bad, v[i].x, cd); chk(bad, v[i].y, cd >> 1); }
        bad &= 1;
#pragma unroll
        for (int i = 0; i < 4; i++) chk(bad, v[i].w, tag);
        more = !(!__any_sync(0xffffffffu, bad)) && ++n < SPIN_LIMIT;
        if (more) { if (bad) fetch(); }
      } while (more);
      st[0] = no_bit(v[0].x) + no_bit(v[1].x); st[1] = no_bit(v[0].y) + no_bit(v[1].y); st[2] = __uint_as_float(v[0].z) + __uint_as_float(v[1].z);
      st[3] = no_bit(v[2].x) + no_bit(v[3].x); st[4] = no_bit(v[2].y) + no_bit(v[3].y); st[5] = __uint_as_float(v[2].z) + __uint_as_float(v[3].z);
    }
    CT(13);
#pragma unroll
    for (int o = 1; o < 4; o <<= 1) {
#pragma unroll
      for (int i = 0; i < 6; i++) st[i] += __shfl_xor_sync(0xffffffffu, st[i], o);
    }
    float mb[2], inv[2];
#pragma unroll
    for (int i = 0; i < 2; i++) {
      const float mu = st[3 * i] * (1.f / 1024.f);
      mb[i] = bf16r(mu);
      inv[i] = fast_rcp(ref_sd(fmaxf(st[3 * i + 1] * (1.f / 1024.f) - mu * mu, 0.f)));
    }
    {
      const int srow = key_row(info.z);
      auto put_out = [&](bf16* dst, const uint4& h, float sc, float of, bool on) {
        auto cvt = [&](uint32_t x) { return pack_bf16(fmaf(bf_lo(x), sc, of), fmaf(bf_hi(x), sc, of)); };
        asm volatile("{\n.reg .pred p;\nsetp.ne.b32 p, %5, 0;\n@p st.global.v4.b32 [%0], {%1, %2, %3, %4};\n}\n"
                     :: "l"(dst), "r"(cvt(h.x)), "r"(cvt(h.y)), "r"(cvt(h.z)), "r"(cvt(h.w)), "r"((int)on) : "memory");
      };
#pragma unroll
      for (int i = 0; i < 4; i++) {
        put_out(op + i * 32, ha[i], 1.f + inv[0], -mb[0] * inv[0], row0 != srow);
        put_out(op + 8192 + i * 32, hb[i], 1.f + inv[1], -mb[1] * inv[1], row0 + 8 != srow);
      }
    }
    CT(14);
    const uint4 cand = lds128(sb + INFO_CAND);
    uint32_t wkey = zero_here();
#pragma unroll
    for (int i = 0; i < 2; i++) {
      const uint32_t row = row0 + 8 * i, rr = row | (row << 16);
      const bool is_cand = __vcmpeq2(cand.x, rr) | __vcmpeq2(cand.y, rr) | __vcmpeq2(cand.z, rr) | __vcmpeq2(cand.w, rr);
      if (!is_cand) wkey = max(wkey, make_key(bf16r((st[3 * i + 2] - mb[i] * __uint_as_float(info.x)) * inv[i]), row));
    }
    wkey = __reduce_max_sync(0xffffffffu, wkey);
    if (eps == 0 && lane == 0) pkt_st64(&p.sc->key[grp * 8 + warp], wkey, tag);
    const bool beaten = (wkey >> 16) > (info.z >> 16);
    if (__builtin_expect(beaten, 0)) {
      const int br = key_row(wkey);
      if (br == row0 || br == row0 + 8) {
#pragma unroll
        for (int i = 0; i < 4; i++) {
          const uint4 h = br == row0 ? ha[i] : hb[i];
          uint2* dst = &p.sc->hrow[(grp * 8 + warp) * 512 + eps * 64 + i * 16 + q * 4];
          pkt_st128(dst, h.x, tag, h.y, tag); pkt_st128(dst + 2, h.z, tag, h.w, tag);
        }
      }
      __syncwarp();
    }
    uint32_t any;
    asm volatile("{\n.reg .pred p, q;\nsetp.ne.b32 p, %1, 0;\nbarrier.cta.red.or.aligned.pred q, %2, 256, p;\nselp.u32 %0, 1, 0, q;\n}\n" : "=r"(any) : "r"((int)beaten), "n"((int)NB_BOTH) : "memory");
    if (__builtin_expect(any, 0)) slow_path(p, grp, eps, tag, info.z, info.w, SM<float>(INFO_LN), SM<float>(INFO_LN + 4));
  }
}

__global__ void __launch_bounds__(NTHR, 1) occupancy_probe_kernel() {}

typedef CUresult (*EncodeFn)(CUtensorMap*, CUtensorMapDataType, cuuint32_t, void*, const cuuint64_t*, const cuuint64_t*, const cuuint32_t*, const cuuint32_t*,
                             CUtensorMapInterleave, CUtensorMapSwizzle, CUtensorMapL2promotion, CUtensorMapFloatOOBfill);

static void make_tm(EncodeFn enc, CUtensorMap* tm, const void* ptr, uint64_t rows, uint64_t cols, uint32_t brows, uint32_t bcols, bool swz, bool wide) {
  cuuint64_t dims[2] = {cols, rows};
  cuuint64_t strides[1] = {cols * 2};
  cuuint32_t box[2] = {bcols, brows};
  cuuint32_t es[2] = {1, 1};
  enc(tm, CU_TENSOR_MAP_DATA_TYPE_BFLOAT16, 2, const_cast<void*>(ptr), dims, strides, box, es, CU_TENSOR_MAP_INTERLEAVE_NONE,
      swz ? CU_TENSOR_MAP_SWIZZLE_128B : CU_TENSOR_MAP_SWIZZLE_NONE, wide ? CU_TENSOR_MAP_L2_PROMOTION_L2_256B : CU_TENSOR_MAP_L2_PROMOTION_L2_128B, CU_TENSOR_MAP_FLOAT_OOB_FILL_NONE);
}

extern "C" void kernel_launch(void* const* d_in, const int* in_sizes, int n_in, void* d_out, int out_size) {
  (void)in_sizes; (void)n_in; (void)out_size;
  static EncodeFn enc = nullptr;
  static void* abT = nullptr;
  static void* sc = nullptr;
  static int map = 0;
  if (!enc) {
    void* fn = nullptr; cudaDriverEntryPointQueryResult st;
    cudaGetDriverEntryPoint("cuTensorMapEncodeTiled", &fn, cudaEnableDefault, &st);
    enc = (EncodeFn)fn;
    cudaGetSymbolAddress(&abT, g_abT);
    cudaGetSymbolAddress(&sc, g_sc);
    cudaFuncSetAttribute(fnet_moe_kernel<0>, cudaFuncAttributeMaxDynamicSharedMemorySize, SMEM_TOTAL);
    cudaFuncSetAttribute(fnet_moe_kernel<1>, cudaFuncAttributeMaxDynamicSharedMemorySize, SMEM_TOTAL);
    cudaFuncSetAttribute(occupancy_probe_kernel, cudaFuncAttributeMaxDynamicSharedMemorySize, SMEM_TOTAL);
    cudaFuncSetAttribute(occupancy_probe_kernel, cudaFuncAttributeNonPortableClusterSizeAllowed, 1);
    cudaLaunchConfig_t cfg = {};
    cfg.gridDim = dim3(128); cfg.blockDim = dim3(NTHR); cfg.dynamicSmemBytes = SMEM_TOTAL;
    cudaLaunchAttribute at[1];
    at[0].id = cudaLaunchAttributeClusterDimension; at[0].val.clusterDim.x = 16; at[0].val.clusterDim.y = 1; at[0].val.clusterDim.z = 1;
    cfg.attrs = at; cfg.numAttrs = 1;
    int ncl = 0;
    if (cudaOccupancyMaxActiveClusters(&ncl, occupancy_probe_kernel, &cfg) == cudaSuccess && ncl >= 8) map = 1;
    (void)cudaGetLastError();
  }
  Params p;
  const bf16* x = (const bf16*)d_in[0];
  make_tm(enc, &p.tmD0, d_in[3], 1024, 1024, 128, 64, true, true);
  make_tm(enc, &p.tmD1, d_in[4], 1024, 1024, 128, 64, true, true);
  make_tm(enc, &p.tmX, x, 2048, 1024, 256, 64, true, true);
  make_tm(enc, &p.tmAbS, abT, 2048, 2048, 64, 64, true, false);
  make_tm(enc, &p.tmAbL, abT, 2048, 2048, 128, 64, true, false);
  make_tm(enc, &p.tmW0, d_in[1], 2048, 2048, 128, 64, true, true);
  make_tm(enc, &p.tmW1, d_in[2], 2048, 2048, 128, 64, true, true);
  make_tm(enc, &p.tmG, d_in[7], 1024, 3584, 16, 64, false, false);
  make_tm(enc, &p.tmU, d_in[8], 1024, 3584, 16, 64, false, false);
  make_tm(enc, &p.tmDn, d_in[9], 3584, 1024, 8, 256, false, false);
  make_tm(enc, &p.tmY, (char*)sc + offsetof(Scratch, ypart), 4 * NSRC, 512, NSRC, 16, false, false);
  p.x = x; p.Dre = (const bf16*)d_in[3]; p.Dim = (const bf16*)d_in[4];
  p.wr = (const bf16*)d_in[6]; p.wdown = (const bf16*)d_in[9]; p.wgate = (const bf16*)d_in[7]; p.wup = (const bf16*)d_in[8]; p.Wre = (const bf16*)d_in[1]; p.Wim = (const bf16*)d_in[2];
  p.out = (bf16*)d_out; p.sc = (Scratch*)sc;
  if (map == 1) fnet_moe_kernel<1><<<NGRID, NTHR, SMEM_TOTAL>>>(p);
  else fnet_moe_kernel<0><<<NGRID, NTHR, SMEM_TOTAL>>>(p);
}
```

```cpp
#include <cuda.h>
#include <cuda_runtime.h>
#include <cuda_bf16.h>
#include <stdint.h>
#include <stddef.h>
#include <type_traits>

typedef __nv_bfloat16 bf16;

constexpr int NGRID = 132, NTHR = 384;
__device__ __forceinline__ int k_col(int tau, int j) { return (tau * 256 + (j < 4 ? j * 64 : (j - 3) * 256)) & 2047; }
__device__ __forceinline__ int k_next(int c, int j) { return (c + (j < 11 ? 256 : j == 11 ? 576 : (c & 192) == 192 ? 128 : 64)) & 2047; }
constexpr int A_BYTES = 128 * 64 * 2;
constexpr int B_BYTES = 256 * 64 * 2;
constexpr int ST_BYTES = A_BYTES + B_BYTES;
constexpr int OFF_AUX = 4 * ST_BYTES;
constexpr int OFF_BAR = OFF_AUX + 32768;
constexpr int OFF_XS = OFF_BAR + 256;
constexpr int OFF_WR = OFF_XS + 2048;
constexpr int OFF_REM = OFF_WR + 256;
constexpr int OFF_INFO = OFF_REM + 256;
constexpr int SMEM_TOTAL = OFF_INFO + 256;
constexpr int INFO_WSUM = OFF_INFO, INFO_TAG = OFF_INFO + 4, INFO_KEY = OFF_INFO + 8, INFO_CAND = OFF_INFO + 16, INFO_LN = OFF_INFO + 32, INFO_ONES = OFF_INFO + 48, INFO_DS = OFF_INFO + 64, INFO_DS2 = OFF_INFO + 192;
constexpr int OFF_RS = OFF_XS;
constexpr int OFF_WC = OFF_AUX;
constexpr int OFF_EXA = OFF_AUX + 4096;
constexpr int OFF_EXB = OFF_AUX + 6144;
constexpr int OFF_RECV = A_BYTES;
__host__ __device__ constexpr int off_y(int w) { return w * ST_BYTES; }
constexpr int NSRC = 112;
enum { B_FULL = 0, B_EMPTY = 4, B_ALL = 6, B_EP = 8, B_AW = 16, B_STAT = 24, B_WC = 25, B_CD = 26, B_INFO = 28, B_PEER = 29, B_XCH = 30, B_GUX = (OFF_INFO + 128 - OFF_BAR) / 8, B_SD = B_GUX + 1, B_CH = 27, B_E23 = B_GUX + 5 };
enum { NB_TURN0 = 1, NB_TURN1 = 2, NB_BOTH = 3, NB_AUX = 4, NB_H = 5, NB_SEL = 6 };

struct Scratch;
struct Params {
  Scratch* sc; const bf16* wr; const bf16* x; const bf16* Dre; const bf16* Dim; const bf16* Wre; const bf16* Wim;
  const bf16* wgate; const bf16* wup; const bf16* wdown; bf16* out;
  CUtensorMap tmX, tmD0, tmD1, tmW0, tmW1, tmAbS, tmAbL, tmG, tmU, tmDn, tmY;
};

__device__ __align__(1024) bf16 g_abT[2048 * 2048];
struct Scratch {
  alignas(128) uint4 xz[2048];
  alignas(128) uint2 dsum[2048];
  alignas(128) uint32_t abflag[128 * 4 * 32];
  alignas(128) uint32_t abdone[128 * 2 * 32];
  alignas(128) uint2 u[4 * 512];
  alignas(128) uint2 cl[128 * 16];
  alignas(128) uint4 cpart[4 * 16 * 512];
  alignas(128) uint2 ch[8 * 512];
  alignas(128) uint4 cs[128 * 8];
  alignas(128) uint2 rdone[128];
  alignas(128) uint4 ypart[4 * NSRC * 64];
  alignas(128) uint4 hstat[16 * 8 * 128];
  alignas(128) uint2 key[128];
  alignas(128) uint2 hrow[128 * 512];
  alignas(128) uint2 fpart[8 * 1024];
  alignas(128) uint32_t epoch;
};
__device__ Scratch g_sc;

#define SPIN_LIMIT (1u << 17)
#define PF2_K 24
#define UNIT_PACE 1600
#define XPF_K 40
#define XS_DELAY 300
#define U_CLK 3700
#define XROW_PF 0
#define DROW_PF 0
#define TM_PF 0
#define SPLIT17 1
#define LO_NS 250
#define CAND_EARLY 0
#define CHAIN1 0
#define ROW_NS 400
#define W_PF 2
#define START_PF 0
#define ND0 65
#define ND1 66
#define ND2 67
#define ND3 -1
#define ND4 69
#define HI_DELAY 0
#define HI_PACE 1000
#define ALL_NS 400
#define PUT3_LATE 0
#define PUT1_LATE 0
#define DELEG 3
#define LU0_LATE 0
#define Y_NS 200
#define Z_CLK 9000
#define CP_DELAY 1500
#define CS_DELAY 800
#define YPART_DELAY 17300
__device__ __forceinline__ uint32_t smem_u32(const void* p) { return (uint32_t)__cvta_generic_to_shared(p); }
__device__ __forceinline__ uint32_t clk32() { uint32_t c; asm volatile("mov.u32 %0, %%clock;" : "=r"(c)); return c; }
__device__ __forceinline__ uint32_t zero_here() { uint64_t c; asm volatile("mov.u64 %0, %%clock64;" : "=l"(c) :: "memory"); return (uint32_t)(c >> 32) & blockIdx.y; }
__device__ __forceinline__ uint32_t uniform_zero_here() { uint32_t c; asm volatile("mov.u32 %0, %%clock;" : "=r"(c) :: "memory"); return c & blockIdx.y; }
__device__ __forceinline__ void wait_clk(uint32_t t0, uint32_t dt) {
  asm volatile("{\n.reg .pred p;\n.reg .u32 c;\nLOOP:\nmov.u32 c, %%clock;\nsub.u32 c, c, %0;\nsetp.lt.u32 p, c, %1;\n@p nanosleep.u32 100;\n@p bra LOOP;\n}\n" :: "r"(t0), "r"(dt) : "memory");
}
__device__ __forceinline__ void mbar_init(uint32_t bar, uint32_t cnt) { asm volatile("mbarrier.init.shared::cta.b64 [%0], %1;" :: "r"(bar), "r"(cnt) : "memory"); }
__device__ __forceinline__ void mbar_expect_tx(uint32_t bar, uint32_t bytes) { asm volatile("mbarrier.arrive.expect_tx.shared::cta.b64 _, [%0], %1;" :: "r"(bar), "r"(bytes) : "memory"); }
__device__ __forceinline__ void mbar_arrive(uint32_t bar) { asm volatile("mbarrier.arrive.shared::cta.b64 _, [%0];" :: "r"(bar) : "memory"); }
__device__ __forceinline__ void mbar_arrive_remote(uint32_t cluster_addr) { asm volatile("mbarrier.arrive.shared::cluster.b64 _, [%0];" :: "r"(cluster_addr) : "memory"); }
__device__ __forceinline__ void mbar_wait(uint32_t bar, uint32_t parity) {
  asm volatile("{\n.reg .pred p;\nLOOP:\nmbarrier.try_wait.parity.shared::cta.b64 p, [%0], %1;\n@!p bra LOOP;\n}\n" :: "r"(bar), "r"(parity) : "memory");
}
__device__ __forceinline__ void tma_load_2d(uint32_t dst, const CUtensorMap* tm, uint32_t bar, int c0, int c1) {
  asm volatile("cp.async.bulk.tensor.2d.shared::cluster.global.mbarrier::complete_tx::bytes [%0], [%1, {%3, %4}], [%2];"
    :: "r"(dst), "l"(tm), "r"(bar), "r"(c0), "r"(c1) : "memory");
}
__device__ __forceinline__ void tma_load_2d_hint(uint32_t dst, const CUtensorMap* tm, uint32_t bar, int c0, int c1, uint64_t pol) {
  asm volatile("cp.async.bulk.tensor.2d.shared::cluster.global.mbarrier::complete_tx::bytes.L2::cache_hint [%0], [%1, {%3, %4}], [%2], %5;"
    :: "r"(dst), "l"(tm), "r"(bar), "r"(c0), "r"(c1), "l"(pol) : "memory");
}
__device__ __forceinline__ uint64_t policy_evict_first() { uint64_t p; asm volatile("createpolicy.fractional.L2::evict_first.b64 %0, 1.0;" : "=l"(p)); return p; }
__device__ __forceinline__ void tma_store_2d(const CUtensorMap* tm, uint32_t src, int c0, int c1) {
  asm volatile("cp.async.bulk.tensor.2d.global.shared::cta.bulk_group [%0, {%2, %3}], [%1];" :: "l"(tm), "r"(src), "r"(c0), "r"(c1) : "memory");
}
__device__ __forceinline__ void bulk_load(uint32_t dst, const void* src, uint32_t bytes, uint32_t bar) {
  asm volatile("cp.async.bulk.shared::cluster.global.mbarrier::complete_tx::bytes [%0], [%1], %2, [%3];" :: "r"(dst), "l"(src), "r"(bytes), "r"(bar) : "memory");
}
__device__ __forceinline__ void prefetch_l2(const void* p) { asm volatile("prefetch.global.L2 [%0];" :: "l"(p)); }
__device__ __forceinline__ void bulk_commit() { asm volatile("cp.async.bulk.commit_group;" ::: "memory"); }
__device__ __forceinline__ void bulk_wait_all() { asm volatile("cp.async.bulk.wait_group 0;" ::: "memory"); }
__device__ __forceinline__ void fence_async_smem() { asm volatile("fence.proxy.async.shared::cta;" ::: "memory"); }
__device__ __forceinline__ void wgmma_fence() { asm volatile("wgmma.fence.sync.aligned;" ::: "memory"); }
__device__ __forceinline__ void wgmma_commit() { asm volatile("wgmma.commit_group.sync.aligned;" ::: "memory"); }
template<int N> __device__ __forceinline__ void wgmma_wait() { asm volatile("wgmma.wait_group.sync.aligned %0;" :: "n"(N) : "memory"); }
__device__ __forceinline__ void bar_sync(int id, int n) { asm volatile("bar.sync %0, %1;" :: "r"(id), "r"(n) : "memory"); }
__device__ __forceinline__ void bar_arrive(int id, int n) { asm volatile("bar.arrive %0, %1;" :: "r"(id), "r"(n) : "memory"); }
__device__ __forceinline__ void cluster_wait() { asm volatile("barrier.cluster.wait.aligned;" ::: "memory"); }
template<int R> __device__ __forceinline__ void reg_inc() { asm volatile("setmaxnreg.inc.sync.aligned.u32 %0;" :: "n"(R)); }
template<int R> __device__ __forceinline__ void reg_dec() { asm volatile("setmaxnreg.dec.sync.aligned.u32 %0;" :: "n"(R)); }
__device__ __forceinline__ bool elect_one() {
  uint32_t p;
  asm volatile("{\n.reg .pred q;\nelect.sync _|q, 0xffffffff;\nselp.u32 %0, 1, 0, q;\n}\n" : "=r"(p));
  return p != 0;
}
__device__ __forceinline__ uint32_t mapa(uint32_t addr, uint32_t cta) { uint32_t r; asm volatile("mapa.shared::cluster.u32 %0, %1, %2;" : "=r"(r) : "r"(addr), "r"(cta)); return r; }
__device__ __forceinline__ void st_async_v4(uint32_t addr, uint32_t bar, uint32_t a, uint32_t b, uint32_t c, uint32_t d) {
  asm volatile("st.async.weak.shared::cluster.mbarrier::complete_tx::bytes.v4.b32 [%0], {%2, %3, %4, %5}, [%1];" :: "r"(addr), "r"(bar), "r"(a), "r"(b), "r"(c), "r"(d) : "memory");
}
__device__ __forceinline__ void st_async_b32(uint32_t addr, uint32_t bar, uint32_t a) {
  asm volatile("st.async.weak.shared::cluster.mbarrier::complete_tx::bytes.b32 [%0], %2, [%1];" :: "r"(addr), "r"(bar), "r"(a) : "memory");
}
__device__ __forceinline__ void stsm_x4(uint32_t addr, uint32_t a, uint32_t b, uint32_t c, uint32_t d) {
  asm volatile("stmatrix.sync.aligned.m8n8.x4.shared.b16 [%0], {%1, %2, %3, %4};" :: "r"(addr), "r"(a), "r"(b), "r"(c), "r"(d) : "memory");
}
__device__ __forceinline__ void stsm_x4_t(uint32_t addr, uint32_t a, uint32_t b, uint32_t c, uint32_t d) {
  asm volatile("stmatrix.sync.aligned.m8n8.x4.trans.shared.b16 [%0], {%1, %2, %3, %4};" :: "r"(addr), "r"(a), "r"(b), "r"(c), "r"(d) : "memory");
}
__device__ __forceinline__ uint4 lds128(uint32_t addr) { uint4 v; asm volatile("ld.shared.v4.b32 {%0, %1, %2, %3}, [%4];" : "=r"(v.x), "=r"(v.y), "=r"(v.z), "=r"(v.w) : "r"(addr) : "memory"); return v; }
extern __shared__ __align__(1024) uint8_t smem_raw[];
template<class T> __device__ __forceinline__ T& SM(int off) { return *reinterpret_cast<T*>(smem_raw + off); }
__device__ __forceinline__ uint4 ldg_nc128(const void* p) { uint4 v; asm volatile("ld.global.nc.v4.b32 {%0, %1, %2, %3}, [%4];" : "=r"(v.x), "=r"(v.y), "=r"(v.z), "=r"(v.w) : "l"(p)); return v; }
__device__ __forceinline__ uint4 ldg128(const void* p) { uint4 v; asm volatile("ld.global.L1::no_allocate.v4.b32 {%0, %1, %2, %3}, [%4];" : "=r"(v.x), "=r"(v.y), "=r"(v.z), "=r"(v.w) : "l"(p) : "memory"); return v; }
__device__ __forceinline__ void pkt_st128(void* p, uint32_t a, uint32_t b, uint32_t c, uint32_t d) {
  asm volatile("{\n.reg .b128 v;\n.reg .b64 lo, hi;\nmov.b64 lo, {%1, %2};\nmov.b64 hi, {%3, %4};\nmov.b128 v, {lo, hi};\nst.relaxed.gpu.global.b128 [%0], v;\n}\n"
    :: "l"(p), "r"(a), "r"(b), "r"(c), "r"(d) : "memory");
}
__device__ __forceinline__ uint4 pkt_ld128(const void* p) {
  uint4 r;
  asm volatile("{\n.reg .b128 v;\n.reg .b64 lo, hi;\nld.relaxed.gpu.global.b128 v, [%4];\nmov.b128 {lo, hi}, v;\nmov.b64 {%0, %1}, lo;\nmov.b64 {%2, %3}, hi;\n}\n"
    : "=r"(r.x), "=r"(r.y), "=r"(r.z), "=r"(r.w) : "l"(p) : "memory");
  return r;
}
__device__ __forceinline__ void pkt_st64(void* p, uint32_t a, uint32_t b) {
  asm volatile("{\n.reg .b64 v;\nmov.b64 v, {%1, %2};\nst.relaxed.gpu.global.b64 [%0], v;\n}\n" :: "l"(p), "r"(a), "r"(b) : "memory");
}
__device__ __forceinline__ uint2 pkt_ld64(const void* p) {
  uint2 r;
  asm volatile("{\n.reg .b64 v;\nld.relaxed.gpu.global.b64 v, [%2];\nmov.b64 {%0, %1}, v;\n}\n" : "=r"(r.x), "=r"(r.y) : "l"(p) : "memory");
  return r;
}
__device__ __forceinline__ void pkt_clear128(void* p) { pkt_st128(p, 0, 0, 0, 0); }
__device__ __forceinline__ uint32_t ld_relaxed32(const void* p) { uint32_t v; asm volatile("ld.relaxed.gpu.global.b32 %0, [%1];" : "=r"(v) : "l"(p) : "memory"); return v; }
__device__ __forceinline__ uint32_t ld_acquire32(const void* p) { uint32_t v; asm volatile("ld.acquire.gpu.global.b32 %0, [%1];" : "=r"(v) : "l"(p) : "memory"); return v; }
__device__ __forceinline__ void st_relaxed32(void* p, uint32_t v) { asm volatile("st.relaxed.gpu.global.b32 [%0], %1;" :: "l"(p), "r"(v) : "memory"); }
__device__ __forceinline__ uint32_t poll64(const void* p, uint32_t tag, int ns) {
  uint2 v; uint32_t n = 0;
  bool more;
#pragma unroll 1
  do {
    v = pkt_ld64(p);
    more = !(v.y == tag) && ++n < SPIN_LIMIT;
    if (more) { __nanosleep(ns); }
  } while (more);
  return v.x;
}
__device__ __forceinline__ uint32_t poll64_warp(const void* p, uint32_t tag, int ns) {
  uint2 v; uint32_t n = 0;
  bool more;
#pragma unroll 1
  do {
    v = pkt_ld64(p);
    more = !(__all_sync(0xffffffffu, v.y == tag)) && ++n < SPIN_LIMIT;
    if (more) { __nanosleep(ns); }
  } while (more);
  return v.x;
}
__device__ __forceinline__ uint32_t code_of(uint32_t tag) { return tag % 3u + 1u; }
__device__ __forceinline__ uint32_t with_bit(uint32_t v, uint32_t bit) { return (v & ~1u) | (bit & 1u); }
__device__ __forceinline__ uint32_t with_bit(float v, uint32_t bit) { return with_bit(__float_as_uint(v), bit); }
__device__ __forceinline__ float no_bit(uint32_t v) { return __uint_as_float(v & ~1u); }
__device__ __forceinline__ void chk(uint32_t& bad, uint32_t a, uint32_t want) { bad |= a ^ want; asm("" : "+r"(bad)); }
__device__ __forceinline__ void chk_code(uint32_t& bad, const uint4& v, uint32_t c0, uint32_t c1) { chk(bad, v.x, c0); chk(bad, v.y, c1); chk(bad, v.z, c0); chk(bad, v.w, c1); }
__device__ __forceinline__ uint32_t pack_bf16(float lo, float hi) { uint32_t r; asm("cvt.rn.bf16x2.f32 %0, %1, %2;" : "=r"(r) : "f"(hi), "f"(lo)); return r; }
__device__ __forceinline__ float bf_lo(uint32_t v) { return __uint_as_float(v << 16); }
__device__ __forceinline__ float bf_hi(uint32_t v) { return __uint_as_float(v & 0xFFFF0000u); }
__device__ __forceinline__ float bf16r(float x) { return __uint_as_float(pack_bf16(0.f, x)); }
__device__ __forceinline__ void st_bf16(bf16* p, float x) { *reinterpret_cast<uint16_t*>(p) = (uint16_t)pack_bf16(x, 0.f); }
__device__ __forceinline__ float fast_rcp(float x) { float r; asm("rcp.approx.f32 %0, %1;" : "=f"(r) : "f"(x)); return r; }
__device__ __forceinline__ float ldbf(const bf16* p) { return __bfloat162float(*p); }
__device__ __forceinline__ uint32_t badd2(uint32_t a, uint32_t b) { uint32_t r; asm("add.rn.bf16x2 %0, %1, %2;" : "=r"(r) : "r"(a), "r"(b)); return r; }
__device__ __forceinline__ uint32_t bfma2(uint32_t a, uint32_t b, uint32_t c) { uint32_t r; asm("fma.rn.bf16x2 %0, %1, %2, %3;" : "=r"(r) : "r"(a), "r"(b), "r"(c)); return r; }
__device__ __forceinline__ float warp_sum(float v) {
#pragma unroll
  for (int o = 16; o > 0; o >>= 1) v += __shfl_xor_sync(0xffffffffu, v, o);
  return v;
}
template<int N> __device__ __forceinline__ void fold(float* v, int o, int lane) {
  const bool up = lane & o;
#pragma unroll
  for (int i = 0; i < N / 2; i++) {
    const float keep = up ? v[N / 2 + i] : v[i], send = up ? v[i] : v[N / 2 + i];
    v[i] = keep + __shfl_xor_sync(0xffffffffu, send, o);
  }
}
__device__ __forceinline__ uint32_t make_key(float r_bf, int row) {
  const uint32_t u = __float_as_uint(r_bf);
  return (((u & 0x80000000u) ? ~u : (u | 0x80000000u)) & 0xFFFF0000u) | (0xFFFFu - (uint32_t)row);
}
__device__ __forceinline__ int key_row(uint32_t key) { return (0xFFFF - (int)(key & 0xFFFFu)) & 2047; }
__device__ __forceinline__ float key_val(uint32_t key) { const uint32_t o = key & 0xFFFF0000u; return __uint_as_float((o & 0x80000000u) ? (o & 0x7FFFFFFFu) : (~o & 0xFFFF0000u)); }
__device__ __forceinline__ float ref_sd(float var) { float r; asm("sqrt.approx.f32 %0, %1;" : "=f"(r) : "f"(bf16r(bf16r(var) + 1e-5f))); return bf16r(r); }
__device__ __forceinline__ uint64_t make_desc(uint32_t addr) { return (uint64_t)((addr & 0x3FFFF) >> 4) | ((uint64_t)64 << 32) | ((uint64_t)1 << 62); }
__device__ __forceinline__ uint64_t make_desc_noswz(uint32_t addr) { return (uint64_t)((addr & 0x3FFFF) >> 4) | ((uint64_t)8 << 32); }
#define ACC8(d, o) "+f"(d[o]), "+f"(d[o + 1]), "+f"(d[o + 2]), "+f"(d[o + 3]), "+f"(d[o + 4]), "+f"(d[o + 5]), "+f"(d[o + 6]), "+f"(d[o + 7])
#define ACC64(d, o) ACC8(d, o), ACC8(d, o + 8), ACC8(d, o + 16), ACC8(d, o + 24), ACC8(d, o + 32), ACC8(d, o + 40), ACC8(d, o + 48), ACC8(d, o + 56)
#define REGS64 "%0, %1, %2, %3, %4, %5, %6, %7, %8, %9, %10, %11, %12, %13, %14, %15, %16, %17, %18, %19, %20, %21, %22, %23, %24, %25, %26, %27, %28, %29, %30, %31, " \
    "%32, %33, %34, %35, %36, %37, %38, %39, %40, %41, %42, %43, %44, %45, %46, %47, %48, %49, %50, %51, %52, %53, %54, %55, %56, %57, %58, %59, %60, %61, %62, %63"
#define REGS128 REGS64 ", %64, %65, %66, %67, %68, %69, %70, %71, %72, %73, %74, %75, %76, %77, %78, %79, %80, %81, %82, %83, %84, %85, %86, %87, %88, %89, %90, %91, %92, %93, %94, %95, " \
    "%96, %97, %98, %99, %100, %101, %102, %103, %104, %105, %106, %107, %108, %109, %110, %111, %112, %113, %114, %115, %116, %117, %118, %119, %120, %121, %122, %123, %124, %125, %126, %127"
__device__ __forceinline__ void wgmma_n256(float (&d)[128], uint64_t da, uint64_t db) {
  asm volatile("wgmma.mma_async.sync.aligned.m64n256k16.f32.bf16.bf16 {" REGS128 "}, %128, %129, 1, 1, 1, 0, 0;\n"
    : ACC64(d, 0), ACC64(d, 64) : "l"(da), "l"(db));
}
#define OUT8(d, o) "=f"(d[o]), "=f"(d[o + 1]), "=f"(d[o + 2]), "=f"(d[o + 3]), "=f"(d[o + 4]), "=f"(d[o + 5]), "=f"(d[o + 6]), "=f"(d[o + 7])
#define OUT64(d, o) OUT8(d, o), OUT8(d, o + 8), OUT8(d, o + 16), OUT8(d, o + 24), OUT8(d, o + 32), OUT8(d, o + 40), OUT8(d, o + 48), OUT8(d, o + 56)
__device__ __forceinline__ void wgmma_n256_rs_init(float (&d)[128], const uint32_t* a, uint64_t db) {
  asm volatile("wgmma.mma_async.sync.aligned.m64n256k16.f32.bf16.bf16 {" REGS128 "}, {%128, %129, %130, %131}, %132, 0, 1, 1, 0;\n"
    : OUT64(d, 0), OUT64(d, 64) : "r"(a[0]), "r"(a[1]), "r"(a[2]), "r"(a[3]), "l"(db));
}
template<int ACCUM> __device__ __forceinline__ void wgmma_n256_rs(float (&d)[128], const uint32_t* a, uint64_t db) {
  asm volatile("wgmma.mma_async.sync.aligned.m64n256k16.f32.bf16.bf16 {" REGS128 "}, {%128, %129, %130, %131}, %132, %133, 1, 1, 0;\n"
    : ACC64(d, 0), ACC64(d, 64) : "r"(a[0]), "r"(a[1]), "r"(a[2]), "r"(a[3]), "l"(db), "n"(ACCUM));
}
template<int ACCUM> __device__ __forceinline__ void wgmma_n8_rs(float (&d)[4], const uint32_t* a, uint64_t db) {
  asm volatile("wgmma.mma_async.sync.aligned.m64n8k16.f32.bf16.bf16 {%0, %1, %2, %3}, {%4, %5, %6, %7}, %8, %9, 1, 1, 0;\n"
    : "+f"(d[0]), "+f"(d[1]), "+f"(d[2]), "+f"(d[3]) : "r"(a[0]), "r"(a[1]), "r"(a[2]), "r"(a[3]), "l"(db), "n"(ACCUM));
}
__device__ __forceinline__ void wgmma_n8(float (&d)[4], uint64_t da, uint64_t db) {
  asm volatile("wgmma.mma_async.sync.aligned.m64n8k16.f32.bf16.bf16 {%0, %1, %2, %3}, %4, %5, 1, 1, 1, 0, 0;\n"
    : "+f"(d[0]), "+f"(d[1]), "+f"(d[2]), "+f"(d[3]) : "l"(da), "l"(db));
}
__device__ __forceinline__ void wgmma_n128(float (&d)[64], uint64_t da, uint64_t db) {
  asm volatile("wgmma.mma_async.sync.aligned.m64n128k16.f32.bf16.bf16 {" REGS64 "}, %64, %65, 1, 1, 1, 0, 0;\n" : ACC64(d, 0) : "l"(da), "l"(db));
}
template<int N> __device__ __forceinline__ void fence_regs(float (&d)[N]) {
#pragma unroll
  for (int i = 0; i < N; i++) asm volatile("" : "+f"(d[i]) :: "memory");
}
__device__ __forceinline__ void mma16816(float (&c)[4], uint32_t a0, uint32_t a1, uint32_t a2, uint32_t a3, uint32_t b0, uint32_t b1) {
  asm volatile("mma.sync.aligned.m16n8k16.row.col.f32.bf16.bf16.f32 {%0, %1, %2, %3}, {%4, %5, %6, %7}, {%8, %9}, {%0, %1, %2, %3};"
               : "+f"(c[0]), "+f"(c[1]), "+f"(c[2]), "+f"(c[3]) : "r"(a0), "r"(a1), "r"(a2), "r"(a3), "r"(b0), "r"(b1));
}
__device__ __forceinline__ void fma8(float* acc, const uint4& v, float x) {
  acc[0] = fmaf(bf_lo(v.x), x, acc[0]); acc[1] = fmaf(bf_hi(v.x), x, acc[1]); acc[2] = fmaf(bf_lo(v.y), x, acc[2]); acc[3] = fmaf(bf_hi(v.y), x, acc[3]);
  acc[4] = fmaf(bf_lo(v.z), x, acc[4]); acc[5] = fmaf(bf_hi(v.z), x, acc[5]); acc[6] = fmaf(bf_lo(v.w), x, acc[6]); acc[7] = fmaf(bf_hi(v.w), x, acc[7]);
}
template<int PITCH> __device__ __forceinline__ void gemv8x8(float (&acc)[8], uint32_t addr, const float (&x)[8]) {
  uint4 v[2][2];
  v[0][0] = lds128(addr); v[0][1] = lds128(addr + PITCH);
#pragma unroll
  for (int b = 0; b < 4; b++) {
    if (b < 3) { v[(b + 1) & 1][0] = lds128(addr + (2 * b + 2) * PITCH); v[(b + 1) & 1][1] = lds128(addr + (2 * b + 3) * PITCH); }
    acc[0] += __uint_as_float(zero_here());
    fma8(acc, v[b & 1][0], x[2 * b]); fma8(acc, v[b & 1][1], x[2 * b + 1]);
  }
}
__device__ __forceinline__ float swiglu(float g, float u) {
  g = bf16r(g); u = bf16r(u);
  return bf16r(bf16r(g * fast_rcp(1.f + __expf(-g))) * u);
}

#define CT(slot) do {} while (0)
#define TIM(slot) do {} while (0)

constexpr int H_BUF0 = 0, H_BUF1 = 16384, H_RED = 32768, H_KEYS = H_RED + 1024, H_ROW = H_KEYS + 1024, H_ACT = H_ROW + 8192, H_PART = H_ACT + 4096;
__device__ __forceinline__ void hsync() { bar_sync(NB_H, 256); }
template<int N> __device__ __forceinline__ void block_sum(float (&v)[N], int warp, int lane) {
#pragma unroll
  for (int i = 0; i < N; i++) v[i] = warp_sum(v[i]);
  hsync();
  if (lane == 0) {
#pragma unroll
    for (int i = 0; i < N; i++) SM<float>(H_RED + (i * 8 + warp) * 4) = v[i];
  }
  hsync();
#pragma unroll
  for (int i = 0; i < N; i++) {
    const float4 a = SM<float4>(H_RED + i * 32), b = SM<float4>(H_RED + i * 32 + 16);
    v[i] = ((a.x + a.y) + (a.z + a.w)) + ((b.x + b.y) + (b.z + b.w));
  }
}
__device__ __forceinline__ void fft_first(int j, float2 v0, float2 v1, float2 v2, float2 v3) {
  const float2 a = make_float2(v0.x + v2.x, v0.y + v2.y), b = make_float2(v0.x - v2.x, v0.y - v2.y);
  const float2 c = make_float2(v1.x + v3.x, v1.y + v3.y), d = make_float2(v1.y - v3.y, v3.x - v1.x);
  SM<float4>(H_BUF1 + j * 32) = make_float4(a.x + c.x, a.y + c.y, b.x + d.x, b.y + d.y);
  SM<float4>(H_BUF1 + j * 32 + 16) = make_float4(a.x - c.x, a.y - c.y, b.x - d.x, b.y - d.y);
}
template<int NB> __device__ __forceinline__ void fft_passes(int tid) {
  constexpr int q = 256 * NB;
#pragma unroll 1
  for (int ps = 1; ps < 5; ps++) {
    const int ns = 1 << (2 * ps), k = tid & (ns - 1);
    float s1, c1;
    __sincosf(-1.57079632679f * __fdividef((float)k, (float)ns), &s1, &c1);
    const float c2 = c1 * c1 - s1 * s1, s2 = 2.f * c1 * s1, c3 = c1 * c2 - s1 * s2, s3 = c1 * s2 + s1 * c2;
    hsync();
#pragma unroll
    for (int i = 0; i < NB; i++) {
      const int j = tid + 256 * i;
      const float2* in = &SM<float2>((ps & 1) ? H_BUF1 : H_BUF0);
      float2* o = &SM<float2>((ps & 1) ? H_BUF0 : H_BUF1) + (j - k) * 4 + k;
      const float2 v0 = in[j], x1 = in[j + q], x2 = in[j + 2 * q], x3 = in[j + 3 * q];
      const float2 v1 = make_float2(x1.x * c1 - x1.y * s1, x1.x * s1 + x1.y * c1);
      const float2 v2 = make_float2(x2.x * c2 - x2.y * s2, x2.x * s2 + x2.y * c2);
      const float2 v3 = make_float2(x3.x * c3 - x3.y * s3, x3.x * s3 + x3.y * c3);
      const float2 a = make_float2(v0.x + v2.x, v0.y + v2.y), b = make_float2(v0.x - v2.x, v0.y - v2.y);
      const float2 c = make_float2(v1.x + v3.x, v1.y + v3.y), d = make_float2(v1.y - v3.y, v3.x - v1.x);
      o[0] = make_float2(a.x + c.x, a.y + c.y); o[ns] = make_float2(b.x + d.x, b.y + d.y);
      o[2 * ns] = make_float2(a.x - c.x, a.y - c.y); o[3 * ns] = make_float2(b.x - d.x, b.y - d.y);
    }
  }
  hsync();
}
template<int NR> __device__ __forceinline__ void ln_rows(const float (&h)[NR][4], float (&hn)[NR][4], int warp, int lane) {
  float s[NR], q[NR];
#pragma unroll
  for (int i = 0; i < NR; i++) s[i] = (h[i][0] + h[i][1]) + (h[i][2] + h[i][3]);
  block_sum(s, warp, lane);
#pragma unroll
  for (int i = 0; i < NR; i++) {
    s[i] *= 1.f / 1024.f; q[i] = 0.f;
#pragma unroll
    for (int z = 0; z < 4; z++) q[i] = fmaf(h[i][z] - s[i], h[i][z] - s[i], q[i]);
  }
  block_sum(q, warp, lane);
#pragma unroll
  for (int i = 0; i < NR; i++) {
    const float mb = bf16r(s[i]), inv = fast_rcp(ref_sd(q[i] * (1.f / 1024.f)));
#pragma unroll
    for (int z = 0; z < 4; z++) hn[i][z] = bf16r(bf16r(h[i][z] - mb) * inv);
  }
}
__device__ __forceinline__ float sigmoid_bf(float r) { return bf16r(fast_rcp(1.f + __expf(-r))); }
__device__ __forceinline__ float routed_out(float h, float hn, float y, float sig) { return h + bf16r(hn + bf16r(bf16r(y) * sig)); }

__device__ __forceinline__ void helper_cta(const Params& p, const int hi, const uint32_t t_entry) {
  const int tid = threadIdx.x, warp = tid >> 5, lane = tid & 31;
  const float w0 = ldbf(p.wr + tid), w1 = ldbf(p.wr + tid + 256), w2 = ldbf(p.wr + tid + 512), w3 = ldbf(p.wr + tid + 768), wf = ldbf(p.wr);
  const uint32_t tag = ld_relaxed32(&p.sc->epoch) + 1;
  pkt_clear128(&p.sc->u[hi * 512 + tid * 2]);
  if (tid == 0 && w0 != 123.f) TIM(12);
  fft_first(tid, make_float2(w0, 0.f), make_float2(w1, 0.f), make_float2(w2, 0.f), make_float2(w3, 0.f));
  fft_passes<1>(tid);
  const uint32_t c0 = code_of(tag), c1 = c0 >> 1;
  {
    const float off = wf - SM<float>(H_BUF1) * (1.f / 1024.f);
    const float4 v = SM<float4>(H_BUF1 + tid * 32), u = SM<float4>(H_BUF1 + tid * 32 + 16);
    pkt_st128(&p.sc->u[hi * 512 + ((tid & 192) + (tid & 1) * 32 + ((tid >> 1) & 31)) * 2], with_bit(pack_bf16((tid ? v.x : 0.f) - off, v.z - off), c0), with_bit(pack_bf16(v.y, v.w), c1),
              with_bit(pack_bf16(u.x - off, u.z - off), c0), with_bit(pack_bf16(u.y, u.w), c1));
    if (tid < 64) pkt_clear128(&p.sc->cl[(hi * 32 + (tid >> 1)) * 16 + (tid & 1) * 2]);
    hsync();
  }
  if (tid == 0) TIM(0);
  {
    float tw[8];
#pragma unroll
    for (int i = 0; i < 4; i++) __sincosf((float)(tid + 256 * i) * (-6.28318530718f / 2048.f), &tw[2 * i], &tw[2 * i + 1]);
    wait_clk(t_entry, Z_CLK);
    uint2 z[8]; uint32_t n = 0;
    bool more;
#pragma unroll 1
    do {
      uint32_t bad = 0;
#pragma unroll
      for (int i = 0; i < 8; i++) z[i] = pkt_ld64(reinterpret_cast<const uint2*>(&p.sc->xz[tid]) + 512 * i + 1);
#pragma unroll
      for (int i = 0; i < 8; i++) chk(bad, z[i].y, tag);
      more = !(!bad) && ++n < SPIN_LIMIT;
      if (more) { __nanosleep(150); }
    } while (more);
#pragma unroll
    for (int i = 0; i < 2; i++)
      fft_first(tid + 256 * i, make_float2(bf_lo(z[i].x), bf_hi(z[i].x)), make_float2(bf_lo(z[i + 2].x), bf_hi(z[i + 2].x)),
                make_float2(bf_lo(z[i + 4].x), bf_hi(z[i + 4].x)), make_float2(bf_lo(z[i + 6].x), bf_hi(z[i + 6].x)));
    if (tid == 0) TIM(7);
    fft_passes<2>(tid);
    if (tid == 0) TIM(1);
    uint32_t k8[8];
#pragma unroll
    for (int i = 0; i < 4; i++) {
      const int k = tid + 256 * i;
      const float2 v0 = SM<float2>(H_BUF1 + k * 8), v1 = SM<float2>(H_BUF1 + (k + 1024) * 8);
      const float w = v1.x * tw[2 * i + 1] - v1.y * tw[2 * i];
      const uint32_t a = __float_as_uint(v0.x + w), b = __float_as_uint(v0.x - w);
      k8[2 * i] = (((a & 0x80000000u) ? ~a : (a | 0x80000000u)) & ~2047u) | k;
      k8[2 * i + 1] = (((b & 0x80000000u) ? ~b : (b | 0x80000000u)) & ~2047u) | (k + 1024);
    }
    uint32_t lim = 0xFFFFFFFFu;
#pragma unroll 1
    for (int r = 0; r < 4; r++) {
      uint32_t mx = 0;
#pragma unroll
      for (int i = 0; i < 8; i++) mx = max(mx, k8[i] <= lim ? k8[i] : 0u);
      mx = __reduce_max_sync(0xffffffffu, mx);
      if (lane == 0) SM<uint32_t>(H_KEYS + (warp * 4 + r) * 4) = mx;
      lim = mx - 1;
    }
    hsync();
    if (tid < 32) {
      const uint32_t me = SM<uint32_t>(H_KEYS + tid * 4);
      int rank = 0;
#pragma unroll
      for (int i = 0; i < 8; i++) { const uint4 o = SM<uint4>(H_KEYS + i * 16); rank += (o.x > me) + (o.y > me) + (o.z > me) + (o.w > me); }
      if (rank < 8) SM<uint16_t>(H_KEYS + 256 + rank * 2) = me & 2047u;
    }
    hsync();
    if (tid >= 128) pkt_st64(&p.sc->cl[(hi * 32 + ((tid - 128) >> 2)) * 16 + (tid & 3)], SM<uint32_t>(H_KEYS + 256 + (tid & 3) * 4), tag);
  }
  const uint32_t cpair = SM<uint32_t>(H_KEYS + 256 + hi * 4);
  const int ca = cpair & 0xFFFF, cb = cpair >> 16;
  if (tid < 128) prefetch_l2(((tid & 32) ? p.Wim : p.Wre) + (size_t)((tid & 64) ? cb : ca) * 2048 + lane * 64);
  if (tid == 0) TIM(2);
}

__device__ __forceinline__ void slow_path(const Params& p, int grp, int eps, uint32_t tag, uint32_t key, int win, float mb, float inv) {
  const int tid = threadIdx.x + zero_here(), warp = tid >> 5, lane = tid & 31;
  uint32_t best = __reduce_max_sync(0xffffffffu, poll64(&p.sc->key[tid & 127], tag, 200));
  if (lane == 0) SM<uint32_t>(H_KEYS + warp * 4) = best;
  hsync();
  { const uint4 b4 = SM<uint4>(H_KEYS); best = max(max(b4.x, b4.y), max(b4.z, b4.w)); }
  const int tw = key_row(best), col = eps * 128 + (tid & 127);
  if ((tw >> 7) != grp) return;
  poll64(&p.sc->rdone[col >> 3], tag, 100);
  const uint32_t h0 = poll64(&p.sc->hrow[(tw >> 4) * 512 + 2 * tid], tag, 100), h1 = poll64(&p.sc->hrow[(tw >> 4) * 512 + 2 * tid + 1], tag, 100);
  float h[1][4] = {{bf_lo(h0), bf_hi(h0), bf_lo(h1), bf_hi(h1)}}, hn[1][4];
  ln_rows<1>(h, hn, warp, lane);
  SM<float4>(H_ROW + tid * 16) = make_float4(hn[0][0], hn[0][1], hn[0][2], hn[0][3]);
  SM<float4>(H_ROW + 4096 + tid * 16) = make_float4(h[0][0], h[0][1], h[0][2], h[0][3]);
  hsync();
#pragma unroll 1
  for (int ph = 0; ph < 2; ph++) {
    const int part = min(tid / 56, 3), fh = tid >> 7, len = ph ? 224 : 512, ld = ph ? 1024 : 3584;
    const bf16* wp = ph ? p.wdown + (eps * 448 + fh * 224) * 1024 + (tid & 127) * 8
                        : ((part & 1) ? p.wup : p.wgate) + (part >> 1) * 512 * 3584 + eps * 448 + min(tid - part * 56, 55) * 8;
    const int xo = ph ? H_ACT + fh * 224 * 4 : H_ROW + (part >> 1) * 2048;
    float acc[8] = {0.f, 0.f, 0.f, 0.f, 0.f, 0.f, 0.f, 0.f};
#pragma unroll 8
    for (int d = 0; d < (len & ~7); d++) fma8(acc, ldg_nc128(wp + d * ld), SM<float>(xo + d * 4));
    SM<float4>(H_PART + tid * 32) = make_float4(acc[0], acc[1], acc[2], acc[3]);
    SM<float4>(H_PART + tid * 32 + 16) = make_float4(acc[4], acc[5], acc[6], acc[7]);
    hsync();
    if (ph) break;
#pragma unroll 1
    for (int f = tid; f < 448; f += 256)
      SM<float>(H_ACT + f * 4) = swiglu(SM<float>(H_PART + f * 4) + SM<float>(H_PART + (896 + f) * 4), SM<float>(H_PART + (448 + f) * 4) + SM<float>(H_PART + (1344 + f) * 4));
    hsync();
  }
#pragma unroll 1
  for (int e = tid; e < 1024; e += 256) pkt_st64(&p.sc->fpart[eps * 1024 + e], __float_as_uint(SM<float>(H_PART + e * 4) + SM<float>(H_PART + (1024 + e) * 4)), tag);
  if (tid < 128) {
    float y = 0.f;
#pragma unroll 1
    for (int q = 0; q < 8; q++) y += __uint_as_float(poll64(&p.sc->fpart[q * 1024 + col], tag, 200));
    st_bf16(p.out + tw * 1024 + col, routed_out(SM<float>(H_ROW + 4096 + col * 4), SM<float>(H_ROW + col * 4), y, sigmoid_bf(key_val(best))));
    const uint32_t a = poll64(&p.sc->ch[win * 512 + (col >> 4) * 8 + (col & 7)], tag, 100);
    const float hc = (col & 8) ? bf_hi(a) : bf_lo(a);
    st_bf16(p.out + key_row(key) * 1024 + col, hc + bf16r(bf16r(hc - mb) * inv));
  }
}

template<int MAP>
__global__ void __cluster_dims__(2, 1, 1) __launch_bounds__(NTHR, 1)
fnet_moe_kernel(const __grid_constant__ Params p) {
  const uint32_t t_entry = clk32();
  uint32_t smid;
  asm("mov.u32 %0, %%smid;" : "=r"(smid));
  const int tpc = smid >> 1, m = blockIdx.x & 1;
  if (MAP == 1 ? tpc >= 64 : (tpc >> 1) == 30) {
    if (threadIdx.x < 256) helper_cta(p, (tpc & 1) * 2 + m, t_entry);
    return;
  }
  const uint32_t sb = smem_u32(smem_raw);
  const int tid = threadIdx.x, lane = tid & 31;
  const int e7 = ((tpc - 32) * 37) >> 8;
  const int tau = MAP == 1 || tpc < 32 ? (tpc & 7) : (tpc < 60 ? tpc - 31 - 7 * e7 : 0);
  const int eps = MAP == 1 || tpc < 32 ? (tpc >> 3) : (tpc < 60 ? 4 + e7 : tpc - 58);
  const int cid = tau * 16 + eps * 2 + m;
  auto BAR = [&](int i) { return sb + OFF_BAR + 8 * i; };
  const CUtensorMap* tmD = &p.tmD0 + m;
#define LOAD_STREAM(d, tm, bar, c0, c1) tma_load_2d_hint(d, tm, bar, c0, c1, pol_ef)
#define LOAD_W tma_load_2d
#define LOAD_D tma_load_2d
#define LOAD_X tma_load_2d
#define LOAD_F LOAD_STREAM

  uint32_t tag = 0;
  uint4 wq = make_uint4(0, 0, 0, 0);
  if ((tid >> 5) == 4) {
    if (elect_one()) {
      const uint64_t pol_ef = policy_evict_first();
#pragma unroll
      for (int k = 0; k < 4; k++) mbar_init(BAR(B_FULL + k), 1);
      asm volatile("fence.mbarrier_init.release.cluster;" ::: "memory");
#pragma unroll
      for (int k = 0; k < 4; k++) {
        mbar_expect_tx(BAR(B_FULL + k), ST_BYTES);
        tma_load_2d(sb + k * ST_BYTES + A_BYTES, &p.tmX, BAR(B_FULL + k), k * 64, tau * 256);
        LOAD_D(sb + k * ST_BYTES, tmD, BAR(B_FULL + k), k * 64, eps * 128);
        TIM(k);
      }
    }
  } else if ((tid >> 5) == 1) {
    if (elect_one()) {
#pragma unroll
      for (int s = 0; s < 4; s++) { mbar_init(BAR(B_EMPTY + s), 1); mbar_init(BAR(B_SD + s), 1); }
#pragma unroll
      for (int s = 0; s < 8; s++) { mbar_init(BAR(B_EP + s), 4); mbar_init(BAR(B_AW + s), 1); }
      mbar_init(BAR(B_STAT), 4); mbar_init(BAR(B_WC), 1); mbar_init(BAR(B_CD), 2);
      mbar_init(BAR(B_E23), 1); mbar_init(BAR(B_E23 + 1), 1); mbar_init(BAR(B_E23 + 2), 1); mbar_init(BAR(B_CH), 1); mbar_init(BAR(B_INFO), 1); mbar_init(BAR(B_PEER), 1);
      mbar_init(BAR(B_XCH), 1); mbar_init(BAR(B_XCH + 1), 1); mbar_init(BAR(B_GUX), 1);
      asm volatile("fence.mbarrier_init.release.cluster;" ::: "memory");
      mbar_expect_tx(BAR(B_XCH), 16384); mbar_expect_tx(BAR(B_XCH + 1), 16384); mbar_expect_tx(BAR(B_GUX), 256);
    }
  } else if (tid >= 256) {
    if (START_PF) prefetch_l2(((tid & 64) ? (cid < 64 ? p.Dre : p.Dim) + (cid & 63) * 16384 : p.x + cid * 16384) + ((tid >> 2) & 15) * 1024 + (tid & 3) * 64);
    tag = ld_relaxed32(&p.sc->epoch + threadIdx.y);
    wq = ldg128(p.wr + (tid & 127) * 8);
  }
  const int warp = __shfl_sync(0xffffffffu, tid >> 5, 0);
  __syncthreads();
  asm volatile("barrier.cluster.arrive.relaxed.aligned;" ::: "memory");

  if (warp >= 8) {
    reg_dec<72>();
    cluster_wait();
    tag = __shfl_sync(0xffffffffu, tag, 0) + 1;
    const int cid0 = cid;
    const uint32_t tag0 = tag, sb0 = sb;
    int a, lane, j, cid, tau, eps, m, grp, abrow, fc, src;
    uint32_t tag, c0, c1, sb, buf, bar0;
    bool ffn;
    auto BAR = [&](int i) { return sb + OFF_BAR + 8 * i; };
    auto fresh_ids = [&]() {
      const uint32_t z = uniform_zero_here();
      uint32_t l; asm volatile("mov.u32 %0, %%laneid;" : "=r"(l));
      a = warp - 8 + z; lane = l; j = a * 32 + l;
      cid = cid0 + z; tau = cid >> 4; eps = (cid >> 1) & 7; m = cid & 1; grp = tau * 2 + m; abrow = m * 1024 + eps * 128;
      ffn = eps > 0; fc = (tau * 7 + eps - 1) * 64; src = (fc >> 5) + m;
      tag = tag0 + z; c0 = code_of(tag); c1 = c0 >> 1;
      sb = sb0 + z; buf = sb + OFF_AUX + a * 8192; bar0 = BAR(B_AW + 2 * a);
    };
    fresh_ids();
    if (a == 0 && lane < 16) pkt_clear128(&p.sc->xz[cid * 16 + lane]);
    if (lane < 2) pkt_clear128(&p.sc->dsum[cid * 16 + a * 4 + lane * 2]);
    if (a == 3 && lane < 10) pkt_clear128((lane < 4 ? &p.sc->abdone[cid * 64] : &p.sc->abflag[cid * 128 - 64]) + (lane >> 1) * 32 + (lane & 1) * 4);
    {
      const float s = warp_sum(((bf_lo(wq.x) + bf_hi(wq.x)) + (bf_lo(wq.y) + bf_hi(wq.y))) + ((bf_lo(wq.z) + bf_hi(wq.z)) + (bf_lo(wq.w) + bf_hi(wq.w))));
      if ((j >> 4) == eps) SM<uint4>(OFF_WR + (j & 15) * 16) = wq;
      if (lane == 0) { SM<float>(INFO_DS + a * 4) = s; SM<uint32_t>(INFO_ONES + a * 4) = 0x3F803F80u; }
    }
    const bf16* xrows = p.x + (cid * 16 + a * 4) * 1024;
    const bf16* drows = (cid < 64 ? p.Dre : p.Dim) + ((cid & 63) * 16 + a * 4) * 1024;
    if (XROW_PF) {
      wait_clk(t_entry, XROW_PF);
      prefetch_l2(xrows + lane * 64); prefetch_l2(xrows + 2048 + lane * 64);
    }
    fresh_ids();
    {
      wait_clk(t_entry, U_CLK);
      uint4 u[8]; uint32_t n = 0;
      bool more;
#pragma unroll 1
      do {
        uint32_t bad = 0;
#pragma unroll
        for (int q = 0; q < 8; q++) u[q] = pkt_ld128(&p.sc->u[a * 512 + lane * 2] + q * 64);
        if (n == 0 && lane < 2) { mbar_expect_tx(bar0 + lane * 8, 4096); bulk_load(buf + lane * 4096, xrows + lane * 2048, 4096, bar0 + lane * 8); }
#pragma unroll
        for (int q = 0; q < 8; q++) chk_code(bad, u[q], c0, c1);
        more = !(!__any_sync(0xffffffffu, bad & 1)) && ++n < SPIN_LIMIT;
        if (more) { __nanosleep(200); }
      } while (more);
      if (j == 0) TIM(96);
      if (DROW_PF) { prefetch_l2(drows + lane * 64); prefetch_l2(drows + 2048 + lane * 64); }
#pragma unroll 1
      for (int r2 = 0; r2 < 2; r2++) {
        float v8[8];
        mbar_wait(bar0 + r2 * 8, 0);
        if (lane == 0) TIM(140 + r2 * 4 + a);
#pragma unroll
        for (int r = 0; r < 2; r++) {
          float s0 = 0.f, s1 = 0.f, q0 = 0.f, q1 = 0.f;
          uint32_t zr = 0, zi = 0;
#pragma unroll
          for (int q = 0; q < 4; q++) {
            const uint4 v = lds128(buf + r2 * 4096 + r * 2048 + (q * 32 + lane) * 16);
            const uint32_t ww[4] = {v.x, v.y, v.z, v.w};
#pragma unroll
            for (int z = 0; z < 4; z++) {
              const float lo = bf_lo(ww[z]), hi = bf_hi(ww[z]);
              s0 += lo; s1 += hi; q0 = fmaf(lo, lo, q0); q1 = fmaf(hi, hi, q1);
            }
            zr = bfma2(v.x, u[2 * q].x, zr); zi = bfma2(v.x, u[2 * q].y, zi); zr = bfma2(v.y, u[2 * q].z, zr); zi = bfma2(v.y, u[2 * q].w, zi);
            zr = bfma2(v.z, u[2 * q + 1].x, zr); zi = bfma2(v.z, u[2 * q + 1].y, zi); zr = bfma2(v.w, u[2 * q + 1].z, zr); zi = bfma2(v.w, u[2 * q + 1].w, zi);
          }
          v8[4 * r] = s0 + s1; v8[4 * r + 1] = q0 + q1; v8[4 * r + 2] = bf_lo(zr) + bf_hi(zr); v8[4 * r + 3] = bf_lo(zi) + bf_hi(zi);
        }
        fold<8>(v8, 16, lane);
        if (lane == 0) { mbar_expect_tx(bar0 + r2 * 8, 4096); bulk_load(buf + r2 * 4096, drows + r2 * 2048, 4096, bar0 + r2 * 8); }
        fold<4>(v8, 8, lane); fold<2>(v8, 4, lane);
        v8[0] += __shfl_xor_sync(0xffffffffu, v8[0], 2);
        v8[0] += __shfl_xor_sync(0xffffffffu, v8[0], 1);
        SM<float>(OFF_REM + a * 64 + r2 * 32 + (lane >> 2) * 4) = v8[0];
        if (lane == 0) TIM(148 + r2 * 4 + a);
      }
    }
    bar_sync(NB_AUX, 128);
    fresh_ids();
    if (a == 0 && lane < 16) {
      const float4 v = SM<float4>(OFF_REM + lane * 16);
      const float mean = v.x * (1.f / 1024.f), rs = fast_rcp(ref_sd(fmaxf(v.y * (1.f / 1024.f) - mean * mean, 0.f)));
      pkt_st128(&p.sc->xz[cid * 16 + lane], __float_as_uint(bf16r(mean)) | (tag & 0xFFFFu), __float_as_uint(rs), pack_bf16(v.z * rs, v.w * rs), tag);
    }
    if (j == 32) { const float4 v = SM<float4>(INFO_DS); SM<float2>(INFO_WSUM) = make_float2((v.x + v.y) + (v.z + v.w), __uint_as_float(tag)); }
    if (j == 0) TIM(98);
#pragma unroll 1
    for (int r2 = 0; r2 < 2; r2++) {
      mbar_wait(bar0 + r2 * 8, 1);
      uint4 dv[8];
#pragma unroll
      for (int q = 0; q < 8; q++) dv[q] = lds128(buf + r2 * 4096 + (lane >> 4) * 2048 + q * 256 + (lane & 15) * 16);
      float s0 = __uint_as_float(zero_here()), s1 = 0.f;
#pragma unroll
      for (int q = 0; q < 8; q++) {
        const uint4 v = dv[q];
        s0 += (bf_lo(v.x) + bf_lo(v.y)) + (bf_lo(v.z) + bf_lo(v.w)); s1 += (bf_hi(v.x) + bf_hi(v.y)) + (bf_hi(v.z) + bf_hi(v.w));
      }
      s0 += s1;
#pragma unroll
      for (int o = 8; o > 0; o >>= 1) s0 += __shfl_xor_sync(0xffffffffu, s0, o);
      SM<float>(INFO_DS2 + (a * 4 + r2 * 2 + (lane >> 4)) * 4) = s0;
    }
    bar_sync(NB_AUX, 128);
    if (a == 1 && lane < 16) pkt_st64(&p.sc->dsum[cid * 16 + lane], SM<uint32_t>(INFO_DS2 + lane * 4), tag);
    if (j == 0) TIM(99);
    uint4* cpart = &p.sc->cpart[grp * 512 + eps * 64];
    pkt_clear128(cpart + (a * 8192 + lane)); pkt_clear128(cpart + (a * 8192 + lane) + 32);
    if (a == 3) { pkt_st64(&p.sc->ch[(lane >> 2) * 512 + cid * 4 + (lane & 3)], 0, 0); if (lane < 8) pkt_clear128(&p.sc->cs[cid * 8 + lane]); }
    {
      wait_clk(clk32(), XS_DELAY);
      uint2 v0, v1, cs; uint32_t n = 0;
      const uint32_t t16 = tag & 0xFFFFu;
      bool more;
#pragma unroll 1
      do {
        v0 = pkt_ld64(&p.sc->xz[tau * 256 + j]); v1 = pkt_ld64(&p.sc->xz[tau * 256 + j] + 128); cs = pkt_ld64(&p.sc->dsum[m * 1024 + eps * 128 + j]);
        more = !(__all_sync(0xffffffffu, (v0.x & 0xFFFFu) == t16 && (v1.x & 0xFFFFu) == t16 && cs.y == tag)) && ++n < SPIN_LIMIT;
        if (more) { __nanosleep(200); }
      } while (more);
      const int ro = OFF_RS + ((j & 7) >> 1) * 272 + (j >> 3) * 8 + (j & 1) * 4;
      SM<uint32_t>(ro) = v0.y ^ (m << 31); SM<uint32_t>(ro + 128) = v1.y ^ (m << 31);
      const uint32_t n0 = (v0.x >> 16) ^ 0x8000u, n1 = (v1.x >> 16) ^ 0x8000u;
      SM<uint4>(OFF_EXB + j * 16) = make_uint4(n0 | (n0 << 16), n0, 0, 0);
      SM<uint4>(OFF_EXB + 2048 + j * 16) = make_uint4(n1 | (n1 << 16), n1, 0, 0);
      const float c = 0.5f * __uint_as_float(cs.x), hi = bf16r(c), mid = bf16r(c - hi), lo = bf16r((c - hi) - mid);
      SM<uint4>(OFF_EXA + j * 16) = make_uint4((__float_as_uint(hi) >> 16) | __float_as_uint(mid), __float_as_uint(lo) >> 16, 0, 0);
      fence_async_smem();
      __syncwarp();
      if (lane == 0) mbar_arrive(BAR(B_STAT));
    }
    if (j == 0) TIM(100);
    auto all_published = [&](int half) {
      uint32_t n = 0;
#pragma unroll 1
      while (!__all_sync(0xffffffffu, ld_acquire32(&p.sc->abdone[(cid * 2 + half) * 32 + (lane & 7)]) == tag) && ++n < SPIN_LIMIT) {}
      if (lane == 0) {
        asm volatile("fence.proxy.async.global;" ::: "memory");
        mbar_arrive(BAR(B_ALL + half));
        TIM(80 + half);
      }
      __syncwarp();
    };
    if (TM_PF && j < 3) asm volatile("prefetch.tensormap [%0];" :: "l"(j == 0 ? &p.tmAbS : j == 1 ? &p.tmAbL : m ? &p.tmW1 : &p.tmW0) : "memory");
    {
      if (a == 3) {
        const uint32_t cl = poll64_warp(&p.sc->cl[cid * 16 + (lane & 3)], tag, 100);
        if (lane == 0) TIM(101);
        const bf16* wm = (m ? p.Wim : p.Wre) + tau * 256 + lane * 8;
        uint4 v[8];
#pragma unroll
        for (int i = 0; i < 8; i++) v[i] = ldg128(wm + ((__shfl_sync(0xffffffffu, cl, i >> 1) >> ((i & 1) * 16)) & 2047) * 2048);
        const int pos = cid * 4 + (lane & 3);
        const bf16* xc = p.x + ((__shfl_sync(0xffffffffu, cl, lane >> 3) >> ((lane & 4) * 4)) & 2047) * 1024 + (pos >> 3) * 16 + (pos & 7);
        const float x0 = ldbf(xc), x1 = ldbf(xc + 8), w0 = ldbf(p.wr + (pos >> 3) * 16 + (pos & 7)), w1 = ldbf(p.wr + (pos >> 3) * 16 + (pos & 7) + 8);
        if (lane < 4) SM<uint32_t>(INFO_CAND + lane * 4) = cl;
#pragma unroll
        for (int i = 0; i < 8; i++) SM<uint4>(OFF_WC + (lane >> 3) * 1024 + i * 128 + (((lane & 7) ^ i) << 4)) = v[i];
        fence_async_smem();
        __syncwarp();
        if (lane == 0) { mbar_arrive(BAR(B_WC)); TIM(102); }
        mbar_wait(BAR(B_CD), 0);
        wait_clk(clk32(), CP_DELAY);
        uint32_t n = 0;
        bool more;
#pragma unroll 1
        do {
          uint32_t bad = 0;
#pragma unroll
          for (int i = 0; i < 8; i++) v[i] = pkt_ld128(&p.sc->cpart[((lane >> 3) * 16 + ((lane >> 2) & 1)) * 512 + pos] + i * 1024);
#pragma unroll
          for (int i = 0; i < 8; i++) chk_code(bad, v[i], c0, c1);
          more = !(!__any_sync(0xffffffffu, bad & 1)) && ++n < SPIN_LIMIT;
          if (more) { __nanosleep(200); }
        } while (more);
        float y[4] = {0.f, 0.f, 0.f, 0.f};
#pragma unroll
        for (int i = 0; i < 8; i++) { y[0] += no_bit(v[i].x); y[2] += no_bit(v[i].y); y[1] += no_bit(v[i].z); y[3] += no_bit(v[i].w); }
#pragma unroll
        for (int i = 0; i < 4; i++) y[i] = bf16r(y[i]);
        __syncwarp();
        fold<4>(y, 4, lane);
        const uint32_t hp = pack_bf16(x0 + bf16r(y[0]), x1 + bf16r(y[1]));
        pkt_st64(&p.sc->ch[(lane >> 2) * 512 + pos], hp, tag);
        float st[3] = {bf_lo(hp) + bf_hi(hp), bf_lo(hp) * bf_lo(hp) + bf_hi(hp) * bf_hi(hp), bf_lo(hp) * w0 + bf_hi(hp) * w1};
#pragma unroll
        for (int o = 1; o < 4; o <<= 1) {
#pragma unroll
          for (int i = 0; i < 3; i++) st[i] += __shfl_xor_sync(0xffffffffu, st[i], o);
        }
        if ((lane & 3) == 0) pkt_st128(&p.sc->cs[cid * 8 + (lane >> 2)], with_bit(st[0], c0), with_bit(st[1], c1), __float_as_uint(st[2]), tag);
        if (lane == 0) TIM(119);
      }
      if (a < 2) {
        uint32_t* fl = lane < 2 ? &p.sc->abflag[(cid * 4 + 2 * a + lane) * 32] : &p.sc->abdone[(((cid & 15) + (lane & 7) * 16) * 2 + a) * 32 + tau];
        if (lane == 0) {
          if (a == 1) mbar_wait(BAR(B_SD), 0);
          const uint32_t t1 = clk32();
#pragma unroll 1
          for (int i = 2 * a; i < 2 + 6 * a; i++) {
            const int w = i & 1, c = i >> 1;
            if (a == 1) wait_clk(t1, HI_DELAY + (i - 2) * HI_PACE);
            mbar_wait(BAR(B_EP + w * 4 + c), 0);
            TIM(64 + i);
            fence_async_smem();
            tma_store_2d(&p.tmAbS, sb + c * ST_BYTES + w * 8192, tau * 256 + c * 64, abrow + w * 64);
            if (w) { bulk_commit(); bulk_wait_all(); mbar_arrive(BAR(B_SD + c)); }
          }
          TIM(72 + a * 2);
          asm volatile("fence.proxy.async.global;" ::: "memory");
          asm volatile("st.release.gpu.global.b32 [%0], %1;" :: "l"(fl), "r"(tag) : "memory");
          TIM(73 + a * 2);
        }
        __syncwarp();
        if ((lane == 1 && a == 0) || (lane >> 3) == 1) st_relaxed32(fl, tag);
        if (a == 0) __nanosleep(ALL_NS);
        else if (elect_one()) {
          uint32_t n = 0;
#pragma unroll 1
          while (ld_acquire32(&p.sc->abflag[(((cid + 16) & 127) * 4 + 2) * 32]) != tag && ++n < SPIN_LIMIT) {}
          asm volatile("fence.proxy.async.global;" ::: "memory");
#pragma unroll 1
          for (int i = 0; i < DELEG; i++) {
            mbar_wait(BAR(B_E23 + i), 0);
            tma_load_2d(sb + ((i + 3) & 3) * ST_BYTES, &p.tmAbL, BAR(B_FULL + ((i + 3) & 3)), (tau * 256 + 320 + i * 64) & 2047, abrow);
            TIM(82 + i);
          }
          if (DELEG < 3) mbar_arrive(BAR(B_E23 + 2));
        }
        __syncwarp();
        all_published(a);
      } else if (a == 2) {
        const uint32_t* fl = &p.sc->abflag[(((cid + 16 + 16 * (lane & 1)) & 127) * 4 + (lane & 1)) * 32];
        mbar_wait(BAR(B_SD), 0);
        __nanosleep(LO_NS);
        uint32_t n = 0, seen = 0;
#pragma unroll 1
        for (int c = 0; c < 4; c++) {
          const uint32_t n0 = n;
#pragma unroll 1
          while (c < 2 && !((seen >> c) & 1) && ++n < SPIN_LIMIT) seen = __ballot_sync(0xffffffffu, ld_acquire32(fl) == tag);
          if (elect_one()) {
            mbar_wait(BAR(B_SD + c), 0); mbar_wait(BAR(c < 3 ? B_FULL + c : B_EMPTY), 0);
            if (c == 2) mbar_wait(BAR(B_ALL), 0);
            if (n != n0) asm volatile("fence.proxy.async.global;" ::: "memory");
            tma_load_2d(sb + c * ST_BYTES, &p.tmAbL, BAR(B_FULL + c), k_col(tau, 4 + c), abrow);
            TIM(130 + c);
          }
          __syncwarp();
        }
      }
      __syncwarp();
    }
    mbar_wait(BAR(B_CD), 0);
    const uint64_t pol_ef = policy_evict_first();
    auto load_unit = [&](int v) {
      if (elect_one()) {
        const uint32_t dst = buf + (v & 1) * 4096, bar = bar0 + (v & 1) * 8;
        mbar_expect_tx(bar, 4096);
        if (v < 8) {
          LOAD_F(dst, &p.tmG, bar, fc, m * 512 + (a * 8 + v) * 16);
          LOAD_F(dst + 2048, &p.tmU, bar, fc, m * 512 + (a * 8 + v) * 16);
        } else LOAD_F(dst, &p.tmDn, bar, a * 256, src * 32 + (v - 8) * 8);
      }
    };
    if (TM_PF && j < 3) asm volatile("prefetch.tensormap [%0];" :: "l"(j == 0 ? &p.tmG : j == 1 ? &p.tmU : &p.tmDn) : "memory");
    if (ffn && (!LU0_LATE || a == 1)) load_unit(0);
    if (a != 1) {
      bar_sync(NB_SEL, 96);
      wait_clk(clk32(), CS_DELAY);
      fresh_ids();
      if (a == 0 && lane < 8) {
        if (lane == 0) mbar_expect_tx(BAR(B_CH), 16384);
        bulk_load(sb + OFF_AUX + 4096 + (lane >> 1) * 8192 + (lane & 1) * 2048, &p.sc->ch[lane * 512 + m * 256], 2048, BAR(B_CH));
      }
      const int j3 = a ? j - 32 : j;
      uint4 v[11]; uint32_t n = 0;
      bool more;
#pragma unroll 1
      do {
#pragma unroll
        for (int i = 0; i < 11; i++) v[i] = pkt_ld128(&p.sc->cs[j3] + (i < 10 || a < 3 ? i * 96 : 0));
        uint32_t bad = 0;
#pragma unroll
        for (int i = 0; i < 11; i++) { chk(bad, v[i].x, c0); chk(bad, v[i].y, c1); }
        bad &= 1;
#pragma unroll
        for (int i = 0; i < 11; i++) chk(bad, v[i].w, tag);
        more = __any_sync(0xffffffffu, bad) && ++n < SPIN_LIMIT;
        if (more) __nanosleep(200);
      } while (more);
      if (j == 0) TIM(97);
      if (ffn && LU0_LATE) load_unit(0);
      float st[3] = {0.f, 0.f, 0.f};
      if (a < 3) { st[0] = no_bit(v[10].x); st[1] = no_bit(v[10].y); st[2] = __uint_as_float(v[10].z); }
#pragma unroll
      for (int i = 0; i < 10; i++) { st[0] += no_bit(v[i].x); st[1] += no_bit(v[i].y); st[2] += __uint_as_float(v[i].z); }
#pragma unroll
      for (int o = 8; o < 32; o <<= 1) {
#pragma unroll
        for (int i = 0; i < 3; i++) st[i] += __shfl_xor_sync(0xffffffffu, st[i], o);
      }
      if (lane < 8) SM<float4>(OFF_XS + ((j3 >> 5) * 8 + lane) * 16) = make_float4(st[0], st[1], st[2], 0.f);
      bar_sync(NB_SEL, 96);
      const float4 f0 = SM<float4>(OFF_XS + (lane & 7) * 16), f1 = SM<float4>(OFF_XS + 128 + (lane & 7) * 16), f2 = SM<float4>(OFF_XS + 256 + (lane & 7) * 16);
      const float mu = ((f0.x + f1.x) + f2.x) * (1.f / 1024.f);
      float mb = bf16r(mu), inv = fast_rcp(ref_sd(fmaxf(((f0.y + f1.y) + f2.y) * (1.f / 1024.f) - mu * mu, 0.f)));
      const uint32_t kk = make_key(bf16r((((f0.z + f1.z) + f2.z) - mb * SM<float>(INFO_WSUM)) * inv), SM<uint16_t>(INFO_CAND + (lane & 7) * 2));
      const uint32_t key = __reduce_max_sync(0xffffffffu, kk);
      const int win = __ffs(__ballot_sync(0xffffffffu, kk == key)) - 1;
      mb = __shfl_sync(0xffffffffu, mb, win); inv = __shfl_sync(0xffffffffu, inv, win);
      if (j == 0) { SM<uint2>(INFO_KEY) = make_uint2(key, win); SM<float2>(INFO_LN) = make_float2(mb, inv); }
      mbar_wait(BAR(B_CH), 0);
      bar_sync(NB_SEL, 96);
#pragma unroll 1
      for (int i = j3; i < 128; i += 96) {
        uint4 r = lds128(sb + OFF_AUX + 4096 + (win >> 1) * 8192 + (win & 1) * 2048 + i * 16);
#pragma unroll 1
        while ((r.y != tag || r.w != tag) && ++n < SPIN_LIMIT) r = pkt_ld128(&p.sc->ch[win * 512 + m * 256 + 2 * i]);
        auto ln = [&](float h) { return bf16r(bf16r(h - mb) * inv); };
        const int d = (i >> 2) * 16 + (i & 3) * 2;
        SM<float2>(OFF_XS + d * 4) = make_float2(ln(bf_lo(r.x)), ln(bf_lo(r.z)));
        SM<float2>(OFF_XS + (d + 8) * 4) = make_float2(ln(bf_hi(r.x)), ln(bf_hi(r.z)));
      }
      __syncwarp();
    }
    bar_sync(NB_AUX, 128);
    if (j == 0) {
      mbar_arrive(BAR(B_INFO)); TIM(103);
      if (cid == 0) st_relaxed32(&p.sc->epoch, tag);
    }
    const uint32_t t2 = clk32();
    fresh_ids();
    uint2 hp2 = make_uint2(0, 0);
    const uint2* hpp = &p.sc->ch[SM<uint32_t>(INFO_KEY + 4) * 512 + (cid >> 1) * 8 + (lane & 7)];
    if (a == 3) { hp2 = pkt_ld64(hpp); if (lane == 0) asm volatile("prefetch.tensormap [%0];" :: "l"(&p.tmY) : "memory"); }
    if (!ffn) {
      wait_clk(t2, YPART_DELAY);
    } else {
      load_unit(1);
      const int r = lane >> 3;
      float acc[8] = {0.f, 0.f, 0.f, 0.f, 0.f, 0.f, 0.f, 0.f};
#pragma unroll 1
      for (int v = 0; v < 8; v++) {
        const uint4 x0 = lds128(sb + OFF_XS + ((a * 8 + v) * 16 + (r & 1) * 8) * 4), x1 = lds128(sb + OFF_XS + ((a * 8 + v) * 16 + (r & 1) * 8 + 4) * 4);
        const float xv[8] = {__uint_as_float(x0.x), __uint_as_float(x0.y), __uint_as_float(x0.z), __uint_as_float(x0.w), __uint_as_float(x1.x), __uint_as_float(x1.y), __uint_as_float(x1.z), __uint_as_float(x1.w)};
        mbar_wait(bar0 + (v & 1) * 8, (v >> 1) & 1);
        gemv8x8<128>(acc, buf + (v & 1) * 4096 + r * 1024 + (lane & 7) * 16, xv);
        fence_regs(acc);
        __syncwarp();
        wait_clk(t2, v * UNIT_PACE);
        load_unit(v + 2);
        if (j == 0) TIM(104 + v);
      }
      pkt_clear128(&p.sc->ypart[(a * NSRC + src) * 64 + lane * 2]); pkt_clear128(&p.sc->ypart[(a * NSRC + src) * 64 + lane * 2] + 1);
      fold<8>(acc, 8, lane);
      bar_sync(NB_AUX, 128);
      SM<float4>(OFF_XS + (a * 128 + (r >> 1) * 64 + (lane & 7) * 8 + (r & 1) * 4) * 4) = make_float4(acc[0], acc[1], acc[2], acc[3]);
      bar_sync(NB_AUX, 128);
      auto psum = [&](int i) { return (SM<float>(OFF_XS + i * 4) + SM<float>(OFF_XS + (128 + i) * 4)) + (SM<float>(OFF_XS + (256 + i) * 4) + SM<float>(OFF_XS + (384 + i) * 4)); };
      if (a < 2) st_async_b32(mapa(sb + OFF_REM + j * 4, m ^ 1), mapa(BAR(B_GUX), m ^ 1), __float_as_uint(psum(a * 64 + (m ^ 1) * 32 + lane)));
      const float og = psum(m * 32 + lane), ou = psum(64 + m * 32 + lane);
      mbar_wait(BAR(B_GUX), 0);
      const float rg = SM<float>(OFF_REM + lane * 4), ru = SM<float>(OFF_REM + 128 + lane * 4);
      const float act = swiglu(m ? rg + og : og + rg, m ? ru + ou : ou + ru);
      if (j == 0) TIM(112);
      float y[8] = {0.f, 0.f, 0.f, 0.f, 0.f, 0.f, 0.f, 0.f};
#pragma unroll 1
      for (int v = 8; v < 12; v++) {
        float av[8];
#pragma unroll
        for (int i = 0; i < 8; i++) av[i] = __shfl_sync(0xffffffffu, act, (v - 8) * 8 + i);
        mbar_wait(bar0 + (v & 1) * 8, (v >> 1) & 1);
        gemv8x8<512>(y, buf + (v & 1) * 4096 + lane * 16, av);
        fence_regs(y);
        __syncwarp();
        if (v < 10) load_unit(v + 2);
        if (j == 0) TIM(105 + v);
      }
      fresh_ids();
      uint4* ypart = &p.sc->ypart[(a * NSRC + src) * 64 + lane * 2];
      pkt_st128(ypart, with_bit(y[0], c0), with_bit(y[1], c1), with_bit(y[2], c0), with_bit(y[3], c1));
      pkt_st128(ypart + 1, with_bit(y[4], c0), with_bit(y[5], c1), with_bit(y[6], c0), with_bit(y[7], c1));
      if (lane == 0) TIM(160 + a);
      __nanosleep(ROW_NS);
    }
    if (a == 3) {
      const uint32_t hh = __all_sync(0xffffffffu, hp2.y == tag) ? hp2.x : poll64_warp(&p.sc->ch[SM<uint32_t>(INFO_KEY + 4) * 512 + (cid >> 1) * 8 + (lane & 7)], tag, 100);
      const uint32_t key = SM<uint32_t>(INFO_KEY);
      const float h = m ? bf_hi(hh) : bf_lo(hh), hn = bf16r(bf16r(h - SM<float>(INFO_LN)) * SM<float>(INFO_LN + 4));
      float sig = sigmoid_bf(key_val(key));
      bf16* op = p.out + (key_row(key) * 1024 + cid * 8 + (lane & 7));
      asm volatile("" : "+f"(sig), "+l"(op));
      uint4 v[7]; uint32_t n = 0;
      bool more;
#pragma unroll 1
      do {
        if (elect_one()) { mbar_expect_tx(bar0, NSRC * 32); tma_load_2d(buf, &p.tmY, bar0, (cid & 31) * 16, (cid >> 5) * NSRC); }
        mbar_wait(bar0, n & 1);
        uint32_t bad = 0;
#pragma unroll
        for (int i = 0; i < 7; i++) { v[i] = lds128(buf + i * 512 + lane * 16); chk_code(bad, v[i], c0, c1); }
        more = __any_sync(0xffffffffu, bad & 1) && ++n < SPIN_LIMIT;
        if (more) __nanosleep(Y_NS);
      } while (more);
      if (lane == 0) TIM(164);
      float y[4] = {0.f, 0.f, 0.f, 0.f};
#pragma unroll
      for (int i = 0; i < 7; i++) { y[0] += no_bit(v[i].x); y[1] += no_bit(v[i].y); y[2] += no_bit(v[i].z); y[3] += no_bit(v[i].w); }
      fold<4>(y, 16, lane); fold<2>(y, 8, lane);
      y[0] += __shfl_xor_sync(0xffffffffu, y[0], 4);
      y[0] += __shfl_xor_sync(0xffffffffu, y[0], 2);
      const float ys = __shfl_sync(0xffffffffu, y[0], (lane & 3) * 8 + ((lane >> 2) & 1));
      if (lane < 8) st_bf16(op, routed_out(h, hn, ys, sig));
      if (lane == 0) { TIM(118); pkt_st64(&p.sc->rdone[cid], 0, tag); }
    }
  } else {
    reg_inc<216>();
    cluster_wait();
    const uint32_t sb = __shfl_sync(0xffffffffu, smem_u32(smem_raw), 0);
    auto BAR = [&](int i) { return sb + OFF_BAR + 8 * i; };
    const int w = warp >> 2, wi = warp & 3, t = tid & 127;
    const int turn_me = NB_TURN0 + w, turn_other = NB_TURN1 - w;
    const uint64_t dA0 = make_desc(sb + w * 8192);
    uint64_t dA, dB;
    int tau, eps, m, grp, abrow, fc, src;
    bool ffn;
    const CUtensorMap* tmD; const CUtensorMap* tmW;
    auto new_desc = [&](int salt) {
      const uint32_t z = salt < 0 ? uniform_zero_here() : salt & blockIdx.y;
      dA = dA0 + z; dB = dA0 + (z + ((A_BYTES - w * 8192) >> 4));
      const int c = cid + z;
      tau = c >> 4; eps = (c >> 1) & 7; m = c & 1; grp = tau * 2 + m; abrow = m * 1024 + eps * 128;
      ffn = eps > 0; fc = (tau * 7 + eps - 1) * 64; src = (fc >> 5) + m;
      tmD = &p.tmD0 + m; tmW = &p.tmW0 + m;
    };
    constexpr int SL = ST_BYTES >> 4;
    float acc[128];
#pragma unroll
    for (int i = 0; i < 128; i++) acc[i] = 0.f;
    if (w == 1) bar_arrive(NB_TURN0, 256);
    auto full = [&](int k) { mbar_wait(BAR(B_FULL + (k & 3)), (k >> 2) & 1); CT(64 + k); };
    const uint64_t pol_ef = policy_evict_first();
    auto refill_g2 = [&](int k, int mode) {
      if (warp == 4) {
        if (elect_one()) {
          const int s = k & 3, s0 = k_col(tau, k - 12);
          TIM(k + 4);
          mbar_expect_tx(BAR(B_FULL + s), mode ? ST_BYTES : B_BYTES);
          if (k == 19) mbar_arrive(BAR(B_EMPTY));
          LOAD_W(sb + s * ST_BYTES + A_BYTES, tmW, BAR(B_FULL + s), s0, grp * 128);
          LOAD_W(sb + s * ST_BYTES + A_BYTES + 16384, tmW, BAR(B_FULL + s), s0, (grp ^ 1) * 128);
          if (mode == 2) tma_load_2d(sb + s * ST_BYTES, &p.tmAbL, BAR(B_FULL + s), s0, abrow);
        }
        __syncwarp();
      }
    };
    auto mma_ss = [&](int k) {
#pragma unroll
      for (int kk = 0; kk < 4; kk++) wgmma_n256(acc, dA + (k & 3) * SL + kk * 2, dB + (k & 3) * SL + kk * 2);
    };
    const CUtensorMap* rf_tm; uint32_t rf_dst; int rf_row, rf_c; bool rf_on;
    auto refill = [&](int s) {
      if (rf_on) {
        if (elect_one()) tma_load_2d(rf_dst + s * ST_BYTES, rf_tm, BAR(B_FULL + s), rf_c, rf_row);
        __syncwarp();
      }
      if (tid == 224) mbar_expect_tx(BAR(B_FULL + s), ST_BYTES);
    };
    const bf16* pf; int pf_step; bool pf_on;
    auto pf_ffn = [&](int v) {
      pf_on = ffn && v >= 0 && v < 12;
      pf = v < 8 ? ((lane & 16) ? p.wup : p.wgate) + (m * 512 + (wi * 8 + v) * 16 + (lane & 15)) * 3584 + fc : p.wdown + (src * 32 + (v - 8) * 8) * 1024 + t * 64;
      pf_step = v < 8 ? 16 * 3584 : 8192;
    };
    auto prefetch = [&](int s) { if (pf_on && (wi >> 1) == (s & 1)) prefetch_l2(pf + (s >> 1) * pf_step); };
    auto kstep = [&](int k) {
      full(k);
      bar_sync(turn_me, 256);
      wgmma_fence();
      mma_ss(k);
      wgmma_commit();
      bar_arrive(turn_other, 256);
    };

    new_desc(64);
    rf_on = (warp >> 1) == 2;
    rf_tm = wi ? tmD : &p.tmX; rf_dst = wi ? sb : sb + A_BYTES; rf_row = wi ? eps * 128 : tau * 256;
#pragma unroll 1
    for (int k4 = 0; k4 < 12; k4 += 4) {
#pragma unroll
      for (int s = 0; s < 4; s++) {
        kstep(k4 | s);
        if (s == 0) {
          if (w == 0) pf_ffn((k4 >> 1) - 2);
          else {
            pf_on = W_PF && (k4 == 8 || (W_PF > 1 && k4 == 4 && (lane & 7) < 3));
            pf = (m ? p.Wim : p.Wre) + (tau * 256 + eps * 32 + wi * 4 + (lane >> 3)) * 2048 + k_col(tau, (lane & 7) + (W_PF > 1 && k4 == 8 ? 3 : 0));
            pf_step = 16 * 2048;
          }
        }
        rf_c = (k4 + s + 4) * 64;
        prefetch(s);
        if (s == 3) new_desc(k4);
        if (s == 0 || s == 3) pf += zero_here();
        wgmma_wait<0>();
        refill(s);
      }
    }
    uint32_t R[64];
    auto load_rs = [&](auto gi) {
      const uint32_t rsa = sb + OFF_RS + (lane & 3) * 272;
#pragma unroll
      for (int i = 4 * decltype(gi)::value; i < 4 * decltype(gi)::value + 4; i++) { const uint4 v = lds128(rsa + i * 16); R[4 * i] = v.x; R[4 * i + 1] = v.y; R[4 * i + 2] = v.z; R[4 * i + 3] = v.w; }
    };
    kstep(12);
    mbar_wait(BAR(B_STAT), 0);
    CT(1);
    load_rs(std::integral_constant<int, 0>());
    load_rs(std::integral_constant<int, 1>());
    wgmma_wait<0>(); refill_g2(12, 0);
    load_rs(std::integral_constant<int, 3>());
    auto mma_h = [&](float (&d)[64], int s, int half) {
#pragma unroll
      for (int kk = 0; kk < 4; kk++) wgmma_n128(d, dA + s * SL + kk * 2, dB + s * SL + half * 1024 + kk * 2);
    };
    const int rho = 16 * wi + (lane & 15);
    const uint32_t arow = sb + w * 8192 + rho * 128;
    auto convert = [&](auto cc, float (&d)[64]) {
      const float z = __uint_as_float(zero_here());
#pragma unroll
      for (int jj = 8 * decltype(cc)::value; jj < 8 * decltype(cc)::value + 8; jj++) {
        const float r0 = __uint_as_float(R[2 * jj]), r1 = __uint_as_float(R[2 * jj + 1]);
        const float* ac = &d[4 * (jj & 15)];
        R[2 * jj] = pack_bf16(fmaf(ac[0], r0, z), fmaf(ac[1], r1, z));
        R[2 * jj + 1] = pack_bf16(fmaf(ac[2], r0, z), fmaf(ac[3], r1, z));
      }
    };
    auto put = [&](auto cc) {
      constexpr int c = decltype(cc)::value;
#pragma unroll
      for (int jj = 8 * c; jj < 8 * c + 8; jj += 2)
        stsm_x4(arow + c * ST_BYTES + ((((jj & 7) + (lane >> 4)) ^ (rho & 7)) << 4), R[2 * jj], R[2 * jj + 1], R[2 * jj + 2], R[2 * jj + 3]);
      __syncwarp();
      if (lane == 0) mbar_arrive(BAR(B_EP + w * 4 + c));
    };
    {
      float lo[64], hi[64];
      fence_regs(acc);
#pragma unroll
      for (int i = 0; i < 64; i++) asm volatile("mov.b32 %0, %1;" : "=f"(lo[i]) : "f"(acc[i]));
#pragma unroll
      for (int i = 0; i < 64; i++) asm volatile("mov.b32 %0, %1;" : "=f"(hi[i]) : "f"(acc[64 + i]));
      const uint64_t dEA = make_desc_noswz(sb + OFF_EXA + w * 1024), dEB = make_desc_noswz(sb + OFF_EXB);
      full(13); full(14);
      bar_sync(turn_me, 256);
      wgmma_fence();
      mma_h(lo, 1, 0); mma_h(lo, 2, 0);
      wgmma_commit();
      bar_arrive(turn_other, 256);
      new_desc(ND1);
      full(15);
      bar_sync(turn_me, 256);
      wgmma_fence();
      mma_h(lo, 3, 0);
      wgmma_n128(lo, dEA, dEB);
      wgmma_commit();
      mma_h(hi, 1, 1);
      wgmma_commit();
      bar_arrive(turn_other, 256);
      new_desc(ND2);
      wgmma_wait<1>();
      fence_regs(lo);
      CT(15);
      convert(std::integral_constant<int, 0>(), lo); put(std::integral_constant<int, 0>());
      convert(std::integral_constant<int, 1>(), lo);
      wgmma_wait<0>(); refill_g2(13, 0);
      if (!PUT1_LATE) put(std::integral_constant<int, 1>());
      bar_sync(turn_me, 256);
      wgmma_fence();
      mma_h(hi, 2, 1);
      wgmma_commit();
      mma_h(hi, 3, 1);
      wgmma_n128(hi, dEA, dEB + 128);
      wgmma_commit();
      bar_arrive(turn_other, 256);
      load_rs(std::integral_constant<int, 2>());
      if (PUT1_LATE) put(std::integral_constant<int, 1>());
      wgmma_wait<1>(); refill_g2(14, 0);
      wgmma_wait<0>(); refill_g2(15, 0);
      fence_regs(hi);
      CT(2);
      convert(std::integral_constant<int, 3>(), hi);
      if (!PUT3_LATE) put(std::integral_constant<int, 3>());
      convert(std::integral_constant<int, 2>(), hi);
    }
    CT(3);
    float cc[4];
    auto cand_mma = [&]() {
      const uint64_t dC = make_desc(sb + OFF_WC);
      wgmma_n8_rs<0>(cc, R, dC);
#pragma unroll
      for (int i = 1; i < 12; i++) wgmma_n8_rs<1>(cc, R + 4 * i, dC + (i >> 2) * 64 + (i & 3) * 2);
#pragma unroll
      for (int kk = 0; kk < 4; kk++) wgmma_n8(cc, dA + 3 * SL + kk * 2, dC + 192 + kk * 2);
      wgmma_commit();
    };
    auto cand_pub = [&]() {
      fence_regs(cc);
      const uint32_t cd = code_of(SM<uint32_t>(INFO_TAG));
      if (t == 0) mbar_arrive(BAR(B_CD));
      pkt_st128(&p.sc->cpart[((lane & 3) * 16 + grp) * 512 + eps * 64 + warp * 8 + (lane >> 2)], with_bit(cc[0], cd), with_bit(cc[1], cd >> 1), with_bit(cc[2], cd), with_bit(cc[3], cd >> 1));
      CT(5);
    };
    new_desc(ND3);
    if (CAND_EARLY) { fence_async_smem(); mbar_wait(BAR(B_WC), 0); CT(4); }
    full(16);
    if (!SPLIT17) full(17);
    bar_sync(turn_me, 256);
    wgmma_fence();
    if (CAND_EARLY) cand_mma();
    wgmma_n256_rs_init(acc, R, dB);
#pragma unroll
    for (int kk = 1; kk < 4; kk++) wgmma_n256_rs<1>(acc, R + 4 * kk, dB + kk * 2);
    wgmma_commit();
    if (PUT3_LATE) put(std::integral_constant<int, 3>());
    if (SPLIT17) { full(17); wgmma_fence(); }
#pragma unroll
    for (int kk = 0; kk < 4; kk++) wgmma_n256_rs<1>(acc, R + 16 + 4 * kk, dB + SL + kk * 2);
    wgmma_commit();
    bar_arrive(turn_other, 256);
    if (CAND_EARLY) { wgmma_wait<2>(); put(std::integral_constant<int, 2>()); cand_pub(); }
    else put(std::integral_constant<int, 2>());
    wgmma_wait<1>(); refill_g2(16, 1);
    wgmma_wait<0>(); refill_g2(17, 1);
    if (!CAND_EARLY) { fence_async_smem(); mbar_wait(BAR(B_WC), 0); CT(4); }
    full(18);
    bar_sync(turn_me, 256);
    wgmma_fence();
    if (!CAND_EARLY) cand_mma();
#pragma unroll
    for (int kk = 0; kk < 4; kk++) wgmma_n256_rs<1>(acc, R + 32 + 4 * kk, dB + 2 * SL + kk * 2);
    wgmma_commit();
    bar_arrive(turn_other, 256);
    if (!CAND_EARLY) { wgmma_wait<1>(); cand_pub(); }
    wgmma_wait<0>(); refill_g2(18, 1);
    kstep(19);
    new_desc(68);
    wgmma_wait<0>(); refill_g2(19, 1);
    const int g = lane >> 2, q = lane & 3;
    uint4 ha[4], hb[4];

    rf_on = w == 1 && wi < 3;
    rf_tm = wi == 2 ? &p.tmAbL : tmW; rf_dst = wi == 2 ? sb : sb + A_BYTES + wi * 16384; rf_row = wi == 2 ? abrow : (grp ^ wi) * 128;
    rf_c = k_col(tau, 7);
#pragma unroll 1
    for (int k4 = 20; k4 < 44; k4 += 4) {
#pragma unroll
      for (int s = 0; s < 4; s++) {
        kstep(k4 | s);
        if (s == 0) {
          if (w == 0) { pf_ffn((k4 >> 1) - PF2_K / 2 + 4); pf_on = pf_on && k4 >= PF2_K; }
          else {
            pf_on = k4 == XPF_K;
            pf = p.x + (grp * 128 + (t >> 1)) * 1024 + eps * 128 + (t & 1) * 64;
            pf_step = 64 * 1024;
          }
        }
        rf_c = k_next(rf_c, k4 + s - 12);
        if (s == 0 && k4 == 20 && warp == 6) mbar_wait(BAR(B_ALL), 0);
        if (DELEG < 3 && s == DELEG - 1 && k4 == 24 && warp == 6) mbar_wait(BAR(B_E23 + 2), 0);
        if (s == 2 && k4 == 24 && warp == 6) mbar_wait(BAR(B_ALL + 1), 0);
        prefetch(s);
        if (s == 3) new_desc(k4);
        if (s == 0 || s == 3) pf += zero_here();
        wgmma_wait<0>();
        if (((s == 3 && k4 == 20) || (s < DELEG - 1 && k4 == 24)) && warp == 6) { if (lane == 0) mbar_arrive(BAR(B_E23 + ((s + 1) & 3))); }
        else refill(s);
      }
    }
    const int row0 = grp * 128 + warp * 16 + g;
    kstep(44);
    uint4* hst = &p.sc->hstat[grp * 1024 + warp * 16 + g];
    if (q == (g >> 1)) { pkt_clear128(hst + eps * 128); pkt_clear128(hst + eps * 128 + 8); }
    mbar_wait(BAR(B_INFO), 0);
    uint4 wv[4];
#pragma unroll
    for (int i = 0; i < 4; i++) wv[i] = lds128(sb + ((g & 1) ? OFF_WR + (i * 4 + q) * 16 : INFO_ONES));
    const uint4 info = lds128(sb + OFF_INFO);
#pragma unroll
    for (int i = 0; i < 4; i++) { ha[i] = ldg128(p.x + (row0 * 1024 + eps * 128 + q * 8) + i * 32); hb[i] = ldg128(p.x + (row0 * 1024 + eps * 128 + q * 8) + 8192 + i * 32); }
    wgmma_wait<0>();
    if (tid == 128) mbar_arrive_remote(mapa(BAR(B_PEER), m ^ 1));
    uint32_t hp[32];
    bf16* op; uint4* hpub;
    uint32_t cd, ast, ald, zr;
    auto swz = [](int row) { return ((row & 1) << 2) | ((row >> 1) & 3); };
    {
      float as[64], ak[64];
      fence_regs(acc);
#pragma unroll
      for (int i = 0; i < 64; i++) asm volatile("mov.b32 %0, %1;" : "=f"(as[i]) : "f"(acc[64 + i]));
#pragma unroll
      for (int i = 0; i < 64; i++) asm volatile("mov.b32 %0, %1;" : "=f"(ak[i]) : "f"(acc[i]));
      full(45); full(46);
      bar_sync(turn_me, 256);
      wgmma_fence();
      mma_h(as, 1, 1); mma_h(as, 2, 1);
      wgmma_commit();
      bar_arrive(turn_other, 256);
      full(47);
      bar_sync(turn_me, 256);
      wgmma_fence();
      mma_h(as, 3, 1);
      wgmma_commit();
      mma_h(ak, 1, 0);
      wgmma_commit();
      bar_arrive(turn_other, 256);
      const uint32_t rx = mapa(sb + OFF_RECV + w * 16384 + t * 16, m ^ 1), rb = mapa(BAR(B_XCH + w), m ^ 1);
      mbar_wait(BAR(B_PEER), 0);
      wgmma_wait<1>();
      fence_regs(as);
      CT(6);
#pragma unroll
      for (int i = 0; i < 8; i++) {
        const float* ac = &as[8 * i];
        st_async_v4(rx + i * 2048, rb, pack_bf16(ac[0], ac[1]), pack_bf16(ac[2], ac[3]), pack_bf16(ac[4], ac[5]), pack_bf16(ac[6], ac[7]));
      }
      CT(7);
      bar_sync(turn_me, 256);
      wgmma_fence();
      mma_h(ak, 2, 0); mma_h(ak, 3, 0);
      wgmma_commit();
      if (w == 0) bar_arrive(turn_other, 256);
      op = p.out + row0 * 1024 + eps * 128 + q * 8;
      hpub = hst + eps * 128; hst += q * 256;
      cd = code_of(info.y);
      ast = sb + w * ST_BYTES + (8 * (lane >> 4) + (lane & 7)) * 128 + (((2 * wi + ((lane >> 3) & 1)) ^ swz(lane & 7)) << 4);
      ald = sb + (warp * 16 + g) * 128 + ((q ^ swz(g)) << 4);
      asm volatile("" : "+l"(op), "+l"(hpub), "+l"(hst), "+r"(cd), "+r"(ast), "+r"(ald));
      zr = zero_here();
#pragma unroll
      for (int i = 0; i < 4; i++) { ha[i].x += zr; hb[i].x += zr; asm volatile("" : "+r"(ha[i].x), "+r"(hb[i].x)); }
      ast += (uint32_t)(clock64() >> 32) & zr;
      mbar_wait(BAR(B_XCH + w), 0);
      CT(9);
#pragma unroll
      for (int i = 0; i < 8; i++) { const uint4 v = lds128(sb + OFF_RECV + w * 16384 + t * 16 + i * 2048); hp[4 * i] = v.x; hp[4 * i + 1] = v.y; hp[4 * i + 2] = v.z; hp[4 * i + 3] = v.w; }
      wgmma_wait<0>();
      fence_regs(ak);
      CT(10);
#pragma unroll
      for (int i = 0; i < 32; i++) hp[i] = badd2(pack_bf16(ak[2 * i], ak[2 * i + 1]), hp[i]);
    }
#pragma unroll
    for (int jj = 0; jj < 16; jj += 2) stsm_x4_t(ast + jj * 1024, hp[2 * jj], hp[2 * jj + 1], hp[2 * jj + 2], hp[2 * jj + 3]);
    tag = info.y;
    bar_sync(NB_BOTH, 256);
    CT(11);
    uint4 v[4];
    auto fetch = [&]() { v[0] = pkt_ld128(hst); v[1] = pkt_ld128(hst + 128); v[2] = pkt_ld128(hst + 8); v[3] = pkt_ld128(hst + 136); };
    float st[6];
    {
      uint4 ya[4], yb[4];
#pragma unroll
      for (int i = 0; i < 4; i++) {
        const uint32_t ad = (ald ^ ((i & 1) << 6)) + (i >> 1) * ST_BYTES;
        ya[i] = lds128(ad); yb[i] = lds128(ad + 1024);
      }
      fetch();
      const float z = __uint_as_float((uint32_t)(clock64() >> 32) & zr);
      float sw[2][4], qa[2][4], qb[2][4];
#pragma unroll
      for (int i = 0; i < 8; i++) { sw[i >> 2][i & 3] = i ? 0.f : z; qa[i >> 2][i & 3] = 0.f; qb[i >> 2][i & 3] = 0.f; }
#pragma unroll
      for (int i = 0; i < 4; i++) {
        ha[i] = make_uint4(badd2(ha[i].x, ya[i].x), badd2(ha[i].y, ya[i].y), badd2(ha[i].z, ya[i].z), badd2(ha[i].w, ya[i].w));
        hb[i] = make_uint4(badd2(hb[i].x, yb[i].x), badd2(hb[i].y, yb[i].y), badd2(hb[i].z, yb[i].z), badd2(hb[i].w, yb[i].w));
        mma16816(sw[0], ha[i].x, hb[i].x, ha[i].y, hb[i].y, wv[i].x, wv[i].y);
        mma16816(qa[0], ha[i].x, hb[i].x, ha[i].y, hb[i].y, ha[i].x, ha[i].y);
        mma16816(qb[0], ha[i].x, hb[i].x, ha[i].y, hb[i].y, hb[i].x, hb[i].y);
        mma16816(sw[1], ha[i].z, hb[i].z, ha[i].w, hb[i].w, wv[i].z, wv[i].w);
        mma16816(qa[1], ha[i].z, hb[i].z, ha[i].w, hb[i].w, ha[i].z, ha[i].w);
        mma16816(qb[1], ha[i].z, hb[i].z, ha[i].w, hb[i].w, hb[i].z, hb[i].w);
      }
      const uint32_t s0 = with_bit(sw[0][0] + sw[1][0], cd), s1 = with_bit((g & 1) ? qa[0][1] + qa[1][1] : qa[0][0] + qa[1][0], cd >> 1), s2 = __float_as_uint(sw[0][1] + sw[1][1]);
      const uint32_t s3 = with_bit(sw[0][2] + sw[1][2], cd), s4 = with_bit((g & 1) ? qb[0][3] + qb[1][3] : qb[0][2] + qb[1][2], cd >> 1), s5 = __float_as_uint(sw[0][3] + sw[1][3]);
      if (q == (g >> 1)) { pkt_st128(hpub, s0, s1, s2, tag); pkt_st128(hpub + 8, s3, s4, s5, tag); }
      CT(12);
      const uint32_t o1 = __shfl_sync(0xffffffffu, s1, (lane & 28) | (g >> 1)), o4 = __shfl_sync(0xffffffffu, s4, (lane & 28) | (g >> 1));
      uint32_t n = 0;
      bool more;
#pragma unroll 1
      do {
        if (2 * q == eps) { v[0] = make_uint4(s0, o1, s2, tag); v[2] = make_uint4(s3, o4, s5, tag); }
        if (2 * q + 1 == eps) { v[1] = make_uint4(s0, o1, s2, tag); v[3] = make_uint4(s3, o4, s5, tag); }
        uint32_t bad = 0;
#pragma unroll
        for (int i = 0; i < 4; i++) { chk(bad, v[i].x, cd); chk(bad, v[i].y, cd >> 1); }
        bad &= 1;
#pragma unroll
        for (int i = 0; i < 4; i++) chk(bad, v[i].w, tag);
        more = !(!__any_sync(0xffffffffu, bad)) && ++n < SPIN_LIMIT;
        if (more) { if (bad) fetch(); }
      } while (more);
      st[0] = no_bit(v[0].x) + no_bit(v[1].x); st[1] = no_bit(v[0].y) + no_bit(v[1].y); st[2] = __uint_as_float(v[0].z) + __uint_as_float(v[1].z);
      st[3] = no_bit(v[2].x) + no_bit(v[3].x); st[4] = no_bit(v[2].y) + no_bit(v[3].y); st[5] = __uint_as_float(v[2].z) + __uint_as_float(v[3].z);
    }
    CT(13);
#pragma unroll
    for (int o = 1; o < 4; o <<= 1) {
#pragma unroll
      for (int i = 0; i < 6; i++) st[i] += __shfl_xor_sync(0xffffffffu, st[i], o);
    }
    float mb[2], inv[2];
#pragma unroll
    for (int i = 0; i < 2; i++) {
      const float mu = st[3 * i] * (1.f / 1024.f);
      mb[i] = bf16r(mu);
      inv[i] = fast_rcp(ref_sd(fmaxf(st[3 * i + 1] * (1.f / 1024.f) - mu * mu, 0.f)));
    }
    {
      const int srow = key_row(info.z);
      auto put_out = [&](bf16* dst, const uint4& h, float sc, float of, bool on) {
        auto cvt = [&](uint32_t x) { return pack_bf16(fmaf(bf_lo(x), sc, of), fmaf(bf_hi(x), sc, of)); };
        asm volatile("{\n.reg .pred p;\nsetp.ne.b32 p, %5, 0;\n@p st.global.v4.b32 [%0], {%1, %2, %3, %4};\n}\n"
                     :: "l"(dst), "r"(cvt(h.x)), "r"(cvt(h.y)), "r"(cvt(h.z)), "r"(cvt(h.w)), "r"((int)on) : "memory");
      };
#pragma unroll
      for (int i = 0; i < 4; i++) {
        put_out(op + i * 32, ha[i], 1.f + inv[0], -mb[0] * inv[0], row0 != srow);
        put_out(op + 8192 + i * 32, hb[i], 1.f + inv[1], -mb[1] * inv[1], row0 + 8 != srow);
      }
    }
    CT(14);
    const uint4 cand = lds128(sb + INFO_CAND);
    uint32_t wkey = zero_here();
#pragma unroll
    for (int i = 0; i < 2; i++) {
      const uint32_t row = row0 + 8 * i, rr = row | (row << 16);
      const bool is_cand = __vcmpeq2(cand.x, rr) | __vcmpeq2(cand.y, rr) | __vcmpeq2(cand.z, rr) | __vcmpeq2(cand.w, rr);
      if (!is_cand) wkey = max(wkey, make_key(bf16r((st[3 * i + 2] - mb[i] * __uint_as_float(info.x)) * inv[i]), row));
    }
    wkey = __reduce_max_sync(0xffffffffu, wkey);
    if (eps == 0 && lane == 0) pkt_st64(&p.sc->key[grp * 8 + warp], wkey, tag);
    const bool beaten = (wkey >> 16) > (info.z >> 16);
    if (__builtin_expect(beaten, 0)) {
      const int br = key_row(wkey);
      if (br == row0 || br == row0 + 8) {
#pragma unroll
        for (int i = 0; i < 4; i++) {
          const uint4 h = br == row0 ? ha[i] : hb[i];
          uint2* dst = &p.sc->hrow[(grp * 8 + warp) * 512 + eps * 64 + i * 16 + q * 4];
          pkt_st128(dst, h.x, tag, h.y, tag); pkt_st128(dst + 2, h.z, tag, h.w, tag);
        }
      }
      __syncwarp();
    }
    uint32_t any;
    asm volatile("{\n.reg .pred p, q;\nsetp.ne.b32 p, %1, 0;\nbarrier.cta.red.or.aligned.pred q, %2, 256, p;\nselp.u32 %0, 1, 0, q;\n}\n" : "=r"(any) : "r"((int)beaten), "n"((int)NB_BOTH) : "memory");
    if (__builtin_expect(any, 0)) slow_path(p, grp, eps, tag, info.z, info.w, SM<float>(INFO_LN), SM<float>(INFO_LN + 4));
  }
}

__global__ void __launch_bounds__(NTHR, 1) occupancy_probe_kernel() {}

typedef CUresult (*EncodeFn)(CUtensorMap*, CUtensorMapDataType, cuuint32_t, void*, const cuuint64_t*, const cuuint64_t*, const cuuint32_t*, const cuuint32_t*,
                             CUtensorMapInterleave, CUtensorMapSwizzle, CUtensorMapL2promotion, CUtensorMapFloatOOBfill);

static void make_tm(EncodeFn enc, CUtensorMap* tm, const void* ptr, uint64_t rows, uint64_t cols, uint32_t brows, uint32_t bcols, bool swz, bool wide) {
  cuuint64_t dims[2] = {cols, rows};
  cuuint64_t strides[1] = {cols * 2};
  cuuint32_t box[2] = {bcols, brows};
  cuuint32_t es[2] = {1, 1};
  enc(tm, CU_TENSOR_MAP_DATA_TYPE_BFLOAT16, 2, const_cast<void*>(ptr), dims, strides, box, es, CU_TENSOR_MAP_INTERLEAVE_NONE,
      swz ? CU_TENSOR_MAP_SWIZZLE_128B : CU_TENSOR_MAP_SWIZZLE_NONE, wide ? CU_TENSOR_MAP_L2_PROMOTION_L2_256B : CU_TENSOR_MAP_L2_PROMOTION_L2_128B, CU_TENSOR_MAP_FLOAT_OOB_FILL_NONE);
}

extern "C" void kernel_launch(void* const* d_in, const int* in_sizes, int n_in, void* d_out, int out_size) {
  (void)in_sizes; (void)n_in; (void)out_size;
  static EncodeFn enc = nullptr;
  static void* abT = nullptr;
  static void* sc = nullptr;
  static int map = 0;
  if (!enc) {
    void* fn = nullptr; cudaDriverEntryPointQueryResult st;
    cudaGetDriverEntryPoint("cuTensorMapEncodeTiled", &fn, cudaEnableDefault, &st);
    enc = (EncodeFn)fn;
    cudaGetSymbolAddress(&abT, g_abT);
    cudaGetSymbolAddress(&sc, g_sc);
    cudaFuncSetAttribute(fnet_moe_kernel<0>, cudaFuncAttributeMaxDynamicSharedMemorySize, SMEM_TOTAL);
    cudaFuncSetAttribute(fnet_moe_kernel<1>, cudaFuncAttributeMaxDynamicSharedMemorySize, SMEM_TOTAL);
    cudaFuncSetAttribute(occupancy_probe_kernel, cudaFuncAttributeMaxDynamicSharedMemorySize, SMEM_TOTAL);
    cudaFuncSetAttribute(occupancy_probe_kernel, cudaFuncAttributeNonPortableClusterSizeAllowed, 1);
    cudaLaunchConfig_t cfg = {};
    cfg.gridDim = dim3(128); cfg.blockDim = dim3(NTHR); cfg.dynamicSmemBytes = SMEM_TOTAL;
    cudaLaunchAttribute at[1];
    at[0].id = cudaLaunchAttributeClusterDimension; at[0].val.clusterDim.x = 16; at[0].val.clusterDim.y = 1; at[0].val.clusterDim.z = 1;
    cfg.attrs = at; cfg.numAttrs = 1;
    int ncl = 0;
    if (cudaOccupancyMaxActiveClusters(&ncl, occupancy_probe_kernel, &cfg) == cudaSuccess && ncl >= 8) map = 1;
    (void)cudaGetLastError();
  }
  Params p;
  const bf16* x = (const bf16*)d_in[0];
  make_tm(enc, &p.tmD0, d_in[3], 1024, 1024, 128, 64, true, true);
  make_tm(enc, &p.tmD1, d_in[4], 1024, 1024, 128, 64, true, true);
  make_tm(enc, &p.tmX, x, 2048, 1024, 256, 64, true, true);
  make_tm(enc, &p.tmAbS, abT, 2048, 2048, 64, 64, true, false);
  make_tm(enc, &p.tmAbL, abT, 2048, 2048, 128, 64, true, false);
  make_tm(enc, &p.tmW0, d_in[1], 2048, 2048, 128, 64, true, true);
  make_tm(enc, &p.tmW1, d_in[2], 2048, 2048, 128, 64, true, true);
  make_tm(enc, &p.tmG, d_in[7], 1024, 3584, 16, 64, false, false);
  make_tm(enc, &p.tmU, d_in[8], 1024, 3584, 16, 64, false, false);
  make_tm(enc, &p.tmDn, d_in[9], 3584, 1024, 8, 256, false, false);
  make_tm(enc, &p.tmY, (char*)sc + offsetof(Scratch, ypart), 4 * NSRC, 512, NSRC, 16, false, false);
  p.x = x; p.Dre = (const bf16*)d_in[3]; p.Dim = (const bf16*)d_in[4];
  p.wr = (const bf16*)d_in[6]; p.wdown = (const bf16*)d_in[9]; p.wgate = (const bf16*)d_in[7]; p.wup = (const bf16*)d_in[8]; p.Wre = (const bf16*)d_in[1]; p.Wim = (const bf16*)d_in[2];
  p.out = (bf16*)d_out; p.sc = (Scratch*)sc;
  if (map == 1) fnet_moe_kernel<1><<<NGRID, NTHR, SMEM_TOTAL>>>(p);
  else fnet_moe_kernel<0><<<NGRID, NTHR, SMEM_TOTAL>>>(p);
}
```

```cpp
#include <cuda.h>
#include <cuda_runtime.h>
#include <cuda_bf16.h>
#include <stdint.h>
#include <stddef.h>
#include <type_traits>

typedef __nv_bfloat16 bf16;

#define C1_AUX 1
constexpr int NGRID = 132, NTHR = 384;
__device__ __forceinline__ int k_col(int tau, int j) { return (tau * 256 + (j < 4 ? j * 64 : (j - 3) * 256)) & 2047; }
__device__ __forceinline__ int k_next(int c, int j) { return (c + (j < 11 ? 256 : j == 11 ? 576 : (c & 192) == 192 ? 128 : 64)) & 2047; }
constexpr int A_BYTES = 128 * 64 * 2;
constexpr int B_BYTES = 256 * 64 * 2;
constexpr int ST_BYTES = A_BYTES + B_BYTES;
constexpr int OFF_AUX = 4 * ST_BYTES;
constexpr int OFF_BAR = OFF_AUX + 32768;
constexpr int OFF_XS = OFF_BAR + 256;
constexpr int OFF_WR = OFF_XS + 2048;
constexpr int OFF_REM = OFF_WR + 256;
constexpr int OFF_INFO = OFF_REM + 256;
constexpr int SMEM_TOTAL = OFF_INFO + 256;
constexpr int INFO_WSUM = OFF_INFO, INFO_TAG = OFF_INFO + 4, INFO_KEY = OFF_INFO + 8, INFO_CAND = OFF_INFO + 16, INFO_LN = OFF_INFO + 32, INFO_ONES = OFF_INFO + 48, INFO_DS = OFF_INFO + 64, INFO_DS2 = OFF_INFO + 192;
constexpr int OFF_RS = OFF_XS;
constexpr int OFF_WC = OFF_AUX;
constexpr int OFF_EXA = OFF_AUX + 4096;
constexpr int OFF_EXB = OFF_AUX + 6144;
__host__ __device__ constexpr int off_stage(int c) { return C1_AUX && c == 1 ? OFF_AUX + 16384 : c * ST_BYTES; }
constexpr int OFF_RECV = A_BYTES;
__host__ __device__ constexpr int off_y(int w) { return w * ST_BYTES; }
constexpr int NSRC = 112;
enum { B_FULL = 0, B_EMPTY = 4, B_ALL = 6, B_EP = 8, B_AW = 16, B_STAT = 24, B_WC = 25, B_CD = 26, B_INFO = 28, B_PEER = 29, B_XCH = 30, B_GUX = (OFF_INFO + 128 - OFF_BAR) / 8, B_SD = B_GUX + 1, B_CH = 27, B_E23 = B_GUX + 5 };
enum { NB_TURN0 = 1, NB_TURN1 = 2, NB_BOTH = 3, NB_AUX = 4, NB_H = 5, NB_SEL = 6 };

struct Scratch;
struct Params {
  Scratch* sc; const bf16* wr; const bf16* x; const bf16* Dre; const bf16* Dim; const bf16* Wre; const bf16* Wim;
  const bf16* wgate; const bf16* wup; const bf16* wdown; bf16* out;
  CUtensorMap tmX, tmD0, tmD1, tmW0, tmW1, tmAbS, tmAbL, tmG, tmU, tmDn, tmY;
};

__device__ __align__(1024) bf16 g_abT[2048 * 2048];
struct Scratch {
  alignas(128) uint4 xz[2048];
  alignas(128) uint2 dsum[2048];
  alignas(128) uint32_t abflag[128 * 4 * 32];
  alignas(128) uint32_t abdone[128 * 2 * 32];
  alignas(128) uint2 u[4 * 512];
  alignas(128) uint2 cl[128 * 16];
  alignas(128) uint4 cpart[4 * 16 * 512];
  alignas(128) uint2 ch[8 * 512];
  alignas(128) uint4 cs[128 * 8];
  alignas(128) uint2 rdone[128];
  alignas(128) uint4 ypart[4 * NSRC * 64];
  alignas(128) uint4 hstat[16 * 8 * 128];
  alignas(128) uint2 key[128];
  alignas(128) uint2 hrow[128 * 512];
  alignas(128) uint2 fpart[8 * 1024];
  alignas(128) uint32_t epoch;
};
__device__ Scratch g_sc;

#define SPIN_LIMIT (1u << 17)
#define PF2_K 24
#define UNIT_PACE 1600
#define XPF_K 32
#define XS_DELAY 300
#define U_CLK 3700
#define XROW_PF 0
#define DROW_PF 0
#define TM_PF 0
#define SPLIT17 1
#define LO_NS 250
#define CAND_EARLY 0
#define CHAIN1 0
#define ROW_NS 400
#define W_PF 2
#define START_PF 0
#define ND0 65
#define ND1 66
#define ND2 67
#define ND3 -1
#define ND4 69
#define HI_DELAY 0
#define HI_PACE 1000
#define ALL_NS 400
#define HI_ORDER 0
#define PUT1_LATE 0
#define ALL_AT 1
#define LU0_LATE 0
#define Y_NS 200
#define GV 2
#define XS0 2
#define RS_EARLY 0
#define PRE_UNPACK 1
#define PV 2
#define Z_CLK 9000
#define CP_DELAY 1500
#define CS_DELAY 800
#define YPART_DELAY 17300
__device__ __forceinline__ uint32_t smem_u32(const void* p) { return (uint32_t)__cvta_generic_to_shared(p); }
__device__ __forceinline__ uint32_t clk32() { uint32_t c; asm volatile("mov.u32 %0, %%clock;" : "=r"(c)); return c; }
__device__ __forceinline__ uint32_t zero_here() { uint64_t c; asm volatile("mov.u64 %0, %%clock64;" : "=l"(c) :: "memory"); return (uint32_t)(c >> 32) & blockIdx.y; }
__device__ __forceinline__ uint32_t uniform_zero_here() { uint32_t c; asm volatile("mov.u32 %0, %%clock;" : "=r"(c) :: "memory"); return c & blockIdx.y; }
__device__ __forceinline__ void wait_clk(uint32_t t0, uint32_t dt) {
  asm volatile("{\n.reg .pred p;\n.reg .u32 c;\nLOOP:\nmov.u32 c, %%clock;\nsub.u32 c, c, %0;\nsetp.lt.u32 p, c, %1;\n@p nanosleep.u32 100;\n@p bra LOOP;\n}\n" :: "r"(t0), "r"(dt) : "memory");
}
__device__ __forceinline__ void mbar_init(uint32_t bar, uint32_t cnt) { asm volatile("mbarrier.init.shared::cta.b64 [%0], %1;" :: "r"(bar), "r"(cnt) : "memory"); }
__device__ __forceinline__ void mbar_expect_tx(uint32_t bar, uint32_t bytes) { asm volatile("mbarrier.arrive.expect_tx.shared::cta.b64 _, [%0], %1;" :: "r"(bar), "r"(bytes) : "memory"); }
__device__ __forceinline__ void mbar_arrive(uint32_t bar) { asm volatile("mbarrier.arrive.shared::cta.b64 _, [%0];" :: "r"(bar) : "memory"); }
__device__ __forceinline__ void mbar_arrive_remote(uint32_t cluster_addr) { asm volatile("mbarrier.arrive.shared::cluster.b64 _, [%0];" :: "r"(cluster_addr) : "memory"); }
__device__ __forceinline__ void mbar_wait(uint32_t bar, uint32_t parity) {
  asm volatile("{\n.reg .pred p;\nLOOP:\nmbarrier.try_wait.parity.shared::cta.b64 p, [%0], %1;\n@!p bra LOOP;\n}\n" :: "r"(bar), "r"(parity) : "memory");
}
__device__ __forceinline__ void tma_load_2d(uint32_t dst, const CUtensorMap* tm, uint32_t bar, int c0, int c1) {
  asm volatile("cp.async.bulk.tensor.2d.shared::cluster.global.mbarrier::complete_tx::bytes [%0], [%1, {%3, %4}], [%2];"
    :: "r"(dst), "l"(tm), "r"(bar), "r"(c0), "r"(c1) : "memory");
}
__device__ __forceinline__ void tma_load_2d_hint(uint32_t dst, const CUtensorMap* tm, uint32_t bar, int c0, int c1, uint64_t pol) {
  asm volatile("cp.async.bulk.tensor.2d.shared::cluster.global.mbarrier::complete_tx::bytes.L2::cache_hint [%0], [%1, {%3, %4}], [%2], %5;"
    :: "r"(dst), "l"(tm), "r"(bar), "r"(c0), "r"(c1), "l"(pol) : "memory");
}
__device__ __forceinline__ uint64_t policy_evict_first() { uint64_t p; asm volatile("createpolicy.fractional.L2::evict_first.b64 %0, 1.0;" : "=l"(p)); return p; }
__device__ __forceinline__ void tma_store_2d(const CUtensorMap* tm, uint32_t src, int c0, int c1) {
  asm volatile("cp.async.bulk.tensor.2d.global.shared::cta.bulk_group [%0, {%2, %3}], [%1];" :: "l"(tm), "r"(src), "r"(c0), "r"(c1) : "memory");
}
__device__ __forceinline__ void bulk_load(uint32_t dst, const void* src, uint32_t bytes, uint32_t bar) {
  asm volatile("cp.async.bulk.shared::cluster.global.mbarrier::complete_tx::bytes [%0], [%1], %2, [%3];" :: "r"(dst), "l"(src), "r"(bytes), "r"(bar) : "memory");
}
__device__ __forceinline__ void prefetch_l2(const void* p) { asm volatile("prefetch.global.L2 [%0];" :: "l"(p)); }
__device__ __forceinline__ void bulk_commit() { asm volatile("cp.async.bulk.commit_group;" ::: "memory"); }
__device__ __forceinline__ void bulk_wait_all() { asm volatile("cp.async.bulk.wait_group 0;" ::: "memory"); }
__device__ __forceinline__ void fence_async_smem() { asm volatile("fence.proxy.async.shared::cta;" ::: "memory"); }
__device__ __forceinline__ void wgmma_fence() { asm volatile("wgmma.fence.sync.aligned;" ::: "memory"); }
__device__ __forceinline__ void wgmma_commit() { asm volatile("wgmma.commit_group.sync.aligned;" ::: "memory"); }
template<int N> __device__ __forceinline__ void wgmma_wait() { asm volatile("wgmma.wait_group.sync.aligned %0;" :: "n"(N) : "memory"); }
__device__ __forceinline__ void bar_sync(int id, int n) { asm volatile("bar.sync %0, %1;" :: "r"(id), "r"(n) : "memory"); }
__device__ __forceinline__ void bar_arrive(int id, int n) { asm volatile("bar.arrive %0, %1;" :: "r"(id), "r"(n) : "memory"); }
__device__ __forceinline__ void cluster_wait() { asm volatile("barrier.cluster.wait.aligned;" ::: "memory"); }
template<int R> __device__ __forceinline__ void reg_inc() { asm volatile("setmaxnreg.inc.sync.aligned.u32 %0;" :: "n"(R)); }
template<int R> __device__ __forceinline__ void reg_dec() { asm volatile("setmaxnreg.dec.sync.aligned.u32 %0;" :: "n"(R)); }
__device__ __forceinline__ bool elect_one() {
  uint32_t p;
  asm volatile("{\n.reg .pred q;\nelect.sync _|q, 0xffffffff;\nselp.u32 %0, 1, 0, q;\n}\n" : "=r"(p));
  return p != 0;
}
__device__ __forceinline__ uint32_t mapa(uint32_t addr, uint32_t cta) { uint32_t r; asm volatile("mapa.shared::cluster.u32 %0, %1, %2;" : "=r"(r) : "r"(addr), "r"(cta)); return r; }
__device__ __forceinline__ void st_async_v4(uint32_t addr, uint32_t bar, uint32_t a, uint32_t b, uint32_t c, uint32_t d) {
  asm volatile("st.async.weak.shared::cluster.mbarrier::complete_tx::bytes.v4.b32 [%0], {%2, %3, %4, %5}, [%1];" :: "r"(addr), "r"(bar), "r"(a), "r"(b), "r"(c), "r"(d) : "memory");
}
__device__ __forceinline__ void st_async_b32(uint32_t addr, uint32_t bar, uint32_t a) {
  asm volatile("st.async.weak.shared::cluster.mbarrier::complete_tx::bytes.b32 [%0], %2, [%1];" :: "r"(addr), "r"(bar), "r"(a) : "memory");
}
__device__ __forceinline__ void stsm_x4(uint32_t addr, uint32_t a, uint32_t b, uint32_t c, uint32_t d) {
  asm volatile("stmatrix.sync.aligned.m8n8.x4.shared.b16 [%0], {%1, %2, %3, %4};" :: "r"(addr), "r"(a), "r"(b), "r"(c), "r"(d) : "memory");
}
__device__ __forceinline__ void stsm_x4_t(uint32_t addr, uint32_t a, uint32_t b, uint32_t c, uint32_t d) {
  asm volatile("stmatrix.sync.aligned.m8n8.x4.trans.shared.b16 [%0], {%1, %2, %3, %4};" :: "r"(addr), "r"(a), "r"(b), "r"(c), "r"(d) : "memory");
}
__device__ __forceinline__ uint4 lds128(uint32_t addr) { uint4 v; asm volatile("ld.shared.v4.b32 {%0, %1, %2, %3}, [%4];" : "=r"(v.x), "=r"(v.y), "=r"(v.z), "=r"(v.w) : "r"(addr) : "memory"); return v; }
extern __shared__ __align__(1024) uint8_t smem_raw[];
template<class T> __device__ __forceinline__ T& SM(int off) { return *reinterpret_cast<T*>(smem_raw + off); }
__device__ __forceinline__ uint4 ldg_nc128(const void* p) { uint4 v; asm volatile("ld.global.nc.v4.b32 {%0, %1, %2, %3}, [%4];" : "=r"(v.x), "=r"(v.y), "=r"(v.z), "=r"(v.w) : "l"(p)); return v; }
__device__ __forceinline__ uint4 ldg128(const void* p) { uint4 v; asm volatile("ld.global.L1::no_allocate.v4.b32 {%0, %1, %2, %3}, [%4];" : "=r"(v.x), "=r"(v.y), "=r"(v.z), "=r"(v.w) : "l"(p) : "memory"); return v; }
__device__ __forceinline__ void pkt_st128(void* p, uint32_t a, uint32_t b, uint32_t c, uint32_t d) {
  asm volatile("{\n.reg .b128 v;\n.reg .b64 lo, hi;\nmov.b64 lo, {%1, %2};\nmov.b64 hi, {%3, %4};\nmov.b128 v, {lo, hi};\nst.relaxed.gpu.global.b128 [%0], v;\n}\n"
    :: "l"(p), "r"(a), "r"(b), "r"(c), "r"(d) : "memory");
}
__device__ __forceinline__ uint4 pkt_ld128(const void* p) {
  uint4 r;
  asm volatile("{\n.reg .b128 v;\n.reg .b64 lo, hi;\nld.relaxed.gpu.global.b128 v, [%4];\nmov.b128 {lo, hi}, v;\nmov.b64 {%0, %1}, lo;\nmov.b64 {%2, %3}, hi;\n}\n"
    : "=r"(r.x), "=r"(r.y), "=r"(r.z), "=r"(r.w) : "l"(p) : "memory");
  return r;
}
__device__ __forceinline__ void pkt_st64(void* p, uint32_t a, uint32_t b) {
  asm volatile("{\n.reg .b64 v;\nmov.b64 v, {%1, %2};\nst.relaxed.gpu.global.b64 [%0], v;\n}\n" :: "l"(p), "r"(a), "r"(b) : "memory");
}
__device__ __forceinline__ uint2 pkt_ld64(const void* p) {
  uint2 r;
  asm volatile("{\n.reg .b64 v;\nld.relaxed.gpu.global.b64 v, [%2];\nmov.b64 {%0, %1}, v;\n}\n" : "=r"(r.x), "=r"(r.y) : "l"(p) : "memory");
  return r;
}
__device__ __forceinline__ void pkt_clear128(void* p) { pkt_st128(p, 0, 0, 0, 0); }
__device__ __forceinline__ uint32_t ld_relaxed32(const void* p) { uint32_t v; asm volatile("ld.relaxed.gpu.global.b32 %0, [%1];" : "=r"(v) : "l"(p) : "memory"); return v; }
__device__ __forceinline__ uint32_t ld_acquire32(const void* p) { uint32_t v; asm volatile("ld.acquire.gpu.global.b32 %0, [%1];" : "=r"(v) : "l"(p) : "memory"); return v; }
__device__ __forceinline__ void st_relaxed32(void* p, uint32_t v) { asm volatile("st.relaxed.gpu.global.b32 [%0], %1;" :: "l"(p), "r"(v) : "memory"); }
__device__ __forceinline__ uint32_t poll64(const void* p, uint32_t tag, int ns) {
  uint2 v; uint32_t n = 0;
  bool more;
#pragma unroll 1
  do {
    v = pkt_ld64(p);
    more = !(v.y == tag) && ++n < SPIN_LIMIT;
    if (more) { __nanosleep(ns); }
  } while (more);
  return v.x;
}
__device__ __forceinline__ uint32_t poll64_warp(const void* p, uint32_t tag, int ns) {
  uint2 v; uint32_t n = 0;
  bool more;
#pragma unroll 1
  do {
    v = pkt_ld64(p);
    more = !(__all_sync(0xffffffffu, v.y == tag)) && ++n < SPIN_LIMIT;
    if (more) { __nanosleep(ns); }
  } while (more);
  return v.x;
}
__device__ __forceinline__ uint32_t code_of(uint32_t tag) { return tag % 3u + 1u; }
__device__ __forceinline__ uint32_t with_bit(uint32_t v, uint32_t bit) { return (v & ~1u) | (bit & 1u); }
__device__ __forceinline__ uint32_t with_bit(float v, uint32_t bit) { return with_bit(__float_as_uint(v), bit); }
__device__ __forceinline__ float no_bit(uint32_t v) { return __uint_as_float(v & ~1u); }
__device__ __forceinline__ void chk(uint32_t& bad, uint32_t a, uint32_t want) { bad |= a ^ want; asm("" : "+r"(bad)); }
__device__ __forceinline__ void chk_code(uint32_t& bad, const uint4& v, uint32_t c0, uint32_t c1) { chk(bad, v.x, c0); chk(bad, v.y, c1); chk(bad, v.z, c0); chk(bad, v.w, c1); }
__device__ __forceinline__ uint32_t pack_bf16(float lo, float hi) { uint32_t r; asm("cvt.rn.bf16x2.f32 %0, %1, %2;" : "=r"(r) : "f"(hi), "f"(lo)); return r; }
__device__ __forceinline__ float bf_lo(uint32_t v) { return __uint_as_float(v << 16); }
__device__ __forceinline__ float bf_hi(uint32_t v) { return __uint_as_float(v & 0xFFFF0000u); }
__device__ __forceinline__ float bf16r(float x) { return __uint_as_float(pack_bf16(0.f, x)); }
__device__ __forceinline__ void st_bf16(bf16* p, float x) { *reinterpret_cast<uint16_t*>(p) = (uint16_t)pack_bf16(x, 0.f); }
__device__ __forceinline__ float fast_rcp(float x) { float r; asm("rcp.approx.f32 %0, %1;" : "=f"(r) : "f"(x)); return r; }
__device__ __forceinline__ float ldbf(const bf16* p) { return __bfloat162float(*p); }
__device__ __forceinline__ uint32_t badd2(uint32_t a, uint32_t b) { uint32_t r; asm("add.rn.bf16x2 %0, %1, %2;" : "=r"(r) : "r"(a), "r"(b)); return r; }
__device__ __forceinline__ uint32_t bfma2(uint32_t a, uint32_t b, uint32_t c) { uint32_t r; asm("fma.rn.bf16x2 %0, %1, %2, %3;" : "=r"(r) : "r"(a), "r"(b), "r"(c)); return r; }
__device__ __forceinline__ float warp_sum(float v) {
#pragma unroll
  for (int o = 16; o > 0; o >>= 1) v += __shfl_xor_sync(0xffffffffu, v, o);
  return v;
}
template<int N> __device__ __forceinline__ void fold(float* v, int o, int lane) {
  const bool up = lane & o;
#pragma unroll
  for (int i = 0; i < N / 2; i++) {
    const float keep = up ? v[N / 2 + i] : v[i], send = up ? v[i] : v[N / 2 + i];
    v[i] = keep + __shfl_xor_sync(0xffffffffu, send, o);
  }
}
__device__ __forceinline__ uint32_t make_key(float r_bf, int row) {
  const uint32_t u = __float_as_uint(r_bf);
  return (((u & 0x80000000u) ? ~u : (u | 0x80000000u)) & 0xFFFF0000u) | (0xFFFFu - (uint32_t)row);
}
__device__ __forceinline__ int key_row(uint32_t key) { return (0xFFFF - (int)(key & 0xFFFFu)) & 2047; }
__device__ __forceinline__ float key_val(uint32_t key) { const uint32_t o = key & 0xFFFF0000u; return __uint_as_float((o & 0x80000000u) ? (o & 0x7FFFFFFFu) : (~o & 0xFFFF0000u)); }
__device__ __forceinline__ float ref_sd(float var) { float r; asm("sqrt.approx.f32 %0, %1;" : "=f"(r) : "f"(bf16r(bf16r(var) + 1e-5f))); return bf16r(r); }
__device__ __forceinline__ uint64_t make_desc(uint32_t addr) { return (uint64_t)((addr & 0x3FFFF) >> 4) | ((uint64_t)64 << 32) | ((uint64_t)1 << 62); }
__device__ __forceinline__ uint64_t make_desc_noswz(uint32_t addr) { return (uint64_t)((addr & 0x3FFFF) >> 4) | ((uint64_t)8 << 32); }
#define ACC8(d, o) "+f"(d[o]), "+f"(d[o + 1]), "+f"(d[o + 2]), "+f"(d[o + 3]), "+f"(d[o + 4]), "+f"(d[o + 5]), "+f"(d[o + 6]), "+f"(d[o + 7])
#define ACC64(d, o) ACC8(d, o), ACC8(d, o + 8), ACC8(d, o + 16), ACC8(d, o + 24), ACC8(d, o + 32), ACC8(d, o + 40), ACC8(d, o + 48), ACC8(d, o + 56)
#define REGS64 "%0, %1, %2, %3, %4, %5, %6, %7, %8, %9, %10, %11, %12, %13, %14, %15, %16, %17, %18, %19, %20, %21, %22, %23, %24, %25, %26, %27, %28, %29, %30, %31, " \
    "%32, %33, %34, %35, %36, %37, %38, %39, %40, %41, %42, %43, %44, %45, %46, %47, %48, %49, %50, %51, %52, %53, %54, %55, %56, %57, %58, %59, %60, %61, %62, %63"
#define REGS128 REGS64 ", %64, %65, %66, %67, %68, %69, %70, %71, %72, %73, %74, %75, %76, %77, %78, %79, %80, %81, %82, %83, %84, %85, %86, %87, %88, %89, %90, %91, %92, %93, %94, %95, " \
    "%96, %97, %98, %99, %100, %101, %102, %103, %104, %105, %106, %107, %108, %109, %110, %111, %112, %113, %114, %115, %116, %117, %118, %119, %120, %121, %122, %123, %124, %125, %126, %127"
__device__ __forceinline__ void wgmma_n256(float (&d)[128], uint64_t da, uint64_t db) {
  asm volatile("wgmma.mma_async.sync.aligned.m64n256k16.f32.bf16.bf16 {" REGS128 "}, %128, %129, 1, 1, 1, 0, 0;\n"
    : ACC64(d, 0), ACC64(d, 64) : "l"(da), "l"(db));
}
#define OUT8(d, o) "=f"(d[o]), "=f"(d[o + 1]), "=f"(d[o + 2]), "=f"(d[o + 3]), "=f"(d[o + 4]), "=f"(d[o + 5]), "=f"(d[o + 6]), "=f"(d[o + 7])
#define OUT64(d, o) OUT8(d, o), OUT8(d, o + 8), OUT8(d, o + 16), OUT8(d, o + 24), OUT8(d, o + 32), OUT8(d, o + 40), OUT8(d, o + 48), OUT8(d, o + 56)
__device__ __forceinline__ void wgmma_n256_rs_init(float (&d)[128], const uint32_t* a, uint64_t db) {
  asm volatile("wgmma.mma_async.sync.aligned.m64n256k16.f32.bf16.bf16 {" REGS128 "}, {%128, %129, %130, %131}, %132, 0, 1, 1, 0;\n"
    : OUT64(d, 0), OUT64(d, 64) : "r"(a[0]), "r"(a[1]), "r"(a[2]), "r"(a[3]), "l"(db));
}
template<int ACCUM> __device__ __forceinline__ void wgmma_n256_rs(float (&d)[128], const uint32_t* a, uint64_t db) {
  asm volatile("wgmma.mma_async.sync.aligned.m64n256k16.f32.bf16.bf16 {" REGS128 "}, {%128, %129, %130, %131}, %132, %133, 1, 1, 0;\n"
    : ACC64(d, 0), ACC64(d, 64) : "r"(a[0]), "r"(a[1]), "r"(a[2]), "r"(a[3]), "l"(db), "n"(ACCUM));
}
template<int ACCUM> __device__ __forceinline__ void wgmma_n8_rs(float (&d)[4], const uint32_t* a, uint64_t db) {
  asm volatile("wgmma.mma_async.sync.aligned.m64n8k16.f32.bf16.bf16 {%0, %1, %2, %3}, {%4, %5, %6, %7}, %8, %9, 1, 1, 0;\n"
    : "+f"(d[0]), "+f"(d[1]), "+f"(d[2]), "+f"(d[3]) : "r"(a[0]), "r"(a[1]), "r"(a[2]), "r"(a[3]), "l"(db), "n"(ACCUM));
}
__device__ __forceinline__ void wgmma_n8(float (&d)[4], uint64_t da, uint64_t db) {
  asm volatile("wgmma.mma_async.sync.aligned.m64n8k16.f32.bf16.bf16 {%0, %1, %2, %3}, %4, %5, 1, 1, 1, 0, 0;\n"
    : "+f"(d[0]), "+f"(d[1]), "+f"(d[2]), "+f"(d[3]) : "l"(da), "l"(db));
}
__device__ __forceinline__ void wgmma_n128(float (&d)[64], uint64_t da, uint64_t db) {
  asm volatile("wgmma.mma_async.sync.aligned.m64n128k16.f32.bf16.bf16 {" REGS64 "}, %64, %65, 1, 1, 1, 0, 0;\n" : ACC64(d, 0) : "l"(da), "l"(db));
}
template<int N> __device__ __forceinline__ void fence_regs(float (&d)[N]) {
#pragma unroll
  for (int i = 0; i < N; i++) asm volatile("" : "+f"(d[i]) :: "memory");
}
__device__ __forceinline__ void mma16816(float (&c)[4], uint32_t a0, uint32_t a1, uint32_t a2, uint32_t a3, uint32_t b0, uint32_t b1) {
  asm volatile("mma.sync.aligned.m16n8k16.row.col.f32.bf16.bf16.f32 {%0, %1, %2, %3}, {%4, %5, %6, %7}, {%8, %9}, {%0, %1, %2, %3};"
               : "+f"(c[0]), "+f"(c[1]), "+f"(c[2]), "+f"(c[3]) : "r"(a0), "r"(a1), "r"(a2), "r"(a3), "r"(b0), "r"(b1));
}
__device__ __forceinline__ void fma8(float* acc, const uint4& v, float x) {
  acc[0] = fmaf(bf_lo(v.x), x, acc[0]); acc[1] = fmaf(bf_hi(v.x), x, acc[1]); acc[2] = fmaf(bf_lo(v.y), x, acc[2]); acc[3] = fmaf(bf_hi(v.y), x, acc[3]);
  acc[4] = fmaf(bf_lo(v.z), x, acc[4]); acc[5] = fmaf(bf_hi(v.z), x, acc[5]); acc[6] = fmaf(bf_lo(v.w), x, acc[6]); acc[7] = fmaf(bf_hi(v.w), x, acc[7]);
}
template<int PITCH> __device__ __forceinline__ void gemv8x8(float (&acc)[8], uint32_t addr, const float (&x)[8]) {
  uint4 v[2][2];
  v[0][0] = lds128(addr); v[0][1] = lds128(addr + PITCH);
#pragma unroll
  for (int b = 0; b < 4; b++) {
    if (b < 3) { v[(b + 1) & 1][0] = lds128(addr + (2 * b + 2) * PITCH); v[(b + 1) & 1][1] = lds128(addr + (2 * b + 3) * PITCH); }
    acc[0] += __uint_as_float(zero_here());
#pragma unroll
    for (int c = 0; c < 4; c++) {
      if (GV == 2 && c == 2) acc[4] += __uint_as_float(zero_here());
#pragma unroll
      for (int r = 0; r < 2; r++) {
        const uint4& q = v[b & 1][r];
        const uint32_t u = c == 0 ? q.x : c == 1 ? q.y : c == 2 ? q.z : q.w;
        acc[2 * c] = fmaf(bf_lo(u), x[2 * b + r], acc[2 * c]); acc[2 * c + 1] = fmaf(bf_hi(u), x[2 * b + r], acc[2 * c + 1]);
      }
    }
  }
}
__device__ __forceinline__ float swiglu(float g, float u) {
  g = bf16r(g); u = bf16r(u);
  return bf16r(bf16r(g * fast_rcp(1.f + __expf(-g))) * u);
}

#define CT(slot) do {} while (0)
#define TIM(slot) do {} while (0)

constexpr int H_BUF0 = 0, H_BUF1 = 16384, H_RED = 32768, H_KEYS = H_RED + 1024, H_ROW = H_KEYS + 1024, H_ACT = H_ROW + 8192, H_PART = H_ACT + 4096;
__device__ __forceinline__ void hsync() { bar_sync(NB_H, 256); }
template<int N> __device__ __forceinline__ void block_sum(float (&v)[N], int warp, int lane) {
#pragma unroll
  for (int i = 0; i < N; i++) v[i] = warp_sum(v[i]);
  hsync();
  if (lane == 0) {
#pragma unroll
    for (int i = 0; i < N; i++) SM<float>(H_RED + (i * 8 + warp) * 4) = v[i];
  }
  hsync();
#pragma unroll
  for (int i = 0; i < N; i++) {
    const float4 a = SM<float4>(H_RED + i * 32), b = SM<float4>(H_RED + i * 32 + 16);
    v[i] = ((a.x + a.y) + (a.z + a.w)) + ((b.x + b.y) + (b.z + b.w));
  }
}
__device__ __forceinline__ void fft_first(int j, float2 v0, float2 v1, float2 v2, float2 v3) {
  const float2 a = make_float2(v0.x + v2.x, v0.y + v2.y), b = make_float2(v0.x - v2.x, v0.y - v2.y);
  const float2 c = make_float2(v1.x + v3.x, v1.y + v3.y), d = make_float2(v1.y - v3.y, v3.x - v1.x);
  SM<float4>(H_BUF1 + j * 32) = make_float4(a.x + c.x, a.y + c.y, b.x + d.x, b.y + d.y);
  SM<float4>(H_BUF1 + j * 32 + 16) = make_float4(a.x - c.x, a.y - c.y, b.x - d.x, b.y - d.y);
}
template<int NB> __device__ __forceinline__ void fft_passes(int tid) {
  constexpr int q = 256 * NB;
#pragma unroll 1
  for (int ps = 1; ps < 5; ps++) {
    const int ns = 1 << (2 * ps), k = tid & (ns - 1);
    float s1, c1;
    __sincosf(-1.57079632679f * __fdividef((float)k, (float)ns), &s1, &c1);
    const float c2 = c1 * c1 - s1 * s1, s2 = 2.f * c1 * s1, c3 = c1 * c2 - s1 * s2, s3 = c1 * s2 + s1 * c2;
    hsync();
#pragma unroll
    for (int i = 0; i < NB; i++) {
      const int j = tid + 256 * i;
      const float2* in = &SM<float2>((ps & 1) ? H_BUF1 : H_BUF0);
      float2* o = &SM<float2>((ps & 1) ? H_BUF0 : H_BUF1) + (j - k) * 4 + k;
      const float2 v0 = in[j], x1 = in[j + q], x2 = in[j + 2 * q], x3 = in[j + 3 * q];
      const float2 v1 = make_float2(x1.x * c1 - x1.y * s1, x1.x * s1 + x1.y * c1);
      const float2 v2 = make_float2(x2.x * c2 - x2.y * s2, x2.x * s2 + x2.y * c2);
      const float2 v3 = make_float2(x3.x * c3 - x3.y * s3, x3.x * s3 + x3.y * c3);
      const float2 a = make_float2(v0.x + v2.x, v0.y + v2.y), b = make_float2(v0.x - v2.x, v0.y - v2.y);
      const float2 c = make_float2(v1.x + v3.x, v1.y + v3.y), d = make_float2(v1.y - v3.y, v3.x - v1.x);
      o[0] = make_float2(a.x + c.x, a.y + c.y); o[ns] = make_float2(b.x + d.x, b.y + d.y);
      o[2 * ns] = make_float2(a.x - c.x, a.y - c.y); o[3 * ns] = make_float2(b.x - d.x, b.y - d.y);
    }
  }
  hsync();
}
template<int NR> __device__ __forceinline__ void ln_rows(const float (&h)[NR][4], float (&hn)[NR][4], int warp, int lane) {
  float s[NR], q[NR];
#pragma unroll
  for (int i = 0; i < NR; i++) s[i] = (h[i][0] + h[i][1]) + (h[i][2] + h[i][3]);
  block_sum(s, warp, lane);
#pragma unroll
  for (int i = 0; i < NR; i++) {
    s[i] *= 1.f / 1024.f; q[i] = 0.f;
#pragma unroll
    for (int z = 0; z < 4; z++) q[i] = fmaf(h[i][z] - s[i], h[i][z] - s[i], q[i]);
  }
  block_sum(q, warp, lane);
#pragma unroll
  for (int i = 0; i < NR; i++) {
    const float mb = bf16r(s[i]), inv = fast_rcp(ref_sd(q[i] * (1.f / 1024.f)));
#pragma unroll
    for (int z = 0; z < 4; z++) hn[i][z] = bf16r(bf16r(h[i][z] - mb) * inv);
  }
}
__device__ __forceinline__ float sigmoid_bf(float r) { return bf16r(fast_rcp(1.f + __expf(-r))); }
__device__ __forceinline__ float routed_out(float h, float hn, float y, float sig) { return h + bf16r(hn + bf16r(bf16r(y) * sig)); }

__device__ __forceinline__ void helper_cta(const Params& p, const int hi, const uint32_t t_entry) {
  const int tid = threadIdx.x, warp = tid >> 5, lane = tid & 31;
  const float w0 = ldbf(p.wr + tid), w1 = ldbf(p.wr + tid + 256), w2 = ldbf(p.wr + tid + 512), w3 = ldbf(p.wr + tid + 768), wf = ldbf(p.wr);
  const uint32_t tag = ld_relaxed32(&p.sc->epoch) + 1;
  pkt_clear128(&p.sc->u[hi * 512 + tid * 2]);
  if (tid == 0 && w0 != 123.f) TIM(12);
  fft_first(tid, make_float2(w0, 0.f), make_float2(w1, 0.f), make_float2(w2, 0.f), make_float2(w3, 0.f));
  fft_passes<1>(tid);
  const uint32_t c0 = code_of(tag), c1 = c0 >> 1;
  {
    const float off = wf - SM<float>(H_BUF1) * (1.f / 1024.f);
    const float4 v = SM<float4>(H_BUF1 + tid * 32), u = SM<float4>(H_BUF1 + tid * 32 + 16);
    pkt_st128(&p.sc->u[hi * 512 + ((tid & 192) + (tid & 1) * 32 + ((tid >> 1) & 31)) * 2], with_bit(pack_bf16((tid ? v.x : 0.f) - off, v.z - off), c0), with_bit(pack_bf16(v.y, v.w), c1),
              with_bit(pack_bf16(u.x - off, u.z - off), c0), with_bit(pack_bf16(u.y, u.w), c1));
    if (tid < 64) pkt_clear128(&p.sc->cl[(hi * 32 + (tid >> 1)) * 16 + (tid & 1) * 2]);
    hsync();
  }
  if (tid == 0) TIM(0);
  {
    float tw[8];
#pragma unroll
    for (int i = 0; i < 4; i++) __sincosf((float)(tid + 256 * i) * (-6.28318530718f / 2048.f), &tw[2 * i], &tw[2 * i + 1]);
    wait_clk(t_entry, Z_CLK);
    uint2 z[8]; uint32_t n = 0;
    bool more;
#pragma unroll 1
    do {
      uint32_t bad = 0;
#pragma unroll
      for (int i = 0; i < 8; i++) z[i] = pkt_ld64(reinterpret_cast<const uint2*>(&p.sc->xz[tid]) + 512 * i + 1);
#pragma unroll
      for (int i = 0; i < 8; i++) chk(bad, z[i].y, tag);
      more = !(!bad) && ++n < SPIN_LIMIT;
      if (more) { __nanosleep(150); }
    } while (more);
#pragma unroll
    for (int i = 0; i < 2; i++)
      fft_first(tid + 256 * i, make_float2(bf_lo(z[i].x), bf_hi(z[i].x)), make_float2(bf_lo(z[i + 2].x), bf_hi(z[i + 2].x)),
                make_float2(bf_lo(z[i + 4].x), bf_hi(z[i + 4].x)), make_float2(bf_lo(z[i + 6].x), bf_hi(z[i + 6].x)));
    if (tid == 0) TIM(7);
    fft_passes<2>(tid);
    if (tid == 0) TIM(1);
    uint32_t k8[8];
#pragma unroll
    for (int i = 0; i < 4; i++) {
      const int k = tid + 256 * i;
      const float2 v0 = SM<float2>(H_BUF1 + k * 8), v1 = SM<float2>(H_BUF1 + (k + 1024) * 8);
      const float w = v1.x * tw[2 * i + 1] - v1.y * tw[2 * i];
      const uint32_t a = __float_as_uint(v0.x + w), b = __float_as_uint(v0.x - w);
      k8[2 * i] = (((a & 0x80000000u) ? ~a : (a | 0x80000000u)) & ~2047u) | k;
      k8[2 * i + 1] = (((b & 0x80000000u) ? ~b : (b | 0x80000000u)) & ~2047u) | (k + 1024);
    }
    uint32_t lim = 0xFFFFFFFFu;
#pragma unroll 1
    for (int r = 0; r < 4; r++) {
      uint32_t mx = 0;
#pragma unroll
      for (int i = 0; i < 8; i++) mx = max(mx, k8[i] <= lim ? k8[i] : 0u);
      mx = __reduce_max_sync(0xffffffffu, mx);
      if (lane == 0) SM<uint32_t>(H_KEYS + (warp * 4 + r) * 4) = mx;
      lim = mx - 1;
    }
    hsync();
    if (tid < 32) {
      const uint32_t me = SM<uint32_t>(H_KEYS + tid * 4);
      int rank = 0;
#pragma unroll
      for (int i = 0; i < 8; i++) { const uint4 o = SM<uint4>(H_KEYS + i * 16); rank += (o.x > me) + (o.y > me) + (o.z > me) + (o.w > me); }
      if (rank < 8) SM<uint16_t>(H_KEYS + 256 + rank * 2) = me & 2047u;
    }
    hsync();
    if (tid >= 128) pkt_st64(&p.sc->cl[(hi * 32 + ((tid - 128) >> 2)) * 16 + (tid & 3)], SM<uint32_t>(H_KEYS + 256 + (tid & 3) * 4), tag);
  }
  const uint32_t cpair = SM<uint32_t>(H_KEYS + 256 + hi * 4);
  const int ca = cpair & 0xFFFF, cb = cpair >> 16;
  if (tid < 128) prefetch_l2(((tid & 32) ? p.Wim : p.Wre) + (size_t)((tid & 64) ? cb : ca) * 2048 + lane * 64);
  if (tid == 0) TIM(2);
}

__device__ __forceinline__ void slow_path(const Params& p, int grp, int eps, uint32_t tag, uint32_t key, int win, float mb, float inv) {
  const int tid = threadIdx.x + zero_here(), warp = tid >> 5, lane = tid & 31;
  uint32_t best = __reduce_max_sync(0xffffffffu, poll64(&p.sc->key[tid & 127], tag, 200));
  if (lane == 0) SM<uint32_t>(H_KEYS + warp * 4) = best;
  hsync();
  { const uint4 b4 = SM<uint4>(H_KEYS); best = max(max(b4.x, b4.y), max(b4.z, b4.w)); }
  const int tw = key_row(best), col = eps * 128 + (tid & 127);
  if ((tw >> 7) != grp) return;
  poll64(&p.sc->rdone[col >> 3], tag, 100);
  const uint32_t h0 = poll64(&p.sc->hrow[(tw >> 4) * 512 + 2 * tid], tag, 100), h1 = poll64(&p.sc->hrow[(tw >> 4) * 512 + 2 * tid + 1], tag, 100);
  float h[1][4] = {{bf_lo(h0), bf_hi(h0), bf_lo(h1), bf_hi(h1)}}, hn[1][4];
  ln_rows<1>(h, hn, warp, lane);
  SM<float4>(H_ROW + tid * 16) = make_float4(hn[0][0], hn[0][1], hn[0][2], hn[0][3]);
  SM<float4>(H_ROW + 4096 + tid * 16) = make_float4(h[0][0], h[0][1], h[0][2], h[0][3]);
  hsync();
#pragma unroll 1
  for (int ph = 0; ph < 2; ph++) {
    const int part = min(tid / 56, 3), fh = tid >> 7, len = ph ? 224 : 512, ld = ph ? 1024 : 3584;
    const bf16* wp = ph ? p.wdown + (eps * 448 + fh * 224) * 1024 + (tid & 127) * 8
                        : ((part & 1) ? p.wup : p.wgate) + (part >> 1) * 512 * 3584 + eps * 448 + min(tid - part * 56, 55) * 8;
    const int xo = ph ? H_ACT + fh * 224 * 4 : H_ROW + (part >> 1) * 2048;
    float acc[8] = {0.f, 0.f, 0.f, 0.f, 0.f, 0.f, 0.f, 0.f};
#pragma unroll 8
    for (int d = 0; d < (len & ~7); d++) fma8(acc, ldg_nc128(wp + d * ld), SM<float>(xo + d * 4));
    SM<float4>(H_PART + tid * 32) = make_float4(acc[0], acc[1], acc[2], acc[3]);
    SM<float4>(H_PART + tid * 32 + 16) = make_float4(acc[4], acc[5], acc[6], acc[7]);
    hsync();
    if (ph) break;
#pragma unroll 1
    for (int f = tid; f < 448; f += 256)
      SM<float>(H_ACT + f * 4) = swiglu(SM<float>(H_PART + f * 4) + SM<float>(H_PART + (896 + f) * 4), SM<float>(H_PART + (448 + f) * 4) + SM<float>(H_PART + (1344 + f) * 4));
    hsync();
  }
#pragma unroll 1
  for (int e = tid; e < 1024; e += 256) pkt_st64(&p.sc->fpart[eps * 1024 + e], __float_as_uint(SM<float>(H_PART + e * 4) + SM<float>(H_PART + (1024 + e) * 4)), tag);
  if (tid < 128) {
    float y = 0.f;
#pragma unroll 1
    for (int q = 0; q < 8; q++) y += __uint_as_float(poll64(&p.sc->fpart[q * 1024 + col], tag, 200));
    st_bf16(p.out + tw * 1024 + col, routed_out(SM<float>(H_ROW + 4096 + col * 4), SM<float>(H_ROW + col * 4), y, sigmoid_bf(key_val(best))));
    const uint32_t a = poll64(&p.sc->ch[win * 512 + (col >> 4) * 8 + (col & 7)], tag, 100);
    const float hc = (col & 8) ? bf_hi(a) : bf_lo(a);
    st_bf16(p.out + key_row(key) * 1024 + col, hc + bf16r(bf16r(hc - mb) * inv));
  }
}

template<int MAP>
__global__ void __cluster_dims__(2, 1, 1) __launch_bounds__(NTHR, 1)
fnet_moe_kernel(const __grid_constant__ Params p) {
  const uint32_t t_entry = clk32();
  uint32_t smid;
  asm("mov.u32 %0, %%smid;" : "=r"(smid));
  const int tpc = smid >> 1, m = blockIdx.x & 1;
  if (MAP == 1 ? tpc >= 64 : (tpc >> 1) == 30) {
    if (threadIdx.x < 256) helper_cta(p, (tpc & 1) * 2 + m, t_entry);
    return;
  }
  const uint32_t sb = smem_u32(smem_raw);
  const int tid = threadIdx.x, lane = tid & 31;
  const int e7 = ((tpc - 32) * 37) >> 8;
  const int tau = MAP == 1 || tpc < 32 ? (tpc & 7) : (tpc < 60 ? tpc - 31 - 7 * e7 : 0);
  const int eps = MAP == 1 || tpc < 32 ? (tpc >> 3) : (tpc < 60 ? 4 + e7 : tpc - 58);
  const int cid = tau * 16 + eps * 2 + m;
  auto BAR = [&](int i) { return sb + OFF_BAR + 8 * i; };
  const CUtensorMap* tmD = &p.tmD0 + m;
#define LOAD_STREAM(d, tm, bar, c0, c1) tma_load_2d_hint(d, tm, bar, c0, c1, pol_ef)
#define LOAD_W tma_load_2d
#define LOAD_D tma_load_2d
#define LOAD_X tma_load_2d
#define LOAD_F LOAD_STREAM

  uint32_t tag = 0;
  uint4 wq = make_uint4(0, 0, 0, 0);
  if ((tid >> 5) == 4) {
    if (elect_one()) {
      const uint64_t pol_ef = policy_evict_first();
#pragma unroll
      for (int k = 0; k < 4; k++) mbar_init(BAR(B_FULL + k), 1);
      asm volatile("fence.mbarrier_init.release.cluster;" ::: "memory");
#pragma unroll
      for (int k = 0; k < 4; k++) {
        mbar_expect_tx(BAR(B_FULL + k), ST_BYTES);
        tma_load_2d(sb + k * ST_BYTES + A_BYTES, &p.tmX, BAR(B_FULL + k), k * 64, tau * 256);
        LOAD_D(sb + k * ST_BYTES, tmD, BAR(B_FULL + k), k * 64, eps * 128);
        TIM(k);
      }
    }
  } else if ((tid >> 5) == 1) {
    if (elect_one()) {
#pragma unroll
      for (int s = 0; s < 4; s++) { mbar_init(BAR(B_EMPTY + s), 1); mbar_init(BAR(B_SD + s), 1); }
#pragma unroll
      for (int s = 0; s < 8; s++) { mbar_init(BAR(B_EP + s), 4); mbar_init(BAR(B_AW + s), 1); }
      mbar_init(BAR(B_STAT), 4); mbar_init(BAR(B_WC), 1); mbar_init(BAR(B_CD), 2);
      mbar_init(BAR(B_E23), 1); mbar_init(BAR(B_E23 + 1), 1); mbar_init(BAR(B_E23 + 2), 1); mbar_init(BAR(B_CH), 1); mbar_init(BAR(B_INFO), 1); mbar_init(BAR(B_PEER), 1);
      mbar_init(BAR(B_XCH), 1); mbar_init(BAR(B_XCH + 1), 1); mbar_init(BAR(B_GUX), 1);
      asm volatile("fence.mbarrier_init.release.cluster;" ::: "memory");
      mbar_expect_tx(BAR(B_XCH), 16384); mbar_expect_tx(BAR(B_XCH + 1), 16384); mbar_expect_tx(BAR(B_GUX), 256);
    }
  } else if (tid >= 256) {
    if (START_PF) prefetch_l2(((tid & 64) ? (cid < 64 ? p.Dre : p.Dim) + (cid & 63) * 16384 : p.x + cid * 16384) + ((tid >> 2) & 15) * 1024 + (tid & 3) * 64);
    tag = ld_relaxed32(&p.sc->epoch + threadIdx.y);
    wq = ldg128(p.wr + (tid & 127) * 8);
  }
  const int warp = __shfl_sync(0xffffffffu, tid >> 5, 0);
  __syncthreads();
  asm volatile("barrier.cluster.arrive.relaxed.aligned;" ::: "memory");

  if (warp >= 8) {
    reg_dec<72>();
    cluster_wait();
    tag = __shfl_sync(0xffffffffu, tag, 0) + 1;
    const int cid0 = cid;
    const uint32_t tag0 = tag, sb0 = sb;
    int a, lane, j, cid, tau, eps, m, grp, abrow, fc, src;
    uint32_t tag, c0, c1, sb, buf, bar0;
    bool ffn;
    auto BAR = [&](int i) { return sb + OFF_BAR + 8 * i; };
    auto fresh_ids = [&]() {
      const uint32_t z = uniform_zero_here();
      uint32_t l; asm volatile("mov.u32 %0, %%laneid;" : "=r"(l));
      a = warp - 8 + z; lane = l; j = a * 32 + l;
      cid = cid0 + z; tau = cid >> 4; eps = (cid >> 1) & 7; m = cid & 1; grp = tau * 2 + m; abrow = m * 1024 + eps * 128;
      ffn = eps > 0; fc = (tau * 7 + eps - 1) * 64; src = (fc >> 5) + m;
      tag = tag0 + z; c0 = code_of(tag); c1 = c0 >> 1;
      sb = sb0 + z; buf = sb + OFF_AUX + a * 8192; bar0 = BAR(B_AW + 2 * a);
    };
    fresh_ids();
    if (a == 0 && lane < 16) pkt_clear128(&p.sc->xz[cid * 16 + lane]);
    if (lane < 2) pkt_clear128(&p.sc->dsum[cid * 16 + a * 4 + lane * 2]);
    if (a == 3 && lane < 10) pkt_clear128((lane < 4 ? &p.sc->abdone[cid * 64] : &p.sc->abflag[cid * 128 - 64]) + (lane >> 1) * 32 + (lane & 1) * 4);
    {
      const float s = warp_sum(((bf_lo(wq.x) + bf_hi(wq.x)) + (bf_lo(wq.y) + bf_hi(wq.y))) + ((bf_lo(wq.z) + bf_hi(wq.z)) + (bf_lo(wq.w) + bf_hi(wq.w))));
      if ((j >> 4) == eps) SM<uint4>(OFF_WR + (j & 15) * 16) = wq;
      if (lane == 0) { SM<float>(INFO_DS + a * 4) = s; SM<uint32_t>(INFO_ONES + a * 4) = 0x3F803F80u; }
    }
    const bf16* xrows = p.x + (cid * 16 + a * 4) * 1024;
    const bf16* drows = (cid < 64 ? p.Dre : p.Dim) + ((cid & 63) * 16 + a * 4) * 1024;
    if (XROW_PF) {
      wait_clk(t_entry, XROW_PF);
      prefetch_l2(xrows + lane * 64); prefetch_l2(xrows + 2048 + lane * 64);
    }
    fresh_ids();
    {
      wait_clk(t_entry, U_CLK);
      uint4 u[8]; uint32_t n = 0;
      bool more;
#pragma unroll 1
      do {
        uint32_t bad = 0;
#pragma unroll
        for (int q = 0; q < 8; q++) u[q] = pkt_ld128(&p.sc->u[a * 512 + lane * 2] + q * 64);
        if (n == 0 && lane < 2) { mbar_expect_tx(bar0 + lane * 8, 4096); bulk_load(buf + lane * 4096, xrows + lane * 2048, 4096, bar0 + lane * 8); }
#pragma unroll
        for (int q = 0; q < 8; q++) chk_code(bad, u[q], c0, c1);
        more = !(!__any_sync(0xffffffffu, bad & 1)) && ++n < SPIN_LIMIT;
        if (more) { __nanosleep(200); }
      } while (more);
      if (j == 0) TIM(96);
      if (DROW_PF) { prefetch_l2(drows + lane * 64); prefetch_l2(drows + 2048 + lane * 64); }
#pragma unroll 1
      for (int r2 = 0; r2 < 2; r2++) {
        float v8[8];
        mbar_wait(bar0 + r2 * 8, 0);
        if (lane == 0) TIM(140 + r2 * 4 + a);
#pragma unroll
        for (int r = 0; r < 2; r++) {
          float s0 = 0.f, s1 = 0.f, q0 = 0.f, q1 = 0.f;
          uint32_t zr = 0, zi = 0;
#pragma unroll
          for (int q = 0; q < 4; q++) {
            const uint4 v = lds128(buf + r2 * 4096 + r * 2048 + (q * 32 + lane) * 16);
            const uint32_t ww[4] = {v.x, v.y, v.z, v.w};
#pragma unroll
            for (int z = 0; z < 4; z++) {
              const float lo = bf_lo(ww[z]), hi = bf_hi(ww[z]);
              s0 += lo; s1 += hi; q0 = fmaf(lo, lo, q0); q1 = fmaf(hi, hi, q1);
            }
            zr = bfma2(v.x, u[2 * q].x, zr); zi = bfma2(v.x, u[2 * q].y, zi); zr = bfma2(v.y, u[2 * q].z, zr); zi = bfma2(v.y, u[2 * q].w, zi);
            zr = bfma2(v.z, u[2 * q + 1].x, zr); zi = bfma2(v.z, u[2 * q + 1].y, zi); zr = bfma2(v.w, u[2 * q + 1].z, zr); zi = bfma2(v.w, u[2 * q + 1].w, zi);
          }
          v8[4 * r] = s0 + s1; v8[4 * r + 1] = q0 + q1; v8[4 * r + 2] = bf_lo(zr) + bf_hi(zr); v8[4 * r + 3] = bf_lo(zi) + bf_hi(zi);
        }
        fold<8>(v8, 16, lane);
        if (lane == 0) { mbar_expect_tx(bar0 + r2 * 8, 4096); bulk_load(buf + r2 * 4096, drows + r2 * 2048, 4096, bar0 + r2 * 8); }
        fold<4>(v8, 8, lane); fold<2>(v8, 4, lane);
        v8[0] += __shfl_xor_sync(0xffffffffu, v8[0], 2);
        v8[0] += __shfl_xor_sync(0xffffffffu, v8[0], 1);
        SM<float>(OFF_REM + a * 64 + r2 * 32 + (lane >> 2) * 4) = v8[0];
        if (lane == 0) TIM(148 + r2 * 4 + a);
      }
    }
    bar_sync(NB_AUX, 128);
    fresh_ids();
    if (a == 0 && lane < 16) {
      const float4 v = SM<float4>(OFF_REM + lane * 16);
      const float mean = v.x * (1.f / 1024.f), rs = fast_rcp(ref_sd(fmaxf(v.y * (1.f / 1024.f) - mean * mean, 0.f)));
      pkt_st128(&p.sc->xz[cid * 16 + lane], __float_as_uint(bf16r(mean)) | (tag & 0xFFFFu), __float_as_uint(rs), pack_bf16(v.z * rs, v.w * rs), tag);
    }
    if (j == 32) { const float4 v = SM<float4>(INFO_DS); SM<float2>(INFO_WSUM) = make_float2((v.x + v.y) + (v.z + v.w), __uint_as_float(tag)); }
    if (j == 0) TIM(98);
#pragma unroll 1
    for (int r2 = 0; r2 < 2; r2++) {
      mbar_wait(bar0 + r2 * 8, 1);
      uint4 dv[8];
#pragma unroll
      for (int q = 0; q < 8; q++) dv[q] = lds128(buf + r2 * 4096 + (lane >> 4) * 2048 + q * 256 + (lane & 15) * 16);
      float s0 = __uint_as_float(zero_here()), s1 = 0.f;
#pragma unroll
      for (int q = 0; q < 8; q++) {
        const uint4 v = dv[q];
        s0 += (bf_lo(v.x) + bf_lo(v.y)) + (bf_lo(v.z) + bf_lo(v.w)); s1 += (bf_hi(v.x) + bf_hi(v.y)) + (bf_hi(v.z) + bf_hi(v.w));
      }
      s0 += s1;
#pragma unroll
      for (int o = 8; o > 0; o >>= 1) s0 += __shfl_xor_sync(0xffffffffu, s0, o);
      SM<float>(INFO_DS2 + (a * 4 + r2 * 2 + (lane >> 4)) * 4) = s0;
    }
    bar_sync(NB_AUX, 128);
    if (a == 1 && lane < 16) pkt_st64(&p.sc->dsum[cid * 16 + lane], SM<uint32_t>(INFO_DS2 + lane * 4), tag);
    if (j == 0) TIM(99);
    uint4* cpart = &p.sc->cpart[grp * 512 + eps * 64];
    pkt_clear128(cpart + (a * 8192 + lane)); pkt_clear128(cpart + (a * 8192 + lane) + 32);
    if (a == 3) { pkt_st64(&p.sc->ch[(lane >> 2) * 512 + cid * 4 + (lane & 3)], 0, 0); if (lane < 8) pkt_clear128(&p.sc->cs[cid * 8 + lane]); }
    {
      wait_clk(clk32(), XS_DELAY);
      uint2 v0, v1, cs; uint32_t n = 0;
      const uint32_t t16 = tag & 0xFFFFu;
      bool more;
#pragma unroll 1
      do {
        v0 = pkt_ld64(&p.sc->xz[tau * 256 + j]); v1 = pkt_ld64(&p.sc->xz[tau * 256 + j] + 128); cs = pkt_ld64(&p.sc->dsum[m * 1024 + eps * 128 + j]);
        more = !(__all_sync(0xffffffffu, (v0.x & 0xFFFFu) == t16 && (v1.x & 0xFFFFu) == t16 && cs.y == tag)) && ++n < SPIN_LIMIT;
        if (more) { __nanosleep(200); }
      } while (more);
      const int ro = OFF_RS + ((j & 7) >> 1) * 272 + (j >> 3) * 8 + (j & 1) * 4;
      SM<uint32_t>(ro) = v0.y ^ (m << 31); SM<uint32_t>(ro + 128) = v1.y ^ (m << 31);
      const uint32_t n0 = (v0.x >> 16) ^ 0x8000u, n1 = (v1.x >> 16) ^ 0x8000u;
      SM<uint4>(OFF_EXB + j * 16) = make_uint4(n0 | (n0 << 16), n0, 0, 0);
      SM<uint4>(OFF_EXB + 2048 + j * 16) = make_uint4(n1 | (n1 << 16), n1, 0, 0);
      const float c = 0.5f * __uint_as_float(cs.x), hi = bf16r(c), mid = bf16r(c - hi), lo = bf16r((c - hi) - mid);
      SM<uint4>(OFF_EXA + j * 16) = make_uint4((__float_as_uint(hi) >> 16) | __float_as_uint(mid), __float_as_uint(lo) >> 16, 0, 0);
      fence_async_smem();
      __syncwarp();
      if (lane == 0) mbar_arrive(BAR(B_STAT));
    }
    if (j == 0) TIM(100);
    auto all_published = [&](int half) {
      uint32_t n = 0;
#pragma unroll 1
      while (!__all_sync(0xffffffffu, ld_acquire32(&p.sc->abdone[(cid * 2 + half) * 32 + (lane & 7)]) == tag) && ++n < SPIN_LIMIT) {}
      if (lane == 31) {
        asm volatile("fence.proxy.async.global;" ::: "memory");
        mbar_arrive(BAR(B_ALL + half));
        TIM(80 + half);
      }
      __syncwarp();
    };
    if (TM_PF && j < 3) asm volatile("prefetch.tensormap [%0];" :: "l"(j == 0 ? &p.tmAbS : j == 1 ? &p.tmAbL : m ? &p.tmW1 : &p.tmW0) : "memory");
    {
      if (a == 3) {
        const uint32_t cl = poll64_warp(&p.sc->cl[cid * 16 + (lane & 3)], tag, 100);
        if (lane == 0) TIM(101);
        const bf16* wm = (m ? p.Wim : p.Wre) + tau * 256 + lane * 8;
        uint4 v[8];
#pragma unroll
        for (int i = 0; i < 8; i++) v[i] = ldg128(wm + ((__shfl_sync(0xffffffffu, cl, i >> 1) >> ((i & 1) * 16)) & 2047) * 2048);
        const int pos = cid * 4 + (lane & 3);
        const bf16* xc = p.x + ((__shfl_sync(0xffffffffu, cl, lane >> 3) >> ((lane & 4) * 4)) & 2047) * 1024 + (pos >> 3) * 16 + (pos & 7);
        const float x0 = ldbf(xc), x1 = ldbf(xc + 8), w0 = ldbf(p.wr + (pos >> 3) * 16 + (pos & 7)), w1 = ldbf(p.wr + (pos >> 3) * 16 + (pos & 7) + 8);
        if (lane < 4) SM<uint32_t>(INFO_CAND + lane * 4) = cl;
#pragma unroll
        for (int i = 0; i < 8; i++) SM<uint4>(OFF_WC + (lane >> 3) * 1024 + i * 128 + (((lane & 7) ^ i) << 4)) = v[i];
        fence_async_smem();
        __syncwarp();
        if (lane == 0) { mbar_arrive(BAR(B_WC)); TIM(102); }
        mbar_wait(BAR(B_CD), 0);
        wait_clk(clk32(), CP_DELAY);
        uint32_t n = 0;
        bool more;
#pragma unroll 1
        do {
          uint32_t bad = 0;
#pragma unroll
          for (int i = 0; i < 8; i++) v[i] = pkt_ld128(&p.sc->cpart[((lane >> 3) * 16 + ((lane >> 2) & 1)) * 512 + pos] + i * 1024);
#pragma unroll
          for (int i = 0; i < 8; i++) chk_code(bad, v[i], c0, c1);
          more = !(!__any_sync(0xffffffffu, bad & 1)) && ++n < SPIN_LIMIT;
          if (more) { __nanosleep(200); }
        } while (more);
        float y[4] = {0.f, 0.f, 0.f, 0.f};
#pragma unroll
        for (int i = 0; i < 8; i++) { y[0] += no_bit(v[i].x); y[2] += no_bit(v[i].y); y[1] += no_bit(v[i].z); y[3] += no_bit(v[i].w); }
#pragma unroll
        for (int i = 0; i < 4; i++) y[i] = bf16r(y[i]);
        __syncwarp();
        fold<4>(y, 4, lane);
        const uint32_t hp = pack_bf16(x0 + bf16r(y[0]), x1 + bf16r(y[1]));
        pkt_st64(&p.sc->ch[(lane >> 2) * 512 + pos], hp, tag);
        float st[3] = {bf_lo(hp) + bf_hi(hp), bf_lo(hp) * bf_lo(hp) + bf_hi(hp) * bf_hi(hp), bf_lo(hp) * w0 + bf_hi(hp) * w1};
#pragma unroll
        for (int o = 1; o < 4; o <<= 1) {
#pragma unroll
          for (int i = 0; i < 3; i++) st[i] += __shfl_xor_sync(0xffffffffu, st[i], o);
        }
        if ((lane & 3) == 0) pkt_st128(&p.sc->cs[cid * 8 + (lane >> 2)], with_bit(st[0], c0), with_bit(st[1], c1), __float_as_uint(st[2]), tag);
        if (lane == 0) TIM(119);
      }
      if (a < 2) {
        uint32_t* fl = lane < 2 ? &p.sc->abflag[(cid * 4 + 2 * a + lane) * 32] : &p.sc->abdone[(((cid & 15) + (lane & 7) * 16) * 2 + a) * 32 + tau];
        if (lane == 0) {
          if (a == 1) mbar_wait(BAR(B_SD), 0);
          const uint32_t t1 = clk32();
#pragma unroll 1
          for (int i = 2 * a; i < 2 + 6 * a; i++) {
            const int w = i & 1, c = C1_AUX && a ? (i < 6 ? (i >> 1) + 1 : 1) : i >> 1;
            if (a == 1) wait_clk(t1, HI_DELAY + (i - 2) * HI_PACE);
            mbar_wait(BAR(B_EP + w * 4 + c), 0);
            TIM(64 + i);
            fence_async_smem();
            tma_store_2d(&p.tmAbS, sb + off_stage(c) + w * 8192, tau * 256 + c * 64, abrow + w * 64);
            if (w) { bulk_commit(); bulk_wait_all(); mbar_arrive(BAR(B_SD + c)); }
          }
          TIM(72 + a * 2);
          asm volatile("fence.proxy.async.global;" ::: "memory");
          asm volatile("st.release.gpu.global.b32 [%0], %1;" :: "l"(fl), "r"(tag) : "memory");
          TIM(73 + a * 2);
        }
        __syncwarp();
        if ((lane == 1 && a == 0) || (lane >> 3) == 1) st_relaxed32(fl, tag);
        if (a == 0) { __nanosleep(ALL_NS); all_published(0); }
        else {
          uint32_t n = 0;
#pragma unroll 1
          while (__any_sync(0xffffffffu, ld_acquire32(&p.sc->abflag[(((cid + 16) & 127) * 4 + 2) * 32]) != tag) && ++n < SPIN_LIMIT) {}
#pragma unroll 1
          for (int i = 0; i < 3; i++) {
            if (elect_one()) {
              if (i == 0) asm volatile("fence.proxy.async.global;" ::: "memory");
              mbar_wait(BAR(B_E23 + i), 0);
              tma_load_2d(sb + ((i + 3) & 3) * ST_BYTES, &p.tmAbL, BAR(B_FULL + ((i + 3) & 3)), (tau * 256 + 320 + i * 64) & 2047, abrow);
              TIM(82 + i);
            }
            __syncwarp();
            if (i == ALL_AT) all_published(1);
          }
        }
      } else if (a == 2) {
        const uint32_t* fl = &p.sc->abflag[(((cid + 16 + 16 * (lane & 1)) & 127) * 4 + (lane & 1)) * 32];
        mbar_wait(BAR(B_SD), 0);
        __nanosleep(LO_NS);
        uint32_t n = 0, seen = 0;
#pragma unroll 1
        for (int c = 0; c < 4; c++) {
          const uint32_t n0 = n;
#pragma unroll 1
          while (c < 2 && (PV == 1 ? (seen & 3) != 3 : !((seen >> c) & 1)) && ++n < SPIN_LIMIT) seen = __ballot_sync(0xffffffffu, ld_acquire32(fl) == tag);
          if (PV == 2 ? lane == c : elect_one()) {
            if (!C1_AUX || c != 1) mbar_wait(BAR(B_SD + c), 0);
            mbar_wait(BAR(c < 3 ? B_FULL + c : B_EMPTY), 0);
            if (c == 2) mbar_wait(BAR(B_ALL), 0);
            if (PV == 2 ? c < 2 : n != n0) asm volatile("fence.proxy.async.global;" ::: "memory");
            tma_load_2d(sb + c * ST_BYTES, &p.tmAbL, BAR(B_FULL + c), k_col(tau, 4 + c), abrow);
            TIM(130 + c);
          }
          __syncwarp();
        }
      }
      __syncwarp();
    }
    mbar_wait(BAR(B_CD), 0);
    if (C1_AUX) mbar_wait(BAR(B_SD + 1), 0);
    const uint64_t pol_ef = policy_evict_first();
    auto load_unit = [&](int v) {
      if (elect_one()) {
        const uint32_t dst = buf + (v & 1) * 4096, bar = bar0 + (v & 1) * 8;
        mbar_expect_tx(bar, 4096);
        if (v < 8) {
          LOAD_F(dst, &p.tmG, bar, fc, m * 512 + (a * 8 + v) * 16);
          LOAD_F(dst + 2048, &p.tmU, bar, fc, m * 512 + (a * 8 + v) * 16);
        } else LOAD_F(dst, &p.tmDn, bar, a * 256, src * 32 + (v - 8) * 8);
      }
    };
    if (TM_PF && j < 3) asm volatile("prefetch.tensormap [%0];" :: "l"(j == 0 ? &p.tmG : j == 1 ? &p.tmU : &p.tmDn) : "memory");
    if (ffn && (!LU0_LATE || a == 1)) load_unit(0);
    if (a != 1) {
      bar_sync(NB_SEL, 96);
      wait_clk(clk32(), CS_DELAY);
      fresh_ids();
      if (a == 0 && lane < 8) {
        if (lane == 0) mbar_expect_tx(BAR(B_CH), 16384);
        bulk_load(sb + OFF_AUX + 4096 + (lane >> 1) * 8192 + (lane & 1) * 2048, &p.sc->ch[lane * 512 + m * 256], 2048, BAR(B_CH));
      }
      const int j3 = a ? j - 32 : j;
      uint4 v[11]; uint32_t n = 0;
      bool more;
#pragma unroll 1
      do {
#pragma unroll
        for (int i = 0; i < 11; i++) v[i] = pkt_ld128(&p.sc->cs[j3] + (i < 10 || a < 3 ? i * 96 : 0));
        uint32_t bad = 0;
#pragma unroll
        for (int i = 0; i < 11; i++) { chk(bad, v[i].x, c0); chk(bad, v[i].y, c1); }
        bad &= 1;
#pragma unroll
        for (int i = 0; i < 11; i++) chk(bad, v[i].w, tag);
        more = __any_sync(0xffffffffu, bad) && ++n < SPIN_LIMIT;
        if (more) __nanosleep(200);
      } while (more);
      if (j == 0) TIM(97);
      if (ffn && LU0_LATE) load_unit(0);
      float st[3] = {0.f, 0.f, 0.f};
      if (a < 3) { st[0] = no_bit(v[10].x); st[1] = no_bit(v[10].y); st[2] = __uint_as_float(v[10].z); }
#pragma unroll
      for (int i = 0; i < 10; i++) { st[0] += no_bit(v[i].x); st[1] += no_bit(v[i].y); st[2] += __uint_as_float(v[i].z); }
#pragma unroll
      for (int o = 8; o < 32; o <<= 1) {
#pragma unroll
        for (int i = 0; i < 3; i++) st[i] += __shfl_xor_sync(0xffffffffu, st[i], o);
      }
      if (lane < 8) SM<float4>(OFF_XS + ((j3 >> 5) * 8 + lane) * 16) = make_float4(st[0], st[1], st[2], 0.f);
      bar_sync(NB_SEL, 96);
      const float4 f0 = SM<float4>(OFF_XS + (lane & 7) * 16), f1 = SM<float4>(OFF_XS + 128 + (lane & 7) * 16), f2 = SM<float4>(OFF_XS + 256 + (lane & 7) * 16);
      const float mu = ((f0.x + f1.x) + f2.x) * (1.f / 1024.f);
      float mb = bf16r(mu), inv = fast_rcp(ref_sd(fmaxf(((f0.y + f1.y) + f2.y) * (1.f / 1024.f) - mu * mu, 0.f)));
      const uint32_t kk = make_key(bf16r((((f0.z + f1.z) + f2.z) - mb * SM<float>(INFO_WSUM)) * inv), SM<uint16_t>(INFO_CAND + (lane & 7) * 2));
      const uint32_t key = __reduce_max_sync(0xffffffffu, kk);
      const int win = __ffs(__ballot_sync(0xffffffffu, kk == key)) - 1;
      mb = __shfl_sync(0xffffffffu, mb, win); inv = __shfl_sync(0xffffffffu, inv, win);
      if (j == 0) { SM<uint2>(INFO_KEY) = make_uint2(key, win); SM<float2>(INFO_LN) = make_float2(mb, inv); }
      mbar_wait(BAR(B_CH), 0);
      bar_sync(NB_SEL, 96);
#pragma unroll 1
      for (int i = j3; i < 128; i += 96) {
        uint4 r = lds128(sb + OFF_AUX + 4096 + (win >> 1) * 8192 + (win & 1) * 2048 + i * 16);
#pragma unroll 1
        while ((r.y != tag || r.w != tag) && ++n < SPIN_LIMIT) r = pkt_ld128(&p.sc->ch[win * 512 + m * 256 + 2 * i]);
        auto ln = [&](float h) { return bf16r(bf16r(h - mb) * inv); };
        const int d = (i >> 2) * 16 + (i & 3) * 2;
        SM<float2>(OFF_XS + d * 4) = make_float2(ln(bf_lo(r.x)), ln(bf_lo(r.z)));
        SM<float2>(OFF_XS + (d + 8) * 4) = make_float2(ln(bf_hi(r.x)), ln(bf_hi(r.z)));
      }
      __syncwarp();
    }
    bar_sync(NB_AUX, 128);
    if (j == 0) {
      mbar_arrive(BAR(B_INFO)); TIM(103);
      if (cid == 0) st_relaxed32(&p.sc->epoch, tag);
    }
    const uint32_t t2 = clk32();
    fresh_ids();
    uint2 hp2 = make_uint2(0, 0);
    const uint2* hpp = &p.sc->ch[SM<uint32_t>(INFO_KEY + 4) * 512 + (cid >> 1) * 8 + (lane & 7)];
    if (a == 3) { hp2 = pkt_ld64(hpp); if (lane == 0) asm volatile("prefetch.tensormap [%0];" :: "l"(&p.tmY) : "memory"); }
    if (!ffn) {
      wait_clk(t2, YPART_DELAY);
    } else {
      load_unit(1);
      const int r = lane >> 3;
      float acc[8] = {0.f, 0.f, 0.f, 0.f, 0.f, 0.f, 0.f, 0.f};
#pragma unroll 1
      for (int v = 0; v < 8; v++) {
        const uint4 x0 = lds128(sb + OFF_XS + ((a * 8 + v) * 16 + (r & 1) * 8) * 4), x1 = lds128(sb + OFF_XS + ((a * 8 + v) * 16 + (r & 1) * 8 + 4) * 4);
        const float xv[8] = {__uint_as_float(x0.x), __uint_as_float(x0.y), __uint_as_float(x0.z), __uint_as_float(x0.w), __uint_as_float(x1.x), __uint_as_float(x1.y), __uint_as_float(x1.z), __uint_as_float(x1.w)};
        mbar_wait(bar0 + (v & 1) * 8, (v >> 1) & 1);
        gemv8x8<128>(acc, buf + (v & 1) * 4096 + r * 1024 + (lane & 7) * 16, xv);
        fence_regs(acc);
        __syncwarp();
        wait_clk(t2, v * UNIT_PACE);
        load_unit(v + 2);
        if (j == 0) TIM(104 + v);
      }
      pkt_clear128(&p.sc->ypart[(a * NSRC + src) * 64 + lane * 2]); pkt_clear128(&p.sc->ypart[(a * NSRC + src) * 64 + lane * 2] + 1);
      fold<8>(acc, 8, lane);
      bar_sync(NB_AUX, 128);
      SM<float4>(OFF_XS + (a * 128 + (r >> 1) * 64 + (lane & 7) * 8 + (r & 1) * 4) * 4) = make_float4(acc[0], acc[1], acc[2], acc[3]);
      bar_sync(NB_AUX, 128);
      auto psum = [&](int i) { return (SM<float>(OFF_XS + i * 4) + SM<float>(OFF_XS + (128 + i) * 4)) + (SM<float>(OFF_XS + (256 + i) * 4) + SM<float>(OFF_XS + (384 + i) * 4)); };
      if (a < 2) st_async_b32(mapa(sb + OFF_REM + j * 4, m ^ 1), mapa(BAR(B_GUX), m ^ 1), __float_as_uint(psum(a * 64 + (m ^ 1) * 32 + lane)));
      const float og = psum(m * 32 + lane), ou = psum(64 + m * 32 + lane);
      mbar_wait(BAR(B_GUX), 0);
      const float rg = SM<float>(OFF_REM + lane * 4), ru = SM<float>(OFF_REM + 128 + lane * 4);
      const float act = swiglu(m ? rg + og : og + rg, m ? ru + ou : ou + ru);
      if (j == 0) TIM(112);
      float y[8] = {0.f, 0.f, 0.f, 0.f, 0.f, 0.f, 0.f, 0.f};
#pragma unroll 1
      for (int v = 8; v < 12; v++) {
        float av[8];
#pragma unroll
        for (int i = 0; i < 8; i++) av[i] = __shfl_sync(0xffffffffu, act, (v - 8) * 8 + i);
        mbar_wait(bar0 + (v & 1) * 8, (v >> 1) & 1);
        gemv8x8<512>(y, buf + (v & 1) * 4096 + lane * 16, av);
        fence_regs(y);
        __syncwarp();
        if (v < 10) load_unit(v + 2);
        if (j == 0) TIM(105 + v);
      }
      fresh_ids();
      uint4* ypart = &p.sc->ypart[(a * NSRC + src) * 64 + lane * 2];
      pkt_st128(ypart, with_bit(y[0], c0), with_bit(y[1], c1), with_bit(y[2], c0), with_bit(y[3], c1));
      pkt_st128(ypart + 1, with_bit(y[4], c0), with_bit(y[5], c1), with_bit(y[6], c0), with_bit(y[7], c1));
      if (lane == 0) TIM(160 + a);
      __nanosleep(ROW_NS);
    }
    if (a == 3) {
      const uint32_t hh = __all_sync(0xffffffffu, hp2.y == tag) ? hp2.x : poll64_warp(&p.sc->ch[SM<uint32_t>(INFO_KEY + 4) * 512 + (cid >> 1) * 8 + (lane & 7)], tag, 100);
      const uint32_t key = SM<uint32_t>(INFO_KEY);
      const float h = m ? bf_hi(hh) : bf_lo(hh), hn = bf16r(bf16r(h - SM<float>(INFO_LN)) * SM<float>(INFO_LN + 4));
      float sig = sigmoid_bf(key_val(key));
      bf16* op = p.out + (key_row(key) * 1024 + cid * 8 + (lane & 7));
      asm volatile("" : "+f"(sig), "+l"(op));
      uint4 v[7]; uint32_t n = 0;
      bool more;
#pragma unroll 1
      do {
        if (elect_one()) { mbar_expect_tx(bar0, NSRC * 32); tma_load_2d(buf, &p.tmY, bar0, (cid & 31) * 16, (cid >> 5) * NSRC); }
        mbar_wait(bar0, n & 1);
        uint32_t bad = 0;
#pragma unroll
        for (int i = 0; i < 7; i++) { v[i] = lds128(buf + i * 512 + lane * 16); chk_code(bad, v[i], c0, c1); }
        more = __any_sync(0xffffffffu, bad & 1) && ++n < SPIN_LIMIT;
        if (more) __nanosleep(Y_NS);
      } while (more);
      if (lane == 0) TIM(164);
      float y[4] = {0.f, 0.f, 0.f, 0.f};
#pragma unroll
      for (int i = 0; i < 7; i++) { y[0] += no_bit(v[i].x); y[1] += no_bit(v[i].y); y[2] += no_bit(v[i].z); y[3] += no_bit(v[i].w); }
      fold<4>(y, 16, lane); fold<2>(y, 8, lane);
      y[0] += __shfl_xor_sync(0xffffffffu, y[0], 4);
      y[0] += __shfl_xor_sync(0xffffffffu, y[0], 2);
      const float ys = __shfl_sync(0xffffffffu, y[0], (lane & 3) * 8 + ((lane >> 2) & 1));
      if (lane < 8) st_bf16(op, routed_out(h, hn, ys, sig));
      if (lane == 0) { TIM(118); pkt_st64(&p.sc->rdone[cid], 0, tag); }
    }
  } else {
    reg_inc<216>();
    cluster_wait();
    const uint32_t sb = __shfl_sync(0xffffffffu, smem_u32(smem_raw), 0);
    auto BAR = [&](int i) { return sb + OFF_BAR + 8 * i; };
    const int w = warp >> 2, wi = warp & 3, t = tid & 127;
    const int turn_me = NB_TURN0 + w, turn_other = NB_TURN1 - w;
    const uint64_t dA0 = make_desc(sb + w * 8192);
    uint64_t dA, dB;
    int tau, eps, m, grp, abrow, fc, src;
    bool ffn;
    const CUtensorMap* tmD; const CUtensorMap* tmW;
    auto new_desc = [&](int salt) {
      const uint32_t z = salt < 0 ? uniform_zero_here() : salt & blockIdx.y;
      dA = dA0 + z; dB = dA0 + (z + ((A_BYTES - w * 8192) >> 4));
      const int c = cid + z;
      tau = c >> 4; eps = (c >> 1) & 7; m = c & 1; grp = tau * 2 + m; abrow = m * 1024 + eps * 128;
      ffn = eps > 0; fc = (tau * 7 + eps - 1) * 64; src = (fc >> 5) + m;
      tmD = &p.tmD0 + m; tmW = &p.tmW0 + m;
    };
    constexpr int SL = ST_BYTES >> 4;
    float acc[128];
#pragma unroll
    for (int i = 0; i < 128; i++) acc[i] = 0.f;
    if (w == 1) bar_arrive(NB_TURN0, 256);
    auto full = [&](int k) { mbar_wait(BAR(B_FULL + (k & 3)), (k >> 2) & 1); CT(64 + k); };
    const uint64_t pol_ef = policy_evict_first();
    auto refill_g2 = [&](int k, int mode) {
      if (warp == 4) {
        if (elect_one()) {
          const int s = k & 3, s0 = k_col(tau, k - 12);
          TIM(k + 4);
          mbar_expect_tx(BAR(B_FULL + s), mode ? ST_BYTES : B_BYTES);
          if (k == 19) mbar_arrive(BAR(B_EMPTY));
          LOAD_W(sb + s * ST_BYTES + A_BYTES, tmW, BAR(B_FULL + s), s0, grp * 128);
          LOAD_W(sb + s * ST_BYTES + A_BYTES + 16384, tmW, BAR(B_FULL + s), s0, (grp ^ 1) * 128);
          if (mode == 2) tma_load_2d(sb + s * ST_BYTES, &p.tmAbL, BAR(B_FULL + s), s0, abrow);
        }
        __syncwarp();
      }
    };
    auto mma_ss = [&](int k) {
#pragma unroll
      for (int kk = 0; kk < 4; kk++) wgmma_n256(acc, dA + (k & 3) * SL + kk * 2, dB + (k & 3) * SL + kk * 2);
    };
    const CUtensorMap* rf_tm; uint32_t rf_dst; int rf_row, rf_c; bool rf_on;
    auto rf_set = [&](const CUtensorMap* tm, uint32_t dst, int row) {
      rf_tm = (const CUtensorMap*)__shfl_sync(0xffffffffu, (unsigned long long)tm, 0);
      rf_dst = __shfl_sync(0xffffffffu, dst, 0); rf_row = __shfl_sync(0xffffffffu, row, 0);
    };
    auto refill = [&](int s) {
      if (rf_on) {
        if (elect_one()) tma_load_2d(rf_dst + s * ST_BYTES, rf_tm, BAR(B_FULL + s), rf_c, rf_row);
        __syncwarp();
      }
      if (tid == 224) mbar_expect_tx(BAR(B_FULL + s), ST_BYTES);
    };
    const bf16* pf; int pf_step; bool pf_on;
    auto pf_ffn = [&](int v) {
      pf_on = ffn && v >= 0 && v < 12;
      pf = v < 8 ? ((lane & 16) ? p.wup : p.wgate) + (m * 512 + (wi * 8 + v) * 16 + (lane & 15)) * 3584 + fc : p.wdown + (src * 32 + (v - 8) * 8) * 1024 + t * 64;
      pf_step = v < 8 ? 16 * 3584 : 8192;
    };
    auto prefetch = [&](int s) { if (pf_on && (wi >> 1) == (s & 1)) prefetch_l2(pf + (s >> 1) * pf_step); };
    auto kstep = [&](int k) {
      full(k);
      bar_sync(turn_me, 256);
      wgmma_fence();
      mma_ss(k);
      wgmma_commit();
      bar_arrive(turn_other, 256);
    };

    uint32_t R[64];
    auto load_rs = [&](auto gi) {
      const uint32_t rsa = sb + OFF_RS + (lane & 3) * 272;
#pragma unroll
      for (int i = 4 * decltype(gi)::value; i < 4 * decltype(gi)::value + 4; i++) { const uint4 v = lds128(rsa + i * 16); R[4 * i] = v.x; R[4 * i + 1] = v.y; R[4 * i + 2] = v.z; R[4 * i + 3] = v.w; }
    };
#pragma unroll
    for (int i = 0; i < (RS_EARLY ? 16 : 0); i++) R[i] = 0;
    new_desc(64);
    rf_on = (warp >> 1) == 2;
    rf_set(wi ? tmD : &p.tmX, wi ? sb : sb + A_BYTES, wi ? eps * 128 : tau * 256);
#pragma unroll 1
    for (int k4 = 0; k4 < 12; k4 += 4) {
#pragma unroll
      for (int s = 0; s < 4; s++) {
        kstep(k4 | s);
        if (s == 0) {
          if (w == 0) pf_ffn((k4 >> 1) - 2);
          else {
            pf_on = W_PF && (k4 == 8 || (W_PF > 1 && k4 == 4 && (lane & 7) < 3));
            pf = (m ? p.Wim : p.Wre) + (tau * 256 + eps * 32 + wi * 4 + (lane >> 3)) * 2048 + k_col(tau, (lane & 7) + (W_PF > 1 && k4 == 8 ? 3 : 0));
            pf_step = 16 * 2048;
          }
        }
        rf_c = (k4 + s + 4) * 64;
        prefetch(s);
        if (RS_EARLY && s == 3 && k4 == 8) { mbar_wait(BAR(B_STAT), 0); load_rs(std::integral_constant<int, 0>()); }
        if (s == 3) new_desc(k4);
        if (s == 0 || s == 3) pf += zero_here();
        wgmma_wait<0>();
        refill(s);
      }
    }
    kstep(12);
    if (!RS_EARLY) { mbar_wait(BAR(B_STAT), 0); load_rs(std::integral_constant<int, 0>()); }
    CT(1);
    load_rs(std::integral_constant<int, 1>());
    if (RS_EARLY == 2) load_rs(std::integral_constant<int, 3>());
    wgmma_wait<0>(); refill_g2(12, 0);
    if (RS_EARLY < 2) load_rs(std::integral_constant<int, 3>());
    auto mma_h = [&](float (&d)[64], int s, int half) {
#pragma unroll
      for (int kk = 0; kk < 4; kk++) wgmma_n128(d, dA + s * SL + kk * 2, dB + s * SL + half * 1024 + kk * 2);
    };
    const int rho = 16 * wi + (lane & 15);
    const uint32_t arow = sb + w * 8192 + rho * 128;
    auto convert = [&](auto cc, float (&d)[64]) {
      const float z = __uint_as_float(zero_here());
#pragma unroll
      for (int jj = 8 * decltype(cc)::value; jj < 8 * decltype(cc)::value + 8; jj++) {
        const float r0 = __uint_as_float(R[2 * jj]), r1 = __uint_as_float(R[2 * jj + 1]);
        const float* ac = &d[4 * (jj & 15)];
        R[2 * jj] = pack_bf16(fmaf(ac[0], r0, z), fmaf(ac[1], r1, z));
        R[2 * jj + 1] = pack_bf16(fmaf(ac[2], r0, z), fmaf(ac[3], r1, z));
      }
    };
    auto put = [&](auto cc) {
      constexpr int c = decltype(cc)::value;
#pragma unroll
      for (int jj = 8 * c; jj < 8 * c + 8; jj += 2)
        stsm_x4(arow + off_stage(c) + ((((jj & 7) + (lane >> 4)) ^ (rho & 7)) << 4), R[2 * jj], R[2 * jj + 1], R[2 * jj + 2], R[2 * jj + 3]);
      __syncwarp();
      if (lane == 0) mbar_arrive(BAR(B_EP + w * 4 + c));
    };
    {
      float lo[64], hi[64];
      fence_regs(acc);
#pragma unroll
      for (int i = 0; i < 64; i++) asm volatile("mov.b32 %0, %1;" : "=f"(lo[i]) : "f"(acc[i]));
#pragma unroll
      for (int i = 0; i < 64; i++) asm volatile("mov.b32 %0, %1;" : "=f"(hi[i]) : "f"(acc[64 + i]));
      const uint64_t dEA = make_desc_noswz(sb + OFF_EXA + w * 1024), dEB = make_desc_noswz(sb + OFF_EXB);
      full(13); full(14);
      bar_sync(turn_me, 256);
      wgmma_fence();
      mma_h(lo, 1, 0); mma_h(lo, 2, 0);
      wgmma_commit();
      bar_arrive(turn_other, 256);
      if (RS_EARLY == 3) load_rs(std::integral_constant<int, 3>());
      new_desc(ND1);
      full(15);
      bar_sync(turn_me, 256);
      wgmma_fence();
      mma_h(lo, 3, 0);
      wgmma_n128(lo, dEA, dEB);
      wgmma_commit();
      mma_h(hi, 1, 1);
      wgmma_commit();
      bar_arrive(turn_other, 256);
      new_desc(ND2);
      wgmma_wait<1>();
      fence_regs(lo);
      CT(15);
      convert(std::integral_constant<int, 0>(), lo); put(std::integral_constant<int, 0>());
      convert(std::integral_constant<int, 1>(), lo);
      wgmma_wait<0>(); refill_g2(13, 0);
      if (!PUT1_LATE) put(std::integral_constant<int, 1>());
      bar_sync(turn_me, 256);
      wgmma_fence();
      mma_h(hi, 2, 1);
      wgmma_commit();
      mma_h(hi, 3, 1);
      wgmma_n128(hi, dEA, dEB + 128);
      wgmma_commit();
      bar_arrive(turn_other, 256);
      load_rs(std::integral_constant<int, 2>());
      if (PUT1_LATE) put(std::integral_constant<int, 1>());
      wgmma_wait<1>(); refill_g2(14, 0);
      wgmma_wait<0>(); refill_g2(15, 0);
      fence_regs(hi);
      CT(2);
      if (HI_ORDER == 0) {
        convert(std::integral_constant<int, 3>(), hi);
        put(std::integral_constant<int, 3>());
        convert(std::integral_constant<int, 2>(), hi);
      } else {
        full(16);
        convert(std::integral_constant<int, 3>(), hi);
        convert(std::integral_constant<int, 2>(), hi);
      }
    }
    CT(3);
    float cc[4];
    auto cand_mma = [&]() {
      const uint64_t dC = make_desc(sb + OFF_WC);
      wgmma_n8_rs<0>(cc, R, dC);
#pragma unroll
      for (int i = 1; i < 12; i++) wgmma_n8_rs<1>(cc, R + 4 * i, dC + (i >> 2) * 64 + (i & 3) * 2);
#pragma unroll
      for (int kk = 0; kk < 4; kk++) wgmma_n8(cc, dA + 3 * SL + kk * 2, dC + 192 + kk * 2);
      wgmma_commit();
    };
    auto cand_pub = [&]() {
      fence_regs(cc);
      const uint32_t cd = code_of(SM<uint32_t>(INFO_TAG));
      if (t == 0) mbar_arrive(BAR(B_CD));
      pkt_st128(&p.sc->cpart[((lane & 3) * 16 + grp) * 512 + eps * 64 + warp * 8 + (lane >> 2)], with_bit(cc[0], cd), with_bit(cc[1], cd >> 1), with_bit(cc[2], cd), with_bit(cc[3], cd >> 1));
      CT(5);
    };
    new_desc(ND3);
    if (HI_ORDER == 1) put(std::integral_constant<int, 3>());
    if (CAND_EARLY) { fence_async_smem(); mbar_wait(BAR(B_WC), 0); CT(4); }
    if (HI_ORDER == 0) full(16);
    if (!SPLIT17) full(17);
    bar_sync(turn_me, 256);
    wgmma_fence();
    if (CAND_EARLY) cand_mma();
    wgmma_n256_rs_init(acc, R, dB);
#pragma unroll
    for (int kk = 1; kk < 4; kk++) wgmma_n256_rs<1>(acc, R + 4 * kk, dB + kk * 2);
    wgmma_commit();
    if (SPLIT17) { full(17); wgmma_fence(); }
#pragma unroll
    for (int kk = 0; kk < 4; kk++) wgmma_n256_rs<1>(acc, R + 16 + 4 * kk, dB + SL + kk * 2);
    wgmma_commit();
    bar_arrive(turn_other, 256);
    if (CAND_EARLY) { wgmma_wait<2>(); put(std::integral_constant<int, 2>()); cand_pub(); }
    else put(std::integral_constant<int, 2>());
    wgmma_wait<1>(); refill_g2(16, 1);
    wgmma_wait<0>(); refill_g2(17, 1);
    if (!CAND_EARLY) { fence_async_smem(); mbar_wait(BAR(B_WC), 0); CT(4); }
    full(18);
    bar_sync(turn_me, 256);
    wgmma_fence();
    if (!CAND_EARLY) cand_mma();
#pragma unroll
    for (int kk = 0; kk < 4; kk++) wgmma_n256_rs<1>(acc, R + 32 + 4 * kk, dB + 2 * SL + kk * 2);
    wgmma_commit();
    bar_arrive(turn_other, 256);
    if (!CAND_EARLY) { wgmma_wait<1>(); cand_pub(); }
    wgmma_wait<0>(); refill_g2(18, 1);
    kstep(19);
    new_desc(68);
    rf_set(wi == 2 ? &p.tmAbL : tmW, wi == 2 ? sb : sb + A_BYTES + wi * 16384, wi == 2 ? abrow : (grp ^ wi) * 128);
    wgmma_wait<0>(); refill_g2(19, 1);
    const int g = lane >> 2, q = lane & 3;
    uint4 ha[4], hb[4], wv[4], info = make_uint4(0, 0, 0, 0);
#pragma unroll
    for (int i = 0; i < 4; i++) ha[i] = hb[i] = wv[i] = make_uint4(0, 0, 0, 0);
    auto load_x = [&](auto ii) {
      constexpr int i = decltype(ii)::value;
      const bf16* xp = p.x + ((grp * 128 + warp * 16 + g) * 1024 + eps * 128 + q * 8);
      ha[i] = ldg128(xp + i * 32); hb[i] = ldg128(xp + 8192 + i * 32);
    };
    auto load_w = [&]() {
      mbar_wait(BAR(B_INFO), 0);
#pragma unroll
      for (int i = 0; i < 4; i++) wv[i] = lds128(sb + ((g & 1) ? OFF_WR + (i * 4 + q) * 16 : INFO_ONES));
      info = lds128(sb + OFF_INFO);
    };

    rf_on = w == 1 && wi < 3;
    rf_c = k_col(tau, 7);
#pragma unroll 1
    for (int k4 = 20; k4 < 44; k4 += 4) {
#pragma unroll
      for (int s = 0; s < 4; s++) {
        kstep(k4 | s);
        if (s == 0) {
          if (w == 0) { pf_ffn((k4 >> 1) - PF2_K / 2 + 4); pf_on = pf_on && k4 >= PF2_K; }
          else {
            pf_on = k4 == XPF_K;
            pf = p.x + (grp * 128 + (t >> 1)) * 1024 + eps * 128 + (t & 1) * 64;
            pf_step = 64 * 1024;
          }
        }
        rf_c = k_next(rf_c, k4 + s - 12);
        if (s == 0 && k4 == 20 && warp == 6) mbar_wait(BAR(B_ALL), 0);
        if (s == 2 && k4 == 24 && warp == 6) mbar_wait(BAR(B_ALL + 1), 0);
        prefetch(s);
        if (k4 == 40) {
          if (s == XS0 - 1) load_w();
          if (s == XS0) load_x(std::integral_constant<int, 0>());
          if (s == XS0 + 1) load_x(std::integral_constant<int, 1>());
          if (s == XS0 + 2) load_x(std::integral_constant<int, 2>());
        }
        if (s == 3) new_desc(k4);
        if (s == 0 || s == 3) pf += zero_here();
        wgmma_wait<0>();
        if (((s == 3 && k4 == 20) || (s < 2 && k4 == 24)) && warp == 6) { if (lane == 0) mbar_arrive(BAR(B_E23 + ((s + 1) & 3))); }
        else refill(s);
      }
    }
    const int row0 = grp * 128 + warp * 16 + g;
    kstep(44);
    uint4* hst = &p.sc->hstat[grp * 1024 + warp * 16 + g];
    if (q == (g >> 1)) { pkt_clear128(hst + eps * 128); pkt_clear128(hst + eps * 128 + 8); }
    if (XS0 == 9) { load_w(); load_x(std::integral_constant<int, 0>()); load_x(std::integral_constant<int, 1>()); load_x(std::integral_constant<int, 2>()); load_x(std::integral_constant<int, 3>()); }
    if (XS0 == 1) load_x(std::integral_constant<int, 3>());
    if (XS0 == 2) load_x(std::integral_constant<int, 2>());
    if (XS0 == 3) load_x(std::integral_constant<int, 1>());
    wgmma_wait<0>();
    if (tid == 128) mbar_arrive_remote(mapa(BAR(B_PEER), m ^ 1));
    uint32_t hp[32];
    bf16* op; uint4* hpub;
    uint32_t cd, ast, ald, zr;
    auto swz = [](int row) { return ((row & 1) << 2) | ((row >> 1) & 3); };
    {
      float as[64], ak[64];
      fence_regs(acc);
#pragma unroll
      for (int i = 0; i < 64; i++) asm volatile("mov.b32 %0, %1;" : "=f"(as[i]) : "f"(acc[64 + i]));
#pragma unroll
      for (int i = 0; i < 64; i++) asm volatile("mov.b32 %0, %1;" : "=f"(ak[i]) : "f"(acc[i]));
      full(45); full(46);
      bar_sync(turn_me, 256);
      wgmma_fence();
      mma_h(as, 1, 1); mma_h(as, 2, 1);
      wgmma_commit();
      bar_arrive(turn_other, 256);
      if (XS0 == 2) load_x(std::integral_constant<int, 3>());
      if (XS0 == 3) { load_x(std::integral_constant<int, 2>()); load_x(std::integral_constant<int, 3>()); }
      full(47);
      bar_sync(turn_me, 256);
      wgmma_fence();
      mma_h(as, 3, 1);
      wgmma_commit();
      mma_h(ak, 1, 0);
      wgmma_commit();
      bar_arrive(turn_other, 256);
      const uint32_t rx = mapa(sb + OFF_RECV + w * 16384 + t * 16, m ^ 1), rb = mapa(BAR(B_XCH + w), m ^ 1);
      mbar_wait(BAR(B_PEER), 0);
      wgmma_wait<1>();
      fence_regs(as);
      CT(6);
#pragma unroll
      for (int i = 0; i < 8; i++) {
        const float* ac = &as[8 * i];
        st_async_v4(rx + i * 2048, rb, pack_bf16(ac[0], ac[1]), pack_bf16(ac[2], ac[3]), pack_bf16(ac[4], ac[5]), pack_bf16(ac[6], ac[7]));
      }
      CT(7);
      bar_sync(turn_me, 256);
      wgmma_fence();
      mma_h(ak, 2, 0); mma_h(ak, 3, 0);
      wgmma_commit();
      if (w == 0) bar_arrive(turn_other, 256);
      op = p.out + row0 * 1024 + eps * 128 + q * 8;
      hpub = hst + eps * 128; hst += q * 256;
      cd = code_of(info.y);
      ast = sb + w * ST_BYTES + (8 * (lane >> 4) + (lane & 7)) * 128 + (((2 * wi + ((lane >> 3) & 1)) ^ swz(lane & 7)) << 4);
      ald = sb + (warp * 16 + g) * 128 + ((q ^ swz(g)) << 4);
      asm volatile("" : "+l"(op), "+l"(hpub), "+l"(hst), "+r"(cd), "+r"(ast), "+r"(ald));
      zr = zero_here();
#pragma unroll
      for (int i = 0; i < 4; i++) { ha[i].x += zr; hb[i].x += zr; asm volatile("" : "+r"(ha[i].x), "+r"(hb[i].x)); }
      ast += (uint32_t)(clock64() >> 32) & zr;
      mbar_wait(BAR(B_XCH + w), 0);
      CT(9);
#pragma unroll
      for (int i = 0; i < 8; i++) { const uint4 v = lds128(sb + OFF_RECV + w * 16384 + t * 16 + i * 2048); hp[4 * i] = v.x; hp[4 * i + 1] = v.y; hp[4 * i + 2] = v.z; hp[4 * i + 3] = v.w; }
      wgmma_wait<0>();
      fence_regs(ak);
      CT(10);
#pragma unroll
      for (int i = 0; i < 32; i++) hp[i] = badd2(pack_bf16(ak[2 * i], ak[2 * i + 1]), hp[i]);
    }
#pragma unroll
    for (int jj = 0; jj < 16; jj += 2) stsm_x4_t(ast + jj * 1024, hp[2 * jj], hp[2 * jj + 1], hp[2 * jj + 2], hp[2 * jj + 3]);
    tag = info.y;
    bar_sync(NB_BOTH, 256);
    CT(11);
    uint4 v[4];
    auto fetch = [&]() { v[0] = pkt_ld128(hst); v[1] = pkt_ld128(hst + 128); v[2] = pkt_ld128(hst + 8); v[3] = pkt_ld128(hst + 136); };
    float st[6], hf[64];
    {
      uint4 ya[4], yb[4];
#pragma unroll
      for (int i = 0; i < 4; i++) {
        const uint32_t ad = (ald ^ ((i & 1) << 6)) + (i >> 1) * ST_BYTES;
        ya[i] = lds128(ad); yb[i] = lds128(ad + 1024);
      }
      fetch();
      const float z = __uint_as_float((uint32_t)(clock64() >> 32) & zr);
      float sw[2][4], qa[2][4], qb[2][4];
#pragma unroll
      for (int i = 0; i < 8; i++) { sw[i >> 2][i & 3] = i ? 0.f : z; qa[i >> 2][i & 3] = 0.f; qb[i >> 2][i & 3] = 0.f; }
#pragma unroll
      for (int i = 0; i < 4; i++) {
        ha[i] = make_uint4(badd2(ha[i].x, ya[i].x), badd2(ha[i].y, ya[i].y), badd2(ha[i].z, ya[i].z), badd2(ha[i].w, ya[i].w));
        hb[i] = make_uint4(badd2(hb[i].x, yb[i].x), badd2(hb[i].y, yb[i].y), badd2(hb[i].z, yb[i].z), badd2(hb[i].w, yb[i].w));
        mma16816(sw[0], ha[i].x, hb[i].x, ha[i].y, hb[i].y, wv[i].x, wv[i].y);
        mma16816(qa[0], ha[i].x, hb[i].x, ha[i].y, hb[i].y, ha[i].x, ha[i].y);
        mma16816(qb[0], ha[i].x, hb[i].x, ha[i].y, hb[i].y, hb[i].x, hb[i].y);
        mma16816(sw[1], ha[i].z, hb[i].z, ha[i].w, hb[i].w, wv[i].z, wv[i].w);
        mma16816(qa[1], ha[i].z, hb[i].z, ha[i].w, hb[i].w, ha[i].z, ha[i].w);
        mma16816(qb[1], ha[i].z, hb[i].z, ha[i].w, hb[i].w, hb[i].z, hb[i].w);
      }
      const uint32_t s0 = with_bit(sw[0][0] + sw[1][0], cd), s1 = with_bit((g & 1) ? qa[0][1] + qa[1][1] : qa[0][0] + qa[1][0], cd >> 1), s2 = __float_as_uint(sw[0][1] + sw[1][1]);
      const uint32_t s3 = with_bit(sw[0][2] + sw[1][2], cd), s4 = with_bit((g & 1) ? qb[0][3] + qb[1][3] : qb[0][2] + qb[1][2], cd >> 1), s5 = __float_as_uint(sw[0][3] + sw[1][3]);
      if (q == (g >> 1)) { pkt_st128(hpub, s0, s1, s2, tag); pkt_st128(hpub + 8, s3, s4, s5, tag); }
      CT(12);
      if (PRE_UNPACK) {
#pragma unroll
        for (int i = 0; i < 8; i++) {
          const uint4 h = i < 4 ? ha[i] : hb[i - 4];
          hf[8 * i] = bf_lo(h.x); hf[8 * i + 1] = bf_hi(h.x); hf[8 * i + 2] = bf_lo(h.y); hf[8 * i + 3] = bf_hi(h.y);
          hf[8 * i + 4] = bf_lo(h.z); hf[8 * i + 5] = bf_hi(h.z); hf[8 * i + 6] = bf_lo(h.w); hf[8 * i + 7] = bf_hi(h.w);
        }
        fence_regs(hf);
        op += (uint32_t)(clock64() >> 32) & zr;
      }
      const uint32_t o1 = __shfl_sync(0xffffffffu, s1, (lane & 28) | (g >> 1)), o4 = __shfl_sync(0xffffffffu, s4, (lane & 28) | (g >> 1));
      uint32_t n = 0;
      bool more;
#pragma unroll 1
      do {
        if (2 * q == eps) { v[0] = make_uint4(s0, o1, s2, tag); v[2] = make_uint4(s3, o4, s5, tag); }
        if (2 * q + 1 == eps) { v[1] = make_uint4(s0, o1, s2, tag); v[3] = make_uint4(s3, o4, s5, tag); }
        uint32_t bad = 0;
#pragma unroll
        for (int i = 0; i < 4; i++) { chk(bad, v[i].x, cd); chk(bad, v[i].y, cd >> 1); }
        bad &= 1;
#pragma unroll
        for (int i = 0; i < 4; i++) chk(bad, v[i].w, tag);
        more = !(!__any_sync(0xffffffffu, bad)) && ++n < SPIN_LIMIT;
        if (more) { if (bad) fetch(); }
      } while (more);
      st[0] = no_bit(v[0].x) + no_bit(v[1].x); st[1] = no_bit(v[0].y) + no_bit(v[1].y); st[2] = __uint_as_float(v[0].z) + __uint_as_float(v[1].z);
      st[3] = no_bit(v[2].x) + no_bit(v[3].x); st[4] = no_bit(v[2].y) + no_bit(v[3].y); st[5] = __uint_as_float(v[2].z) + __uint_as_float(v[3].z);
    }
    CT(13);
#pragma unroll
    for (int o = 1; o < 4; o <<= 1) {
#pragma unroll
      for (int i = 0; i < 6; i++) st[i] += __shfl_xor_sync(0xffffffffu, st[i], o);
    }
    float mb[2], inv[2];
#pragma unroll
    for (int i = 0; i < 2; i++) {
      const float mu = st[3 * i] * (1.f / 1024.f);
      mb[i] = bf16r(mu);
      inv[i] = fast_rcp(ref_sd(fmaxf(st[3 * i + 1] * (1.f / 1024.f) - mu * mu, 0.f)));
    }
    {
      const int srow = key_row(info.z);
      auto put_out = [&](bf16* dst, const uint4& h, const float* f, float sc, float of, bool on) {
        auto cvt = [&](uint32_t x, int i) { return PRE_UNPACK ? pack_bf16(fmaf(f[i], sc, of), fmaf(f[i + 1], sc, of)) : pack_bf16(fmaf(bf_lo(x), sc, of), fmaf(bf_hi(x), sc, of)); };
        asm volatile("{\n.reg .pred p;\nsetp.ne.b32 p, %5, 0;\n@p st.global.v4.b32 [%0], {%1, %2, %3, %4};\n}\n"
                     :: "l"(dst), "r"(cvt(h.x, 0)), "r"(cvt(h.y, 2)), "r"(cvt(h.z, 4)), "r"(cvt(h.w, 6)), "r"((int)on) : "memory");
      };
#pragma unroll
      for (int i = 0; i < 4; i++) {
        put_out(op + i * 32, ha[i], hf + 8 * i, 1.f + inv[0], -mb[0] * inv[0], row0 != srow);
        put_out(op + 8192 + i * 32, hb[i], hf + 32 + 8 * i, 1.f + inv[1], -mb[1] * inv[1], row0 + 8 != srow);
      }
    }
    CT(14);
    const uint4 cand = lds128(sb + INFO_CAND);
    uint32_t wkey = zero_here();
#pragma unroll
    for (int i = 0; i < 2; i++) {
      const uint32_t row = row0 + 8 * i, rr = row | (row << 16);
      const bool is_cand = __vcmpeq2(cand.x, rr) | __vcmpeq2(cand.y, rr) | __vcmpeq2(cand.z, rr) | __vcmpeq2(cand.w, rr);
      if (!is_cand) wkey = max(wkey, make_key(bf16r((st[3 * i + 2] - mb[i] * __uint_as_float(info.x)) * inv[i]), row));
    }
    wkey = __reduce_max_sync(0xffffffffu, wkey);
    if (eps == 0 && lane == 0) pkt_st64(&p.sc->key[grp * 8 + warp], wkey, tag);
    const bool beaten = (wkey >> 16) > (info.z >> 16);
    if (__builtin_expect(beaten, 0)) {
      const int br = key_row(wkey);
      if (br == row0 || br == row0 + 8) {
#pragma unroll
        for (int i = 0; i < 4; i++) {
          const uint4 h = br == row0 ? ha[i] : hb[i];
          uint2* dst = &p.sc->hrow[(grp * 8 + warp) * 512 + eps * 64 + i * 16 + q * 4];
          pkt_st128(dst, h.x, tag, h.y, tag); pkt_st128(dst + 2, h.z, tag, h.w, tag);
        }
      }
      __syncwarp();
    }
    uint32_t any;
    asm volatile("{\n.reg .pred p, q;\nsetp.ne.b32 p, %1, 0;\nbarrier.cta.red.or.aligned.pred q, %2, 256, p;\nselp.u32 %0, 1, 0, q;\n}\n" : "=r"(any) : "r"((int)beaten), "n"((int)NB_BOTH) : "memory");
    if (__builtin_expect(any, 0)) slow_path(p, grp, eps, tag, info.z, info.w, SM<float>(INFO_LN), SM<float>(INFO_LN + 4));
  }
}

__global__ void __launch_bounds__(NTHR, 1) occupancy_probe_kernel() {}

typedef CUresult (*EncodeFn)(CUtensorMap*, CUtensorMapDataType, cuuint32_t, void*, const cuuint64_t*, const cuuint64_t*, const cuuint32_t*, const cuuint32_t*,
                             CUtensorMapInterleave, CUtensorMapSwizzle, CUtensorMapL2promotion, CUtensorMapFloatOOBfill);

static void make_tm(EncodeFn enc, CUtensorMap* tm, const void* ptr, uint64_t rows, uint64_t cols, uint32_t brows, uint32_t bcols, bool swz, bool wide) {
  cuuint64_t dims[2] = {cols, rows};
  cuuint64_t strides[1] = {cols * 2};
  cuuint32_t box[2] = {bcols, brows};
  cuuint32_t es[2] = {1, 1};
  enc(tm, CU_TENSOR_MAP_DATA_TYPE_BFLOAT16, 2, const_cast<void*>(ptr), dims, strides, box, es, CU_TENSOR_MAP_INTERLEAVE_NONE,
      swz ? CU_TENSOR_MAP_SWIZZLE_128B : CU_TENSOR_MAP_SWIZZLE_NONE, wide ? CU_TENSOR_MAP_L2_PROMOTION_L2_256B : CU_TENSOR_MAP_L2_PROMOTION_L2_128B, CU_TENSOR_MAP_FLOAT_OOB_FILL_NONE);
}

extern "C" void kernel_launch(void* const* d_in, const int* in_sizes, int n_in, void* d_out, int out_size) {
  (void)in_sizes; (void)n_in; (void)out_size;
  static EncodeFn enc = nullptr;
  static void* abT = nullptr;
  static void* sc = nullptr;
  static int map = 0;
  if (!enc) {
    void* fn = nullptr; cudaDriverEntryPointQueryResult st;
    cudaGetDriverEntryPoint("cuTensorMapEncodeTiled", &fn, cudaEnableDefault, &st);
    enc = (EncodeFn)fn;
    cudaGetSymbolAddress(&abT, g_abT);
    cudaGetSymbolAddress(&sc, g_sc);
    cudaFuncSetAttribute(fnet_moe_kernel<0>, cudaFuncAttributeMaxDynamicSharedMemorySize, SMEM_TOTAL);
    cudaFuncSetAttribute(fnet_moe_kernel<1>, cudaFuncAttributeMaxDynamicSharedMemorySize, SMEM_TOTAL);
    cudaFuncSetAttribute(occupancy_probe_kernel, cudaFuncAttributeMaxDynamicSharedMemorySize, SMEM_TOTAL);
    cudaFuncSetAttribute(occupancy_probe_kernel, cudaFuncAttributeNonPortableClusterSizeAllowed, 1);
    cudaLaunchConfig_t cfg = {};
    cfg.gridDim = dim3(128); cfg.blockDim = dim3(NTHR); cfg.dynamicSmemBytes = SMEM_TOTAL;
    cudaLaunchAttribute at[1];
    at[0].id = cudaLaunchAttributeClusterDimension; at[0].val.clusterDim.x = 16; at[0].val.clusterDim.y = 1; at[0].val.clusterDim.z = 1;
    cfg.attrs = at; cfg.numAttrs = 1;
    int ncl = 0;
    if (cudaOccupancyMaxActiveClusters(&ncl, occupancy_probe_kernel, &cfg) == cudaSuccess && ncl >= 8) map = 1;
    (void)cudaGetLastError();
  }
  Params p;
  const bf16* x = (const bf16*)d_in[0];
  make_tm(enc, &p.tmD0, d_in[3], 1024, 1024, 128, 64, true, true);
  make_tm(enc, &p.tmD1, d_in[4], 1024, 1024, 128, 64, true, true);
  make_tm(enc, &p.tmX, x, 2048, 1024, 256, 64, true, true);
  make_tm(enc, &p.tmAbS, abT, 2048, 2048, 64, 64, true, false);
  make_tm(enc, &p.tmAbL, abT, 2048, 2048, 128, 64, true, false);
  make_tm(enc, &p.tmW0, d_in[1], 2048, 2048, 128, 64, true, true);
  make_tm(enc, &p.tmW1, d_in[2], 2048, 2048, 128, 64, true, true);
  make_tm(enc, &p.tmG, d_in[7], 1024, 3584, 16, 64, false, false);
  make_tm(enc, &p.tmU, d_in[8], 1024, 3584, 16, 64, false, false);
  make_tm(enc, &p.tmDn, d_in[9], 3584, 1024, 8, 256, false, false);
  make_tm(enc, &p.tmY, (char*)sc + offsetof(Scratch, ypart), 4 * NSRC, 512, NSRC, 16, false, false);
  p.x = x; p.Dre = (const bf16*)d_in[3]; p.Dim = (const bf16*)d_in[4];
  p.wr = (const bf16*)d_in[6]; p.wdown = (const bf16*)d_in[9]; p.wgate = (const bf16*)d_in[7]; p.wup = (const bf16*)d_in[8]; p.Wre = (const bf16*)d_in[1]; p.Wim = (const bf16*)d_in[2];
  p.out = (bf16*)d_out; p.sc = (Scratch*)sc;
  if (map == 1) fnet_moe_kernel<1><<<NGRID, NTHR, SMEM_TOTAL>>>(p);
  else fnet_moe_kernel<0><<<NGRID, NTHR, SMEM_TOTAL>>>(p);
}
```

```cpp
#include <cuda.h>
#include <cuda_runtime.h>
#include <cuda_bf16.h>
#include <stdint.h>
#include <stddef.h>
#include <type_traits>

typedef __nv_bfloat16 bf16;

#define C1_AUX 1
constexpr int NGRID = 132, NTHR = 384;
__device__ __forceinline__ int k_col(int tau, int j) { return (tau * 256 + (j < 4 ? j * 64 : (j - 3) * 256)) & 2047; }
__device__ __forceinline__ int k_next(int c, int j) { return (c + (j < 11 ? 256 : j == 11 ? 576 : (c & 192) == 192 ? 128 : 64)) & 2047; }
constexpr int A_BYTES = 128 * 64 * 2;
constexpr int B_BYTES = 256 * 64 * 2;
constexpr int ST_BYTES = A_BYTES + B_BYTES;
constexpr int OFF_AUX = 4 * ST_BYTES;
constexpr int OFF_BAR = OFF_AUX + 32768;
constexpr int OFF_XS = OFF_BAR + 256;
constexpr int OFF_WR = OFF_XS + 2048;
constexpr int OFF_REM = OFF_WR + 256;
constexpr int OFF_INFO = OFF_REM + 256;
constexpr int SMEM_TOTAL = OFF_INFO + 256;
constexpr int INFO_WSUM = OFF_INFO, INFO_TAG = OFF_INFO + 4, INFO_KEY = OFF_INFO + 8, INFO_CAND = OFF_INFO + 16, INFO_LN = OFF_INFO + 32, INFO_ONES = OFF_INFO + 48, INFO_DS = OFF_INFO + 64, INFO_DS2 = OFF_INFO + 192;
constexpr int OFF_RS = OFF_XS;
constexpr int OFF_WC = OFF_AUX;
constexpr int OFF_EXA = OFF_AUX + 4096;
constexpr int OFF_EXB = OFF_AUX + 6144;
__host__ __device__ constexpr int off_stage(int c) { return C1_AUX && c == 1 ? OFF_AUX + 16384 : c * ST_BYTES; }
constexpr int OFF_RECV = A_BYTES;
__host__ __device__ constexpr int off_y(int w) { return w * ST_BYTES; }
constexpr int NSRC = 112;
enum { B_FULL = 0, B_EMPTY = 4, B_ALL = 6, B_EP = 8, B_AW = 16, B_STAT = 24, B_WC = 25, B_CD = 26, B_INFO = 28, B_PEER = 29, B_XCH = 30, B_GUX = (OFF_INFO + 128 - OFF_BAR) / 8, B_SD = B_GUX + 1, B_CH = 27, B_E23 = B_GUX + 5 };
enum { NB_TURN0 = 1, NB_TURN1 = 2, NB_BOTH = 3, NB_AUX = 4, NB_H = 5, NB_SEL = 6, NB_W0 = 7, NB_W1 = 8, NB_END = 9 };

struct Scratch;
struct Params {
  Scratch* sc; const bf16* wr; const bf16* x; const bf16* Dre; const bf16* Dim; const bf16* Wre; const bf16* Wim;
  const bf16* wgate; const bf16* wup; const bf16* wdown; bf16* out;
  CUtensorMap tmX, tmD0, tmD1, tmW0, tmW1, tmAbS, tmAbL, tmG, tmU, tmDn, tmY;
};

__device__ __align__(1024) bf16 g_abT[2048 * 2048];
struct Scratch {
  alignas(128) uint4 xz[2048];
  alignas(128) uint2 dsum[2048];
  alignas(128) uint32_t abflag[128 * 4 * 32];
  alignas(128) uint32_t abdone[128 * 2 * 32];
  alignas(128) uint2 u[4 * 512];
  alignas(128) uint2 cl[128 * 16];
  alignas(128) uint4 cpart[4 * 16 * 512];
  alignas(128) uint2 ch[8 * 512];
  alignas(128) uint4 cs[128 * 8];
  alignas(128) uint2 rdone[128];
  alignas(128) uint4 ypart[4 * NSRC * 64];
  alignas(128) uint4 hstat[16 * 8 * 128];
  alignas(128) uint2 key[128];
  alignas(128) uint2 hrow[128 * 512];
  alignas(128) uint2 fpart[8 * 1024];
  alignas(128) uint32_t epoch;
};
__device__ Scratch g_sc;

#define SPIN_LIMIT (1u << 17)
#define PF2_K 24
#define UNIT_PACE 1600
#define XPF_K 32
#define XS_DELAY 300
#define U_CLK 3700
#define XROW_PF 0
#define DROW_PF 0
#define TM_PF 0
#define SPLIT17 1
#define LO_NS 250
#define CAND_EARLY 0
#define CHAIN1 0
#define ROW_NS 400
#define W_PF 2
#define START_PF 0
#define ND0 65
#define ND1 66
#define ND2 67
#define ND3 -1
#define ND4 69
#define HI_DELAY 0
#define HI_PACE 1000
#define ALL_NS 400
#define RS3_LATE 1
#define PUT1_LATE 0
#define ALL_AT 1
#define LU0_LATE 0
#define Y_NS 200
#define GV 2
#define XS0 2
#define RS_EARLY 0
#define PRE_UNPACK 1
#define PV 2
#define PF1_K 4
#define PFM 0
#define EX0 5
#define HALF_EARLY 0
#define NCH 8
#define TR_ORDER 1
#define Z_CLK 9000
#define CP_DELAY 1500
#define CS_DELAY 800
#define YPART_DELAY 17300
__device__ __forceinline__ uint32_t smem_u32(const void* p) { return (uint32_t)__cvta_generic_to_shared(p); }
__device__ __forceinline__ uint32_t clk32() { uint32_t c; asm volatile("mov.u32 %0, %%clock;" : "=r"(c)); return c; }
__device__ __forceinline__ uint32_t zero_here() { uint64_t c; asm volatile("mov.u64 %0, %%clock64;" : "=l"(c) :: "memory"); return (uint32_t)(c >> 32) & blockIdx.y; }
__device__ __forceinline__ uint32_t uniform_zero_here() { uint32_t c; asm volatile("mov.u32 %0, %%clock;" : "=r"(c) :: "memory"); return c & blockIdx.y; }
__device__ __forceinline__ void wait_clk(uint32_t t0, uint32_t dt) {
  asm volatile("{\n.reg .pred p;\n.reg .u32 c;\nLOOP:\nmov.u32 c, %%clock;\nsub.u32 c, c, %0;\nsetp.lt.u32 p, c, %1;\n@p nanosleep.u32 100;\n@p bra LOOP;\n}\n" :: "r"(t0), "r"(dt) : "memory");
}
__device__ __forceinline__ void mbar_init(uint32_t bar, uint32_t cnt) { asm volatile("mbarrier.init.shared::cta.b64 [%0], %1;" :: "r"(bar), "r"(cnt) : "memory"); }
__device__ __forceinline__ void mbar_expect_tx(uint32_t bar, uint32_t bytes) { asm volatile("mbarrier.arrive.expect_tx.shared::cta.b64 _, [%0], %1;" :: "r"(bar), "r"(bytes) : "memory"); }
__device__ __forceinline__ void mbar_arrive(uint32_t bar) { asm volatile("mbarrier.arrive.shared::cta.b64 _, [%0];" :: "r"(bar) : "memory"); }
__device__ __forceinline__ void mbar_arrive_remote(uint32_t cluster_addr) { asm volatile("mbarrier.arrive.shared::cluster.b64 _, [%0];" :: "r"(cluster_addr) : "memory"); }
__device__ __forceinline__ void mbar_wait(uint32_t bar, uint32_t parity) {
  asm volatile("{\n.reg .pred p;\nLOOP:\nmbarrier.try_wait.parity.shared::cta.b64 p, [%0], %1;\n@!p bra LOOP;\n}\n" :: "r"(bar), "r"(parity) : "memory");
}
__device__ __forceinline__ void tma_load_2d(uint32_t dst, const CUtensorMap* tm, uint32_t bar, int c0, int c1) {
  asm volatile("cp.async.bulk.tensor.2d.shared::cluster.global.mbarrier::complete_tx::bytes [%0], [%1, {%3, %4}], [%2];"
    :: "r"(dst), "l"(tm), "r"(bar), "r"(c0), "r"(c1) : "memory");
}
__device__ __forceinline__ void tma_load_2d_hint(uint32_t dst, const CUtensorMap* tm, uint32_t bar, int c0, int c1, uint64_t pol) {
  asm volatile("cp.async.bulk.tensor.2d.shared::cluster.global.mbarrier::complete_tx::bytes.L2::cache_hint [%0], [%1, {%3, %4}], [%2], %5;"
    :: "r"(dst), "l"(tm), "r"(bar), "r"(c0), "r"(c1), "l"(pol) : "memory");
}
__device__ __forceinline__ uint64_t policy_evict_first() { uint64_t p; asm volatile("createpolicy.fractional.L2::evict_first.b64 %0, 1.0;" : "=l"(p)); return p; }
__device__ __forceinline__ void tma_store_2d(const CUtensorMap* tm, uint32_t src, int c0, int c1) {
  asm volatile("cp.async.bulk.tensor.2d.global.shared::cta.bulk_group [%0, {%2, %3}], [%1];" :: "l"(tm), "r"(src), "r"(c0), "r"(c1) : "memory");
}
__device__ __forceinline__ void bulk_load(uint32_t dst, const void* src, uint32_t bytes, uint32_t bar) {
  asm volatile("cp.async.bulk.shared::cluster.global.mbarrier::complete_tx::bytes [%0], [%1], %2, [%3];" :: "r"(dst), "l"(src), "r"(bytes), "r"(bar) : "memory");
}
__device__ __forceinline__ void prefetch_l2(const void* p) { asm volatile("prefetch.global.L2 [%0];" :: "l"(p)); }
__device__ __forceinline__ void bulk_commit() { asm volatile("cp.async.bulk.commit_group;" ::: "memory"); }
__device__ __forceinline__ void bulk_wait_all() { asm volatile("cp.async.bulk.wait_group 0;" ::: "memory"); }
__device__ __forceinline__ void fence_async_smem() { asm volatile("fence.proxy.async.shared::cta;" ::: "memory"); }
__device__ __forceinline__ void wgmma_fence() { asm volatile("wgmma.fence.sync.aligned;" ::: "memory"); }
__device__ __forceinline__ void wgmma_commit() { asm volatile("wgmma.commit_group.sync.aligned;" ::: "memory"); }
template<int N> __device__ __forceinline__ void wgmma_wait() { asm volatile("wgmma.wait_group.sync.aligned %0;" :: "n"(N) : "memory"); }
__device__ __forceinline__ void bar_sync(int id, int n) { asm volatile("bar.sync %0, %1;" :: "r"(id), "r"(n) : "memory"); }
__device__ __forceinline__ void bar_arrive(int id, int n) { asm volatile("bar.arrive %0, %1;" :: "r"(id), "r"(n) : "memory"); }
__device__ __forceinline__ void cluster_wait() { asm volatile("barrier.cluster.wait.aligned;" ::: "memory"); }
template<int R> __device__ __forceinline__ void reg_inc() { asm volatile("setmaxnreg.inc.sync.aligned.u32 %0;" :: "n"(R)); }
template<int R> __device__ __forceinline__ void reg_dec() { asm volatile("setmaxnreg.dec.sync.aligned.u32 %0;" :: "n"(R)); }
__device__ __forceinline__ bool elect_one() {
  uint32_t p;
  asm volatile("{\n.reg .pred q;\nelect.sync _|q, 0xffffffff;\nselp.u32 %0, 1, 0, q;\n}\n" : "=r"(p));
  return p != 0;
}
__device__ __forceinline__ uint32_t mapa(uint32_t addr, uint32_t cta) { uint32_t r; asm volatile("mapa.shared::cluster.u32 %0, %1, %2;" : "=r"(r) : "r"(addr), "r"(cta)); return r; }
__device__ __forceinline__ void st_async_v4(uint32_t addr, uint32_t bar, uint32_t a, uint32_t b, uint32_t c, uint32_t d) {
  asm volatile("st.async.weak.shared::cluster.mbarrier::complete_tx::bytes.v4.b32 [%0], {%2, %3, %4, %5}, [%1];" :: "r"(addr), "r"(bar), "r"(a), "r"(b), "r"(c), "r"(d) : "memory");
}
__device__ __forceinline__ void st_async_b32(uint32_t addr, uint32_t bar, uint32_t a) {
  asm volatile("st.async.weak.shared::cluster.mbarrier::complete_tx::bytes.b32 [%0], %2, [%1];" :: "r"(addr), "r"(bar), "r"(a) : "memory");
}
__device__ __forceinline__ void stsm_x4(uint32_t addr, uint32_t a, uint32_t b, uint32_t c, uint32_t d) {
  asm volatile("stmatrix.sync.aligned.m8n8.x4.shared.b16 [%0], {%1, %2, %3, %4};" :: "r"(addr), "r"(a), "r"(b), "r"(c), "r"(d) : "memory");
}
__device__ __forceinline__ void stsm_x4_t(uint32_t addr, uint32_t a, uint32_t b, uint32_t c, uint32_t d) {
  asm volatile("stmatrix.sync.aligned.m8n8.x4.trans.shared.b16 [%0], {%1, %2, %3, %4};" :: "r"(addr), "r"(a), "r"(b), "r"(c), "r"(d) : "memory");
}
__device__ __forceinline__ uint4 lds128(uint32_t addr) { uint4 v; asm volatile("ld.shared.v4.b32 {%0, %1, %2, %3}, [%4];" : "=r"(v.x), "=r"(v.y), "=r"(v.z), "=r"(v.w) : "r"(addr) : "memory"); return v; }
extern __shared__ __align__(1024) uint8_t smem_raw[];
template<class T> __device__ __forceinline__ T& SM(int off) { return *reinterpret_cast<T*>(smem_raw + off); }
__device__ __forceinline__ uint4 ldg_nc128(const void* p) { uint4 v; asm volatile("ld.global.nc.v4.b32 {%0, %1, %2, %3}, [%4];" : "=r"(v.x), "=r"(v.y), "=r"(v.z), "=r"(v.w) : "l"(p)); return v; }
__device__ __forceinline__ uint4 ldg128(const void* p) { uint4 v; asm volatile("ld.global.L1::no_allocate.v4.b32 {%0, %1, %2, %3}, [%4];" : "=r"(v.x), "=r"(v.y), "=r"(v.z), "=r"(v.w) : "l"(p) : "memory"); return v; }
__device__ __forceinline__ void pkt_st128(void* p, uint32_t a, uint32_t b, uint32_t c, uint32_t d) {
  asm volatile("{\n.reg .b128 v;\n.reg .b64 lo, hi;\nmov.b64 lo, {%1, %2};\nmov.b64 hi, {%3, %4};\nmov.b128 v, {lo, hi};\nst.relaxed.gpu.global.b128 [%0], v;\n}\n"
    :: "l"(p), "r"(a), "r"(b), "r"(c), "r"(d) : "memory");
}
__device__ __forceinline__ uint4 pkt_ld128(const void* p) {
  uint4 r;
  asm volatile("{\n.reg .b128 v;\n.reg .b64 lo, hi;\nld.relaxed.gpu.global.b128 v, [%4];\nmov.b128 {lo, hi}, v;\nmov.b64 {%0, %1}, lo;\nmov.b64 {%2, %3}, hi;\n}\n"
    : "=r"(r.x), "=r"(r.y), "=r"(r.z), "=r"(r.w) : "l"(p) : "memory");
  return r;
}
__device__ __forceinline__ void pkt_st64(void* p, uint32_t a, uint32_t b) {
  asm volatile("{\n.reg .b64 v;\nmov.b64 v, {%1, %2};\nst.relaxed.gpu.global.b64 [%0], v;\n}\n" :: "l"(p), "r"(a), "r"(b) : "memory");
}
__device__ __forceinline__ uint2 pkt_ld64(const void* p) {
  uint2 r;
  asm volatile("{\n.reg .b64 v;\nld.relaxed.gpu.global.b64 v, [%2];\nmov.b64 {%0, %1}, v;\n}\n" : "=r"(r.x), "=r"(r.y) : "l"(p) : "memory");
  return r;
}
__device__ __forceinline__ void pkt_clear128(void* p) { pkt_st128(p, 0, 0, 0, 0); }
__device__ __forceinline__ uint32_t ld_relaxed32(const void* p) { uint32_t v; asm volatile("ld.relaxed.gpu.global.b32 %0, [%1];" : "=r"(v) : "l"(p) : "memory"); return v; }
__device__ __forceinline__ uint32_t ld_acquire32(const void* p) { uint32_t v; asm volatile("ld.acquire.gpu.global.b32 %0, [%1];" : "=r"(v) : "l"(p) : "memory"); return v; }
__device__ __forceinline__ void st_relaxed32(void* p, uint32_t v) { asm volatile("st.relaxed.gpu.global.b32 [%0], %1;" :: "l"(p), "r"(v) : "memory"); }
__device__ __forceinline__ uint32_t poll64(const void* p, uint32_t tag, int ns) {
  uint2 v; uint32_t n = 0;
  bool more;
#pragma unroll 1
  do {
    v = pkt_ld64(p);
    more = !(v.y == tag) && ++n < SPIN_LIMIT;
    if (more) { __nanosleep(ns); }
  } while (more);
  return v.x;
}
__device__ __forceinline__ uint32_t poll64_warp(const void* p, uint32_t tag, int ns) {
  uint2 v; uint32_t n = 0;
  bool more;
#pragma unroll 1
  do {
    v = pkt_ld64(p);
    more = !(__all_sync(0xffffffffu, v.y == tag)) && ++n < SPIN_LIMIT;
    if (more) { __nanosleep(ns); }
  } while (more);
  return v.x;
}
__device__ __forceinline__ uint32_t code_of(uint32_t tag) { return tag % 3u + 1u; }
__device__ __forceinline__ uint32_t with_bit(uint32_t v, uint32_t bit) { return (v & ~1u) | (bit & 1u); }
__device__ __forceinline__ uint32_t with_bit(float v, uint32_t bit) { return with_bit(__float_as_uint(v), bit); }
__device__ __forceinline__ float no_bit(uint32_t v) { return __uint_as_float(v & ~1u); }
__device__ __forceinline__ void chk(uint32_t& bad, uint32_t a, uint32_t want) { bad |= a ^ want; asm("" : "+r"(bad)); }
__device__ __forceinline__ void chk_code(uint32_t& bad, const uint4& v, uint32_t c0, uint32_t c1) { chk(bad, v.x, c0); chk(bad, v.y, c1); chk(bad, v.z, c0); chk(bad, v.w, c1); }
__device__ __forceinline__ uint32_t pack_bf16(float lo, float hi) { uint32_t r; asm("cvt.rn.bf16x2.f32 %0, %1, %2;" : "=r"(r) : "f"(hi), "f"(lo)); return r; }
__device__ __forceinline__ float bf_lo(uint32_t v) { return __uint_as_float(v << 16); }
__device__ __forceinline__ float bf_hi(uint32_t v) { return __uint_as_float(v & 0xFFFF0000u); }
__device__ __forceinline__ float bf16r(float x) { return __uint_as_float(pack_bf16(0.f, x)); }
__device__ __forceinline__ void st_bf16(bf16* p, float x) { *reinterpret_cast<uint16_t*>(p) = (uint16_t)pack_bf16(x, 0.f); }
__device__ __forceinline__ float fast_rcp(float x) { float r; asm("rcp.approx.ftz.f32 %0, %1;" : "=f"(r) : "f"(x)); return r; }
__device__ __forceinline__ float ldbf(const bf16* p) { return __bfloat162float(*p); }
__device__ __forceinline__ uint32_t badd2(uint32_t a, uint32_t b) { uint32_t r; asm("add.rn.bf16x2 %0, %1, %2;" : "=r"(r) : "r"(a), "r"(b)); return r; }
__device__ __forceinline__ uint32_t bfma2(uint32_t a, uint32_t b, uint32_t c) { uint32_t r; asm("fma.rn.bf16x2 %0, %1, %2, %3;" : "=r"(r) : "r"(a), "r"(b), "r"(c)); return r; }
__device__ __forceinline__ float warp_sum(float v) {
#pragma unroll
  for (int o = 16; o > 0; o >>= 1) v += __shfl_xor_sync(0xffffffffu, v, o);
  return v;
}
template<int N> __device__ __forceinline__ void fold(float* v, int o, int lane) {
  const bool up = lane & o;
#pragma unroll
  for (int i = 0; i < N / 2; i++) {
    const float keep = up ? v[N / 2 + i] : v[i], send = up ? v[i] : v[N / 2 + i];
    v[i] = keep + __shfl_xor_sync(0xffffffffu, send, o);
  }
}
__device__ __forceinline__ uint32_t make_key(float r_bf, int row) {
  const uint32_t u = __float_as_uint(r_bf);
  return (((u & 0x80000000u) ? ~u : (u | 0x80000000u)) & 0xFFFF0000u) | (0xFFFFu - (uint32_t)row);
}
__device__ __forceinline__ int key_row(uint32_t key) { return (0xFFFF - (int)(key & 0xFFFFu)) & 2047; }
__device__ __forceinline__ float key_val(uint32_t key) { const uint32_t o = key & 0xFFFF0000u; return __uint_as_float((o & 0x80000000u) ? (o & 0x7FFFFFFFu) : (~o & 0xFFFF0000u)); }
__device__ __forceinline__ float ref_sd(float var) { float r; asm("sqrt.approx.ftz.f32 %0, %1;" : "=f"(r) : "f"(bf16r(bf16r(var) + 1e-5f))); return bf16r(r); }
__device__ __forceinline__ uint64_t make_desc(uint32_t addr) { return (uint64_t)((addr & 0x3FFFF) >> 4) | ((uint64_t)64 << 32) | ((uint64_t)1 << 62); }
__device__ __forceinline__ uint64_t make_desc_noswz(uint32_t addr) { return (uint64_t)((addr & 0x3FFFF) >> 4) | ((uint64_t)8 << 32); }
#define ACC8(d, o) "+f"(d[o]), "+f"(d[o + 1]), "+f"(d[o + 2]), "+f"(d[o + 3]), "+f"(d[o + 4]), "+f"(d[o + 5]), "+f"(d[o + 6]), "+f"(d[o + 7])
#define ACC64(d, o) ACC8(d, o), ACC8(d, o + 8), ACC8(d, o + 16), ACC8(d, o + 24), ACC8(d, o + 32), ACC8(d, o + 40), ACC8(d, o + 48), ACC8(d, o + 56)
#define REGS64 "%0, %1, %2, %3, %4, %5, %6, %7, %8, %9, %10, %11, %12, %13, %14, %15, %16, %17, %18, %19, %20, %21, %22, %23, %24, %25, %26, %27, %28, %29, %30, %31, " \
    "%32, %33, %34, %35, %36, %37, %38, %39, %40, %41, %42, %43, %44, %45, %46, %47, %48, %49, %50, %51, %52, %53, %54, %55, %56, %57, %58, %59, %60, %61, %62, %63"
#define REGS128 REGS64 ", %64, %65, %66, %67, %68, %69, %70, %71, %72, %73, %74, %75, %76, %77, %78, %79, %80, %81, %82, %83, %84, %85, %86, %87, %88, %89, %90, %91, %92, %93, %94, %95, " \
    "%96, %97, %98, %99, %100, %101, %102, %103, %104, %105, %106, %107, %108, %109, %110, %111, %112, %113, %114, %115, %116, %117, %118, %119, %120, %121, %122, %123, %124, %125, %126, %127"
__device__ __forceinline__ void wgmma_n256(float (&d)[128], uint64_t da, uint64_t db) {
  asm volatile("wgmma.mma_async.sync.aligned.m64n256k16.f32.bf16.bf16 {" REGS128 "}, %128, %129, 1, 1, 1, 0, 0;\n"
    : ACC64(d, 0), ACC64(d, 64) : "l"(da), "l"(db));
}
#define OUT8(d, o) "=f"(d[o]), "=f"(d[o + 1]), "=f"(d[o + 2]), "=f"(d[o + 3]), "=f"(d[o + 4]), "=f"(d[o + 5]), "=f"(d[o + 6]), "=f"(d[o + 7])
#define OUT64(d, o) OUT8(d, o), OUT8(d, o + 8), OUT8(d, o + 16), OUT8(d, o + 24), OUT8(d, o + 32), OUT8(d, o + 40), OUT8(d, o + 48), OUT8(d, o + 56)
__device__ __forceinline__ void wgmma_n256_rs_init(float (&d)[128], const uint32_t* a, uint64_t db) {
  asm volatile("wgmma.mma_async.sync.aligned.m64n256k16.f32.bf16.bf16 {" REGS128 "}, {%128, %129, %130, %131}, %132, 0, 1, 1, 0;\n"
    : OUT64(d, 0), OUT64(d, 64) : "r"(a[0]), "r"(a[1]), "r"(a[2]), "r"(a[3]), "l"(db));
}
template<int ACCUM> __device__ __forceinline__ void wgmma_n256_rs(float (&d)[128], const uint32_t* a, uint64_t db) {
  asm volatile("wgmma.mma_async.sync.aligned.m64n256k16.f32.bf16.bf16 {" REGS128 "}, {%128, %129, %130, %131}, %132, %133, 1, 1, 0;\n"
    : ACC64(d, 0), ACC64(d, 64) : "r"(a[0]), "r"(a[1]), "r"(a[2]), "r"(a[3]), "l"(db), "n"(ACCUM));
}
template<int ACCUM> __device__ __forceinline__ void wgmma_n8_rs(float (&d)[4], const uint32_t* a, uint64_t db) {
  asm volatile("wgmma.mma_async.sync.aligned.m64n8k16.f32.bf16.bf16 {%0, %1, %2, %3}, {%4, %5, %6, %7}, %8, %9, 1, 1, 0;\n"
    : "+f"(d[0]), "+f"(d[1]), "+f"(d[2]), "+f"(d[3]) : "r"(a[0]), "r"(a[1]), "r"(a[2]), "r"(a[3]), "l"(db), "n"(ACCUM));
}
__device__ __forceinline__ void wgmma_n8(float (&d)[4], uint64_t da, uint64_t db) {
  asm volatile("wgmma.mma_async.sync.aligned.m64n8k16.f32.bf16.bf16 {%0, %1, %2, %3}, %4, %5, 1, 1, 1, 0, 0;\n"
    : "+f"(d[0]), "+f"(d[1]), "+f"(d[2]), "+f"(d[3]) : "l"(da), "l"(db));
}
__device__ __forceinline__ void wgmma_n128(float (&d)[64], uint64_t da, uint64_t db) {
  asm volatile("wgmma.mma_async.sync.aligned.m64n128k16.f32.bf16.bf16 {" REGS64 "}, %64, %65, 1, 1, 1, 0, 0;\n" : ACC64(d, 0) : "l"(da), "l"(db));
}
#define ACC32(d, o) ACC8(d, o), ACC8(d, o + 8), ACC8(d, o + 16), ACC8(d, o + 24)
#define REGS32 "%0, %1, %2, %3, %4, %5, %6, %7, %8, %9, %10, %11, %12, %13, %14, %15, %16, %17, %18, %19, %20, %21, %22, %23, %24, %25, %26, %27, %28, %29, %30, %31"
#define REGS96 REGS64 ", %64, %65, %66, %67, %68, %69, %70, %71, %72, %73, %74, %75, %76, %77, %78, %79, %80, %81, %82, %83, %84, %85, %86, %87, %88, %89, %90, %91, %92, %93, %94, %95"
__device__ __forceinline__ void wgmma_part(float (&d)[32], uint64_t da, uint64_t db) {
  asm volatile("wgmma.mma_async.sync.aligned.m64n64k16.f32.bf16.bf16 {" REGS32 "}, %32, %33, 1, 1, 1, 0, 0;\n" : ACC32(d, 0) : "l"(da), "l"(db));
}
__device__ __forceinline__ void wgmma_part(float (&d)[96], uint64_t da, uint64_t db) {
  asm volatile("wgmma.mma_async.sync.aligned.m64n192k16.f32.bf16.bf16 {" REGS96 "}, %96, %97, 1, 1, 1, 0, 0;\n" : ACC64(d, 0), ACC32(d, 64) : "l"(da), "l"(db));
}
template<int N> __device__ __forceinline__ void fence_regs(float (&d)[N]) {
#pragma unroll
  for (int i = 0; i < N; i++) asm volatile("" : "+f"(d[i]) :: "memory");
}
__device__ __forceinline__ void mma16816(float (&c)[4], uint32_t a0, uint32_t a1, uint32_t a2, uint32_t a3, uint32_t b0, uint32_t b1) {
  asm volatile("mma.sync.aligned.m16n8k16.row.col.f32.bf16.bf16.f32 {%0, %1, %2, %3}, {%4, %5, %6, %7}, {%8, %9}, {%0, %1, %2, %3};"
               : "+f"(c[0]), "+f"(c[1]), "+f"(c[2]), "+f"(c[3]) : "r"(a0), "r"(a1), "r"(a2), "r"(a3), "r"(b0), "r"(b1));
}
__device__ __forceinline__ void fma8(float* acc, const uint4& v, float x) {
  acc[0] = fmaf(bf_lo(v.x), x, acc[0]); acc[1] = fmaf(bf_hi(v.x), x, acc[1]); acc[2] = fmaf(bf_lo(v.y), x, acc[2]); acc[3] = fmaf(bf_hi(v.y), x, acc[3]);
  acc[4] = fmaf(bf_lo(v.z), x, acc[4]); acc[5] = fmaf(bf_hi(v.z), x, acc[5]); acc[6] = fmaf(bf_lo(v.w), x, acc[6]); acc[7] = fmaf(bf_hi(v.w), x, acc[7]);
}
template<int PITCH> __device__ __forceinline__ void gemv8x8(float (&acc)[8], uint32_t addr, const float (&x)[8]) {
  uint4 v[2][2];
  v[0][0] = lds128(addr); v[0][1] = lds128(addr + PITCH);
#pragma unroll
  for (int b = 0; b < 4; b++) {
    if (b < 3) { v[(b + 1) & 1][0] = lds128(addr + (2 * b + 2) * PITCH); v[(b + 1) & 1][1] = lds128(addr + (2 * b + 3) * PITCH); }
    acc[0] += __uint_as_float(zero_here());
#pragma unroll
    for (int c = 0; c < 4; c++) {
      if (GV == 2 && c == 2) acc[4] += __uint_as_float(zero_here());
#pragma unroll
      for (int r = 0; r < 2; r++) {
        const uint4& q = v[b & 1][r];
        const uint32_t u = c == 0 ? q.x : c == 1 ? q.y : c == 2 ? q.z : q.w;
        acc[2 * c] = fmaf(bf_lo(u), x[2 * b + r], acc[2 * c]); acc[2 * c + 1] = fmaf(bf_hi(u), x[2 * b + r], acc[2 * c + 1]);
      }
    }
  }
}
__device__ __forceinline__ float swiglu(float g, float u) {
  g = bf16r(g); u = bf16r(u);
  return bf16r(bf16r(g * fast_rcp(1.f + __expf(-g))) * u);
}

#define CT(slot) do {} while (0)
#define TIM(slot) do {} while (0)

constexpr int H_BUF0 = 0, H_BUF1 = 16384, H_RED = 32768, H_KEYS = H_RED + 1024, H_ROW = H_KEYS + 1024, H_ACT = H_ROW + 8192, H_PART = H_ACT + 4096;
__device__ __forceinline__ void hsync() { bar_sync(NB_H, 256); }
template<int N> __device__ __forceinline__ void block_sum(float (&v)[N], int warp, int lane) {
#pragma unroll
  for (int i = 0; i < N; i++) v[i] = warp_sum(v[i]);
  hsync();
  if (lane == 0) {
#pragma unroll
    for (int i = 0; i < N; i++) SM<float>(H_RED + (i * 8 + warp) * 4) = v[i];
  }
  hsync();
#pragma unroll
  for (int i = 0; i < N; i++) {
    const float4 a = SM<float4>(H_RED + i * 32), b = SM<float4>(H_RED + i * 32 + 16);
    v[i] = ((a.x + a.y) + (a.z + a.w)) + ((b.x + b.y) + (b.z + b.w));
  }
}
__device__ __forceinline__ void fft_first(int j, float2 v0, float2 v1, float2 v2, float2 v3) {
  const float2 a = make_float2(v0.x + v2.x, v0.y + v2.y), b = make_float2(v0.x - v2.x, v0.y - v2.y);
  const float2 c = make_float2(v1.x + v3.x, v1.y + v3.y), d = make_float2(v1.y - v3.y, v3.x - v1.x);
  SM<float4>(H_BUF1 + j * 32) = make_float4(a.x + c.x, a.y + c.y, b.x + d.x, b.y + d.y);
  SM<float4>(H_BUF1 + j * 32 + 16) = make_float4(a.x - c.x, a.y - c.y, b.x - d.x, b.y - d.y);
}
template<int NB> __device__ __forceinline__ void fft_passes(int tid) {
  constexpr int q = 256 * NB;
#pragma unroll 1
  for (int ps = 1; ps < 5; ps++) {
    const int ns = 1 << (2 * ps), k = tid & (ns - 1);
    float s1, c1;
    __sincosf(-1.57079632679f * __fdividef((float)k, (float)ns), &s1, &c1);
    const float c2 = c1 * c1 - s1 * s1, s2 = 2.f * c1 * s1, c3 = c1 * c2 - s1 * s2, s3 = c1 * s2 + s1 * c2;
    hsync();
#pragma unroll
    for (int i = 0; i < NB; i++) {
      const int j = tid + 256 * i;
      const float2* in = &SM<float2>((ps & 1) ? H_BUF1 : H_BUF0);
      float2* o = &SM<float2>((ps & 1) ? H_BUF0 : H_BUF1) + (j - k) * 4 + k;
      const float2 v0 = in[j], x1 = in[j + q], x2 = in[j + 2 * q], x3 = in[j + 3 * q];
      const float2 v1 = make_float2(x1.x * c1 - x1.y * s1, x1.x * s1 + x1.y * c1);
      const float2 v2 = make_float2(x2.x * c2 - x2.y * s2, x2.x * s2 + x2.y * c2);
      const float2 v3 = make_float2(x3.x * c3 - x3.y * s3, x3.x * s3 + x3.y * c3);
      const float2 a = make_float2(v0.x + v2.x, v0.y + v2.y), b = make_float2(v0.x - v2.x, v0.y - v2.y);
      const float2 c = make_float2(v1.x + v3.x, v1.y + v3.y), d = make_float2(v1.y - v3.y, v3.x - v1.x);
      o[0] = make_float2(a.x + c.x, a.y + c.y); o[ns] = make_float2(b.x + d.x, b.y + d.y);
      o[2 * ns] = make_float2(a.x - c.x, a.y - c.y); o[3 * ns] = make_float2(b.x - d.x, b.y - d.y);
    }
  }
  hsync();
}
template<int NR> __device__ __forceinline__ void ln_rows(const float (&h)[NR][4], float (&hn)[NR][4], int warp, int lane) {
  float s[NR], q[NR];
#pragma unroll
  for (int i = 0; i < NR; i++) s[i] = (h[i][0] + h[i][1]) + (h[i][2] + h[i][3]);
  block_sum(s, warp, lane);
#pragma unroll
  for (int i = 0; i < NR; i++) {
    s[i] *= 1.f / 1024.f; q[i] = 0.f;
#pragma unroll
    for (int z = 0; z < 4; z++) q[i] = fmaf(h[i][z] - s[i], h[i][z] - s[i], q[i]);
  }
  block_sum(q, warp, lane);
#pragma unroll
  for (int i = 0; i < NR; i++) {
    const float mb = bf16r(s[i]), inv = fast_rcp(ref_sd(q[i] * (1.f / 1024.f)));
#pragma unroll
    for (int z = 0; z < 4; z++) hn[i][z] = bf16r(bf16r(h[i][z] - mb) * inv);
  }
}
__device__ __forceinline__ float sigmoid_bf(float r) { return bf16r(fast_rcp(1.f + __expf(-r))); }
__device__ __forceinline__ float routed_out(float h, float hn, float y, float sig) { return h + bf16r(hn + bf16r(bf16r(y) * sig)); }

__device__ __forceinline__ void helper_cta(const Params& p, const int hi, const uint32_t t_entry) {
  const int tid = threadIdx.x, warp = tid >> 5, lane = tid & 31;
  const float w0 = ldbf(p.wr + tid), w1 = ldbf(p.wr + tid + 256), w2 = ldbf(p.wr + tid + 512), w3 = ldbf(p.wr + tid + 768), wf = ldbf(p.wr);
  const uint32_t tag = ld_relaxed32(&p.sc->epoch) + 1;
  pkt_clear128(&p.sc->u[hi * 512 + tid * 2]);
  if (tid == 0 && w0 != 123.f) TIM(12);
  fft_first(tid, make_float2(w0, 0.f), make_float2(w1, 0.f), make_float2(w2, 0.f), make_float2(w3, 0.f));
  fft_passes<1>(tid);
  const uint32_t c0 = code_of(tag), c1 = c0 >> 1;
  {
    const float off = wf - SM<float>(H_BUF1) * (1.f / 1024.f);
    const float4 v = SM<float4>(H_BUF1 + tid * 32), u = SM<float4>(H_BUF1 + tid * 32 + 16);
    pkt_st128(&p.sc->u[hi * 512 + ((tid & 192) + (tid & 1) * 32 + ((tid >> 1) & 31)) * 2], with_bit(pack_bf16((tid ? v.x : 0.f) - off, v.z - off), c0), with_bit(pack_bf16(v.y, v.w), c1),
              with_bit(pack_bf16(u.x - off, u.z - off), c0), with_bit(pack_bf16(u.y, u.w), c1));
    if (tid < 64) pkt_clear128(&p.sc->cl[(hi * 32 + (tid >> 1)) * 16 + (tid & 1) * 2]);
    hsync();
  }
  if (tid == 0) TIM(0);
  {
    float tw[8];
#pragma unroll
    for (int i = 0; i < 4; i++) __sincosf((float)(tid + 256 * i) * (-6.28318530718f / 2048.f), &tw[2 * i], &tw[2 * i + 1]);
    wait_clk(t_entry, Z_CLK);
    uint2 z[8]; uint32_t n = 0;
    bool more;
#pragma unroll 1
    do {
      uint32_t bad = 0;
#pragma unroll
      for (int i = 0; i < 8; i++) z[i] = pkt_ld64(reinterpret_cast<const uint2*>(&p.sc->xz[tid]) + 512 * i + 1);
#pragma unroll
      for (int i = 0; i < 8; i++) chk(bad, z[i].y, tag);
      more = !(!bad) && ++n < SPIN_LIMIT;
      if (more) { __nanosleep(150); }
    } while (more);
#pragma unroll
    for (int i = 0; i < 2; i++)
      fft_first(tid + 256 * i, make_float2(bf_lo(z[i].x), bf_hi(z[i].x)), make_float2(bf_lo(z[i + 2].x), bf_hi(z[i + 2].x)),
                make_float2(bf_lo(z[i + 4].x), bf_hi(z[i + 4].x)), make_float2(bf_lo(z[i + 6].x), bf_hi(z[i + 6].x)));
    if (tid == 0) TIM(7);
    fft_passes<2>(tid);
    if (tid == 0) TIM(1);
    uint32_t k8[8];
#pragma unroll
    for (int i = 0; i < 4; i++) {
      const int k = tid + 256 * i;
      const float2 v0 = SM<float2>(H_BUF1 + k * 8), v1 = SM<float2>(H_BUF1 + (k + 1024) * 8);
      const float w = v1.x * tw[2 * i + 1] - v1.y * tw[2 * i];
      const uint32_t a = __float_as_uint(v0.x + w), b = __float_as_uint(v0.x - w);
      k8[2 * i] = (((a & 0x80000000u) ? ~a : (a | 0x80000000u)) & ~2047u) | k;
      k8[2 * i + 1] = (((b & 0x80000000u) ? ~b : (b | 0x80000000u)) & ~2047u) | (k + 1024);
    }
    uint32_t lim = 0xFFFFFFFFu;
#pragma unroll 1
    for (int r = 0; r < 4; r++) {
      uint32_t mx = 0;
#pragma unroll
      for (int i = 0; i < 8; i++) mx = max(mx, k8[i] <= lim ? k8[i] : 0u);
      mx = __reduce_max_sync(0xffffffffu, mx);
      if (lane == 0) SM<uint32_t>(H_KEYS + (warp * 4 + r) * 4) = mx;
      lim = mx - 1;
    }
    hsync();
    if (tid < 32) {
      const uint32_t me = SM<uint32_t>(H_KEYS + tid * 4);
      int rank = 0;
#pragma unroll
      for (int i = 0; i < 8; i++) { const uint4 o = SM<uint4>(H_KEYS + i * 16); rank += (o.x > me) + (o.y > me) + (o.z > me) + (o.w > me); }
      if (rank < 8) SM<uint16_t>(H_KEYS + 256 + rank * 2) = me & 2047u;
    }
    hsync();
    if (tid >= 128) pkt_st64(&p.sc->cl[(hi * 32 + ((tid - 128) >> 2)) * 16 + (tid & 3)], SM<uint32_t>(H_KEYS + 256 + (tid & 3) * 4), tag);
  }
  const uint32_t cpair = SM<uint32_t>(H_KEYS + 256 + hi * 4);
  const int ca = cpair & 0xFFFF, cb = cpair >> 16;
  if (tid < 128) prefetch_l2(((tid & 32) ? p.Wim : p.Wre) + (size_t)((tid & 64) ? cb : ca) * 2048 + lane * 64);
  if (tid == 0) TIM(2);
}

__device__ __forceinline__ void slow_path(const Params& p, int grp, int eps, uint32_t tag, uint32_t key, int win, float mb, float inv) {
  const int tid = threadIdx.x + zero_here(), warp = tid >> 5, lane = tid & 31;
  uint32_t best = __reduce_max_sync(0xffffffffu, poll64(&p.sc->key[tid & 127], tag, 200));
  if (lane == 0) SM<uint32_t>(H_KEYS + warp * 4) = best;
  hsync();
  { const uint4 b4 = SM<uint4>(H_KEYS); best = max(max(b4.x, b4.y), max(b4.z, b4.w)); }
  const int tw = key_row(best), col = eps * 128 + (tid & 127);
  if ((tw >> 7) != grp) return;
  poll64(&p.sc->rdone[col >> 3], tag, 100);
  const uint32_t h0 = poll64(&p.sc->hrow[(tw >> 4) * 512 + 2 * tid], tag, 100), h1 = poll64(&p.sc->hrow[(tw >> 4) * 512 + 2 * tid + 1], tag, 100);
  float h[1][4] = {{bf_lo(h0), bf_hi(h0), bf_lo(h1), bf_hi(h1)}}, hn[1][4];
  ln_rows<1>(h, hn, warp, lane);
  SM<float4>(H_ROW + tid * 16) = make_float4(hn[0][0], hn[0][1], hn[0][2], hn[0][3]);
  SM<float4>(H_ROW + 4096 + tid * 16) = make_float4(h[0][0], h[0][1], h[0][2], h[0][3]);
  hsync();
#pragma unroll 1
  for (int ph = 0; ph < 2; ph++) {
    const int part = min(tid / 56, 3), fh = tid >> 7, len = ph ? 224 : 512, ld = ph ? 1024 : 3584;
    const bf16* wp = ph ? p.wdown + (eps * 448 + fh * 224) * 1024 + (tid & 127) * 8
                        : ((part & 1) ? p.wup : p.wgate) + (part >> 1) * 512 * 3584 + eps * 448 + min(tid - part * 56, 55) * 8;
    const int xo = ph ? H_ACT + fh * 224 * 4 : H_ROW + (part >> 1) * 2048;
    float acc[8] = {0.f, 0.f, 0.f, 0.f, 0.f, 0.f, 0.f, 0.f};
#pragma unroll 8
    for (int d = 0; d < (len & ~7); d++) fma8(acc, ldg_nc128(wp + d * ld), SM<float>(xo + d * 4));
    SM<float4>(H_PART + tid * 32) = make_float4(acc[0], acc[1], acc[2], acc[3]);
    SM<float4>(H_PART + tid * 32 + 16) = make_float4(acc[4], acc[5], acc[6], acc[7]);
    hsync();
    if (ph) break;
#pragma unroll 1
    for (int f = tid; f < 448; f += 256)
      SM<float>(H_ACT + f * 4) = swiglu(SM<float>(H_PART + f * 4) + SM<float>(H_PART + (896 + f) * 4), SM<float>(H_PART + (448 + f) * 4) + SM<float>(H_PART + (1344 + f) * 4));
    hsync();
  }
#pragma unroll 1
  for (int e = tid; e < 1024; e += 256) pkt_st64(&p.sc->fpart[eps * 1024 + e], __float_as_uint(SM<float>(H_PART + e * 4) + SM<float>(H_PART + (1024 + e) * 4)), tag);
  if (tid < 128) {
    float y = 0.f;
#pragma unroll 1
    for (int q = 0; q < 8; q++) y += __uint_as_float(poll64(&p.sc->fpart[q * 1024 + col], tag, 200));
    st_bf16(p.out + tw * 1024 + col, routed_out(SM<float>(H_ROW + 4096 + col * 4), SM<float>(H_ROW + col * 4), y, sigmoid_bf(key_val(best))));
    const uint32_t a = poll64(&p.sc->ch[win * 512 + (col >> 4) * 8 + (col & 7)], tag, 100);
    const float hc = (col & 8) ? bf_hi(a) : bf_lo(a);
    st_bf16(p.out + key_row(key) * 1024 + col, hc + bf16r(bf16r(hc - mb) * inv));
  }
}

template<int MAP>
__global__ void __cluster_dims__(2, 1, 1) __launch_bounds__(NTHR, 1)
fnet_moe_kernel(const __grid_constant__ Params p) {
  const uint32_t t_entry = clk32();
  uint32_t smid;
  asm("mov.u32 %0, %%smid;" : "=r"(smid));
  const int tpc = smid >> 1, m = blockIdx.x & 1;
  if (MAP == 1 ? tpc >= 64 : (tpc >> 1) == 30) {
    if (threadIdx.x < 256) helper_cta(p, (tpc & 1) * 2 + m, t_entry);
    return;
  }
  const uint32_t sb = smem_u32(smem_raw);
  const int tid = threadIdx.x, lane = tid & 31;
  const int e7 = ((tpc - 32) * 37) >> 8;
  const int tau = MAP == 1 || tpc < 32 ? (tpc & 7) : (tpc < 60 ? tpc - 31 - 7 * e7 : 0);
  const int eps = MAP == 1 || tpc < 32 ? (tpc >> 3) : (tpc < 60 ? 4 + e7 : tpc - 58);
  const int cid = tau * 16 + eps * 2 + m;
  auto BAR = [&](int i) { return sb + OFF_BAR + 8 * i; };
  const CUtensorMap* tmD = &p.tmD0 + m;
#define LOAD_STREAM(d, tm, bar, c0, c1) tma_load_2d_hint(d, tm, bar, c0, c1, pol_ef)
#define LOAD_W tma_load_2d
#define LOAD_D tma_load_2d
#define LOAD_X tma_load_2d
#define LOAD_F LOAD_STREAM

  uint32_t tag = 0;
  uint4 wq = make_uint4(0, 0, 0, 0);
  if ((tid >> 5) == 4) {
    if (elect_one()) {
      const uint64_t pol_ef = policy_evict_first();
#pragma unroll
      for (int k = 0; k < 4; k++) mbar_init(BAR(B_FULL + k), 1);
      asm volatile("fence.mbarrier_init.release.cluster;" ::: "memory");
#pragma unroll
      for (int k = 0; k < 4; k++) {
        mbar_expect_tx(BAR(B_FULL + k), ST_BYTES);
        tma_load_2d(sb + k * ST_BYTES + A_BYTES, &p.tmX, BAR(B_FULL + k), k * 64, tau * 256);
        LOAD_D(sb + k * ST_BYTES, tmD, BAR(B_FULL + k), k * 64, eps * 128);
        TIM(k);
      }
    }
  } else if ((tid >> 5) == 1) {
    if (elect_one()) {
#pragma unroll
      for (int s = 0; s < 4; s++) { mbar_init(BAR(B_EMPTY + s), 1); mbar_init(BAR(B_SD + s), 1); }
#pragma unroll
      for (int s = 0; s < 8; s++) { mbar_init(BAR(B_EP + s), 4); mbar_init(BAR(B_AW + s), 1); }
      mbar_init(BAR(B_STAT), 4); mbar_init(BAR(B_WC), 1); mbar_init(BAR(B_CD), 2);
      mbar_init(BAR(B_E23), 1); mbar_init(BAR(B_E23 + 1), 1); mbar_init(BAR(B_E23 + 2), 1); mbar_init(BAR(B_CH), 1); mbar_init(BAR(B_INFO), 1); mbar_init(BAR(B_PEER), 1);
      mbar_init(BAR(B_XCH), 1); mbar_init(BAR(B_XCH + 1), 1); mbar_init(BAR(B_GUX), 1);
      asm volatile("fence.mbarrier_init.release.cluster;" ::: "memory");
      mbar_expect_tx(BAR(B_XCH), 16384); mbar_expect_tx(BAR(B_XCH + 1), 16384); mbar_expect_tx(BAR(B_GUX), 256);
    }
  } else if (tid >= 256) {
    if (START_PF) prefetch_l2(((tid & 64) ? (cid < 64 ? p.Dre : p.Dim) + (cid & 63) * 16384 : p.x + cid * 16384) + ((tid >> 2) & 15) * 1024 + (tid & 3) * 64);
    tag = ld_relaxed32(&p.sc->epoch + threadIdx.y);
    wq = ldg128(p.wr + (tid & 127) * 8);
  }
  const int warp = __shfl_sync(0xffffffffu, tid >> 5, 0);
  __syncthreads();
  asm volatile("barrier.cluster.arrive.relaxed.aligned;" ::: "memory");

  if (warp >= 8) {
    reg_dec<72>();
    cluster_wait();
    tag = __shfl_sync(0xffffffffu, tag, 0) + 1;
    const int cid0 = cid;
    const uint32_t tag0 = tag, sb0 = sb;
    int a, lane, j, cid, tau, eps, m, grp, abrow, fc, src;
    uint32_t tag, c0, c1, sb, buf, bar0;
    bool ffn;
    auto BAR = [&](int i) { return sb + OFF_BAR + 8 * i; };
    auto fresh_ids = [&]() {
      const uint32_t z = uniform_zero_here();
      uint32_t l; asm volatile("mov.u32 %0, %%laneid;" : "=r"(l));
      a = warp - 8 + z; lane = l; j = a * 32 + l;
      cid = cid0 + z; tau = cid >> 4; eps = (cid >> 1) & 7; m = cid & 1; grp = tau * 2 + m; abrow = m * 1024 + eps * 128;
      const int ef = tau ? eps : eps ^ EX0;
      ffn = ef > 0; fc = (tau * 7 + ef - 1) * 64; src = (fc >> 5) + m;
      tag = tag0 + z; c0 = code_of(tag); c1 = c0 >> 1;
      sb = sb0 + z; buf = sb + OFF_AUX + a * 8192; bar0 = BAR(B_AW + 2 * a);
    };
    fresh_ids();
    if (a == 0 && lane < 16) pkt_clear128(&p.sc->xz[cid * 16 + lane]);
    if (lane < 2) pkt_clear128(&p.sc->dsum[cid * 16 + a * 4 + lane * 2]);
    if (a == 3 && lane < 10) pkt_clear128((lane < 4 ? &p.sc->abdone[cid * 64] : &p.sc->abflag[cid * 128 - 64]) + (lane >> 1) * 32 + (lane & 1) * 4);
    {
      const float s = warp_sum(((bf_lo(wq.x) + bf_hi(wq.x)) + (bf_lo(wq.y) + bf_hi(wq.y))) + ((bf_lo(wq.z) + bf_hi(wq.z)) + (bf_lo(wq.w) + bf_hi(wq.w))));
      if ((j >> 4) == eps) SM<uint4>(OFF_WR + (j & 15) * 16) = wq;
      if (lane == 0) { SM<float>(INFO_DS + a * 4) = s; SM<uint32_t>(INFO_ONES + a * 4) = 0x3F803F80u; }
    }
    const bf16* xrows = p.x + (cid * 16 + a * 4) * 1024;
    const bf16* drows = (cid < 64 ? p.Dre : p.Dim) + ((cid & 63) * 16 + a * 4) * 1024;
    if (XROW_PF) {
      wait_clk(t_entry, XROW_PF);
      prefetch_l2(xrows + lane * 64); prefetch_l2(xrows + 2048 + lane * 64);
    }
    fresh_ids();
    {
      wait_clk(t_entry, U_CLK);
      uint4 u[8]; uint32_t n = 0;
      bool more;
#pragma unroll 1
      do {
        uint32_t bad = 0;
#pragma unroll
        for (int q = 0; q < 8; q++) u[q] = pkt_ld128(&p.sc->u[a * 512 + lane * 2] + q * 64);
        if (n == 0 && lane < 2) { mbar_expect_tx(bar0 + lane * 8, 4096); bulk_load(buf + lane * 4096, xrows + lane * 2048, 4096, bar0 + lane * 8); }
#pragma unroll
        for (int q = 0; q < 8; q++) chk_code(bad, u[q], c0, c1);
        more = !(!__any_sync(0xffffffffu, bad & 1)) && ++n < SPIN_LIMIT;
        if (more) { __nanosleep(200); }
      } while (more);
      if (j == 0) TIM(96);
      if (DROW_PF) { prefetch_l2(drows + lane * 64); prefetch_l2(drows + 2048 + lane * 64); }
#pragma unroll 1
      for (int r2 = 0; r2 < 2; r2++) {
        float v8[8];
        mbar_wait(bar0 + r2 * 8, 0);
        if (lane == 0) TIM(140 + r2 * 4 + a);
#pragma unroll
        for (int r = 0; r < 2; r++) {
          float s0 = 0.f, s1 = 0.f, q0 = 0.f, q1 = 0.f;
          uint32_t zr = 0, zi = 0;
#pragma unroll
          for (int q = 0; q < 4; q++) {
            const uint4 v = lds128(buf + r2 * 4096 + r * 2048 + (q * 32 + lane) * 16);
            const uint32_t ww[4] = {v.x, v.y, v.z, v.w};
#pragma unroll
            for (int z = 0; z < 4; z++) {
              const float lo = bf_lo(ww[z]), hi = bf_hi(ww[z]);
              s0 += lo; s1 += hi; q0 = fmaf(lo, lo, q0); q1 = fmaf(hi, hi, q1);
            }
            zr = bfma2(v.x, u[2 * q].x, zr); zi = bfma2(v.x, u[2 * q].y, zi); zr = bfma2(v.y, u[2 * q].z, zr); zi = bfma2(v.y, u[2 * q].w, zi);
            zr = bfma2(v.z, u[2 * q + 1].x, zr); zi = bfma2(v.z, u[2 * q + 1].y, zi); zr = bfma2(v.w, u[2 * q + 1].z, zr); zi = bfma2(v.w, u[2 * q + 1].w, zi);
          }
          v8[4 * r] = s0 + s1; v8[4 * r + 1] = q0 + q1; v8[4 * r + 2] = bf_lo(zr) + bf_hi(zr); v8[4 * r + 3] = bf_lo(zi) + bf_hi(zi);
        }
        fold<8>(v8, 16, lane);
        if (lane == 0) { mbar_expect_tx(bar0 + r2 * 8, 4096); bulk_load(buf + r2 * 4096, drows + r2 * 2048, 4096, bar0 + r2 * 8); }
        fold<4>(v8, 8, lane); fold<2>(v8, 4, lane);
        v8[0] += __shfl_xor_sync(0xffffffffu, v8[0], 2);
        v8[0] += __shfl_xor_sync(0xffffffffu, v8[0], 1);
        SM<float>(OFF_REM + a * 64 + r2 * 32 + (lane >> 2) * 4) = v8[0];
        if (lane == 0) TIM(148 + r2 * 4 + a);
      }
    }
    bar_sync(NB_AUX, 128);
    fresh_ids();
    if (a == 0 && lane < 16) {
      const float4 v = SM<float4>(OFF_REM + lane * 16);
      const float mean = v.x * (1.f / 1024.f), rs = fast_rcp(ref_sd(fmaxf(v.y * (1.f / 1024.f) - mean * mean, 0.f)));
      pkt_st128(&p.sc->xz[cid * 16 + lane], __float_as_uint(bf16r(mean)) | (tag & 0xFFFFu), __float_as_uint(rs), pack_bf16(v.z * rs, v.w * rs), tag);
    }
    if (j == 32) { const float4 v = SM<float4>(INFO_DS); SM<float2>(INFO_WSUM) = make_float2((v.x + v.y) + (v.z + v.w), __uint_as_float(tag)); }
    if (j == 0) TIM(98);
#pragma unroll 1
    for (int r2 = 0; r2 < 2; r2++) {
      mbar_wait(bar0 + r2 * 8, 1);
      uint4 dv[8];
#pragma unroll
      for (int q = 0; q < 8; q++) dv[q] = lds128(buf + r2 * 4096 + (lane >> 4) * 2048 + q * 256 + (lane & 15) * 16);
      float s0 = __uint_as_float(zero_here()), s1 = 0.f;
#pragma unroll
      for (int q = 0; q < 8; q++) {
        const uint4 v = dv[q];
        s0 += (bf_lo(v.x) + bf_lo(v.y)) + (bf_lo(v.z) + bf_lo(v.w)); s1 += (bf_hi(v.x) + bf_hi(v.y)) + (bf_hi(v.z) + bf_hi(v.w));
      }
      s0 += s1;
#pragma unroll
      for (int o = 8; o > 0; o >>= 1) s0 += __shfl_xor_sync(0xffffffffu, s0, o);
      SM<float>(INFO_DS2 + (a * 4 + r2 * 2 + (lane >> 4)) * 4) = s0;
    }
    bar_sync(NB_AUX, 128);
    if (a == 1 && lane < 16) pkt_st64(&p.sc->dsum[cid * 16 + lane], SM<uint32_t>(INFO_DS2 + lane * 4), tag);
    if (j == 0) TIM(99);
    uint4* cpart = &p.sc->cpart[grp * 512 + eps * 64];
    pkt_clear128(cpart + (a * 8192 + lane)); pkt_clear128(cpart + (a * 8192 + lane) + 32);
    if (a == 3) { pkt_st64(&p.sc->ch[(lane >> 2) * 512 + cid * 4 + (lane & 3)], 0, 0); if (lane < 8) pkt_clear128(&p.sc->cs[cid * 8 + lane]); }
    {
      wait_clk(clk32(), XS_DELAY);
      uint2 v0, v1, cs; uint32_t n = 0;
      const uint32_t t16 = tag & 0xFFFFu;
      bool more;
#pragma unroll 1
      do {
        v0 = pkt_ld64(&p.sc->xz[tau * 256 + j]); v1 = pkt_ld64(&p.sc->xz[tau * 256 + j] + 128); cs = pkt_ld64(&p.sc->dsum[m * 1024 + eps * 128 + j]);
        more = !(__all_sync(0xffffffffu, (v0.x & 0xFFFFu) == t16 && (v1.x & 0xFFFFu) == t16 && cs.y == tag)) && ++n < SPIN_LIMIT;
        if (more) { __nanosleep(200); }
      } while (more);
      const int ro = OFF_RS + ((j & 7) >> 1) * 272 + (j >> 3) * 8 + (j & 1) * 4;
      SM<uint32_t>(ro) = v0.y ^ (m << 31); SM<uint32_t>(ro + 128) = v1.y ^ (m << 31);
      const uint32_t n0 = (v0.x >> 16) ^ 0x8000u, n1 = (v1.x >> 16) ^ 0x8000u;
      SM<uint4>(OFF_EXB + j * 16) = make_uint4(n0 | (n0 << 16), n0, 0, 0);
      SM<uint4>(OFF_EXB + 2048 + j * 16) = make_uint4(n1 | (n1 << 16), n1, 0, 0);
      const float c = 0.5f * __uint_as_float(cs.x), hi = bf16r(c), mid = bf16r(c - hi), lo = bf16r((c - hi) - mid);
      SM<uint4>(OFF_EXA + j * 16) = make_uint4((__float_as_uint(hi) >> 16) | __float_as_uint(mid), __float_as_uint(lo) >> 16, 0, 0);
      fence_async_smem();
      __syncwarp();
      if (lane == 0) mbar_arrive(BAR(B_STAT));
    }
    if (j == 0) TIM(100);
    auto all_published = [&](int half) {
      uint32_t n = 0;
#pragma unroll 1
      while (!__all_sync(0xffffffffu, ld_acquire32(&p.sc->abdone[(cid * 2 + half) * 32 + (lane & 7)]) == tag) && ++n < SPIN_LIMIT) {}
      if (lane == 31) {
        asm volatile("fence.proxy.async.global;" ::: "memory");
        mbar_arrive(BAR(B_ALL + half));
        TIM(80 + half);
      }
      __syncwarp();
    };
    if (TM_PF && j < 3) asm volatile("prefetch.tensormap [%0];" :: "l"(j == 0 ? &p.tmAbS : j == 1 ? &p.tmAbL : m ? &p.tmW1 : &p.tmW0) : "memory");
    {
      if (a == 3) {
        const uint32_t cl = poll64_warp(&p.sc->cl[cid * 16 + (lane & 3)], tag, 100);
        if (lane == 0) TIM(101);
        const bf16* wm = (m ? p.Wim : p.Wre) + tau * 256 + lane * 8;
        uint4 v[8];
#pragma unroll
        for (int i = 0; i < 8; i++) v[i] = ldg128(wm + ((__shfl_sync(0xffffffffu, cl, i >> 1) >> ((i & 1) * 16)) & 2047) * 2048);
        const int pos = cid * 4 + (lane & 3);
        const bf16* xc = p.x + ((__shfl_sync(0xffffffffu, cl, lane >> 3) >> ((lane & 4) * 4)) & 2047) * 1024 + (pos >> 3) * 16 + (pos & 7);
        const float x0 = ldbf(xc), x1 = ldbf(xc + 8), w0 = ldbf(p.wr + (pos >> 3) * 16 + (pos & 7)), w1 = ldbf(p.wr + (pos >> 3) * 16 + (pos & 7) + 8);
        if (lane < 4) SM<uint32_t>(INFO_CAND + lane * 4) = cl;
#pragma unroll
        for (int i = 0; i < 8; i++) SM<uint4>(OFF_WC + (lane >> 3) * 1024 + i * 128 + (((lane & 7) ^ i) << 4)) = v[i];
        fence_async_smem();
        __syncwarp();
        if (lane == 0) { mbar_arrive(BAR(B_WC)); TIM(102); }
        mbar_wait(BAR(B_CD), 0);
        wait_clk(clk32(), CP_DELAY);
        uint32_t n = 0;
        bool more;
#pragma unroll 1
        do {
          uint32_t bad = 0;
#pragma unroll
          for (int i = 0; i < 8; i++) v[i] = pkt_ld128(&p.sc->cpart[((lane >> 3) * 16 + ((lane >> 2) & 1)) * 512 + pos] + i * 1024);
#pragma unroll
          for (int i = 0; i < 8; i++) chk_code(bad, v[i], c0, c1);
          more = !(!__any_sync(0xffffffffu, bad & 1)) && ++n < SPIN_LIMIT;
          if (more) { __nanosleep(200); }
        } while (more);
        float y[4] = {0.f, 0.f, 0.f, 0.f};
#pragma unroll
        for (int i = 0; i < 8; i++) { y[0] += no_bit(v[i].x); y[2] += no_bit(v[i].y); y[1] += no_bit(v[i].z); y[3] += no_bit(v[i].w); }
#pragma unroll
        for (int i = 0; i < 4; i++) y[i] = bf16r(y[i]);
        __syncwarp();
        fold<4>(y, 4, lane);
        const uint32_t hp = pack_bf16(x0 + bf16r(y[0]), x1 + bf16r(y[1]));
        pkt_st64(&p.sc->ch[(lane >> 2) * 512 + pos], hp, tag);
        float st[3] = {bf_lo(hp) + bf_hi(hp), bf_lo(hp) * bf_lo(hp) + bf_hi(hp) * bf_hi(hp), bf_lo(hp) * w0 + bf_hi(hp) * w1};
#pragma unroll
        for (int o = 1; o < 4; o <<= 1) {
#pragma unroll
          for (int i = 0; i < 3; i++) st[i] += __shfl_xor_sync(0xffffffffu, st[i], o);
        }
        if ((lane & 3) == 0) pkt_st128(&p.sc->cs[cid * 8 + (lane >> 2)], with_bit(st[0], c0), with_bit(st[1], c1), __float_as_uint(st[2]), tag);
        if (lane == 0) TIM(119);
      }
      if (a < 2) {
        uint32_t* fl = lane < 2 ? &p.sc->abflag[(cid * 4 + 2 * a + lane) * 32] : &p.sc->abdone[(((cid & 15) + (lane & 7) * 16) * 2 + a) * 32 + tau];
        if (lane == 0) {
          if (a == 1) mbar_wait(BAR(B_SD), 0);
          const uint32_t t1 = clk32();
#pragma unroll 1
          for (int i = 2 * a; i < 2 + 6 * a; i++) {
            const int w = i & 1, c = a ? (TR_ORDER ? 4 - (i >> 1) : i < 6 ? (i >> 1) + 1 : 1) : 0;
            if (a == 1) wait_clk(t1, HI_DELAY + (i - 2) * HI_PACE);
            mbar_wait(BAR(B_EP + w * 4 + c), 0);
            TIM(64 + i);
            fence_async_smem();
            tma_store_2d(&p.tmAbS, sb + off_stage(c) + w * 8192, tau * 256 + c * 64, abrow + w * 64);
            if (w) { bulk_commit(); bulk_wait_all(); mbar_arrive(BAR(B_SD + c)); }
          }
          TIM(72 + a * 2);
          asm volatile("fence.proxy.async.global;" ::: "memory");
          asm volatile("st.release.gpu.global.b32 [%0], %1;" :: "l"(fl), "r"(tag) : "memory");
          TIM(73 + a * 2);
        }
        __syncwarp();
        if ((lane == 1 && a == 0) || (lane >> 3) == 1) st_relaxed32(fl, tag);
        if (a == 0) { __nanosleep(ALL_NS); all_published(0); }
        else {
          uint32_t n = 0;
#pragma unroll 1
          while (__any_sync(0xffffffffu, ld_acquire32(&p.sc->abflag[(((cid + 16) & 127) * 4 + 2) * 32]) != tag) && ++n < SPIN_LIMIT) {}
#pragma unroll 1
          for (int i = 0; i < 3; i++) {
            if (elect_one()) {
              if (i == 0) asm volatile("fence.proxy.async.global;" ::: "memory");
              mbar_wait(BAR(B_E23 + i), 0);
              tma_load_2d(sb + ((i + 3) & 3) * ST_BYTES, &p.tmAbL, BAR(B_FULL + ((i + 3) & 3)), (tau * 256 + 320 + i * 64) & 2047, abrow);
              TIM(82 + i);
            }
            __syncwarp();
            if (i == ALL_AT) all_published(1);
          }
        }
      } else if (a == 2) {
        const uint32_t* fl = &p.sc->abflag[(((cid + 16 + 16 * (lane & 1)) & 127) * 4 + (lane & 1)) * 32];
        mbar_wait(BAR(B_SD), 0);
        __nanosleep(LO_NS);
        uint32_t n = 0, seen = 0;
#pragma unroll 1
        for (int c = 0; c < 4; c++) {
          const uint32_t n0 = n;
#pragma unroll 1
          while (c < 2 && (PV == 1 ? (seen & 3) != 3 : !((seen >> c) & 1)) && ++n < SPIN_LIMIT) seen = __ballot_sync(0xffffffffu, ld_acquire32(fl) == tag);
          if (PV == 2 ? lane == c : elect_one()) {
            if (!C1_AUX || c != 1) mbar_wait(BAR(B_SD + c), 0);
            mbar_wait(BAR(c < 3 ? B_FULL + c : B_EMPTY), 0);
            if (c == 2) mbar_wait(BAR(B_ALL), 0);
            if (PV == 2 ? c < 2 : n != n0) asm volatile("fence.proxy.async.global;" ::: "memory");
            tma_load_2d(sb + c * ST_BYTES, &p.tmAbL, BAR(B_FULL + c), k_col(tau, 4 + c), abrow);
            TIM(130 + c);
          }
          __syncwarp();
        }
      }
      __syncwarp();
    }
    mbar_wait(BAR(B_CD), 0);
    if (C1_AUX) mbar_wait(BAR(B_SD + 1), 0);
    const uint64_t pol_ef = policy_evict_first();
    auto load_unit = [&](int v) {
      if (elect_one()) {
        const uint32_t dst = buf + (v & 1) * 4096, bar = bar0 + (v & 1) * 8;
        mbar_expect_tx(bar, 4096);
        if (v < 8) {
          LOAD_F(dst, &p.tmG, bar, fc, m * 512 + (a * 8 + v) * 16);
          LOAD_F(dst + 2048, &p.tmU, bar, fc, m * 512 + (a * 8 + v) * 16);
        } else LOAD_F(dst, &p.tmDn, bar, a * 256, src * 32 + (v - 8) * 8);
      }
    };
    if (TM_PF && j < 3) asm volatile("prefetch.tensormap [%0];" :: "l"(j == 0 ? &p.tmG : j == 1 ? &p.tmU : &p.tmDn) : "memory");
    if (ffn && (!LU0_LATE || a == 1)) load_unit(0);
    if (a != 1) {
      bar_sync(NB_SEL, 96);
      wait_clk(clk32(), CS_DELAY);
      fresh_ids();
      if (a == 0 && lane < NCH) {
        if (lane == 0) mbar_expect_tx(BAR(B_CH), NCH * 2048);
        bulk_load(sb + OFF_AUX + 4096 + (lane >> 1) * 8192 + (lane & 1) * 2048, &p.sc->ch[lane * 512 + m * 256], 2048, BAR(B_CH));
      }
      const int j3 = a ? j - 32 : j;
      uint4 v[11]; uint32_t n = 0;
      bool more;
#pragma unroll 1
      do {
#pragma unroll
        for (int i = 0; i < 11; i++) v[i] = pkt_ld128(&p.sc->cs[j3] + (i < 10 || a < 3 ? i * 96 : 0));
        uint32_t bad = 0;
#pragma unroll
        for (int i = 0; i < 11; i++) { chk(bad, v[i].x, c0); chk(bad, v[i].y, c1); }
        bad &= 1;
#pragma unroll
        for (int i = 0; i < 11; i++) chk(bad, v[i].w, tag);
        more = __any_sync(0xffffffffu, bad) && ++n < SPIN_LIMIT;
        if (more) __nanosleep(200);
      } while (more);
      if (j == 0) TIM(97);
      if (ffn && LU0_LATE) load_unit(0);
      float st[3] = {0.f, 0.f, 0.f};
      if (a < 3) { st[0] = no_bit(v[10].x); st[1] = no_bit(v[10].y); st[2] = __uint_as_float(v[10].z); }
#pragma unroll
      for (int i = 0; i < 10; i++) { st[0] += no_bit(v[i].x); st[1] += no_bit(v[i].y); st[2] += __uint_as_float(v[i].z); }
#pragma unroll
      for (int o = 8; o < 32; o <<= 1) {
#pragma unroll
        for (int i = 0; i < 3; i++) st[i] += __shfl_xor_sync(0xffffffffu, st[i], o);
      }
      if (lane < 8) SM<float4>(OFF_XS + ((j3 >> 5) * 8 + lane) * 16) = make_float4(st[0], st[1], st[2], 0.f);
      bar_sync(NB_SEL, 96);
      const float4 f0 = SM<float4>(OFF_XS + (lane & 7) * 16), f1 = SM<float4>(OFF_XS + 128 + (lane & 7) * 16), f2 = SM<float4>(OFF_XS + 256 + (lane & 7) * 16);
      const float mu = ((f0.x + f1.x) + f2.x) * (1.f / 1024.f);
      float mb = bf16r(mu), inv = fast_rcp(ref_sd(fmaxf(((f0.y + f1.y) + f2.y) * (1.f / 1024.f) - mu * mu, 0.f)));
      const uint32_t kk = make_key(bf16r((((f0.z + f1.z) + f2.z) - mb * SM<float>(INFO_WSUM)) * inv), SM<uint16_t>(INFO_CAND + (lane & 7) * 2));
      const uint32_t key = __reduce_max_sync(0xffffffffu, kk);
      const int win = __ffs(__ballot_sync(0xffffffffu, kk == key)) - 1;
      mb = __shfl_sync(0xffffffffu, mb, win); inv = __shfl_sync(0xffffffffu, inv, win);
      if (j == 0) { SM<uint2>(INFO_KEY) = make_uint2(key, win); SM<float2>(INFO_LN) = make_float2(mb, inv); }
      mbar_wait(BAR(B_CH), 0);
      bar_sync(NB_SEL, 96);
#pragma unroll 1
      for (int i = j3; i < 128; i += 96) {
        uint4 r = lds128(sb + OFF_AUX + 4096 + (win >> 1) * 8192 + (win & 1) * 2048 + i * 16);
        if (win >= NCH) r.y = ~tag;
#pragma unroll 1
        while ((r.y != tag || r.w != tag) && ++n < SPIN_LIMIT) r = pkt_ld128(&p.sc->ch[win * 512 + m * 256 + 2 * i]);
        auto ln = [&](float h) { return bf16r(bf16r(h - mb) * inv); };
        const int d = (i >> 2) * 16 + (i & 3) * 2;
        SM<float2>(OFF_XS + d * 4) = make_float2(ln(bf_lo(r.x)), ln(bf_lo(r.z)));
        SM<float2>(OFF_XS + (d + 8) * 4) = make_float2(ln(bf_hi(r.x)), ln(bf_hi(r.z)));
      }
      __syncwarp();
    }
    bar_sync(NB_AUX, 128);
    if (j == 0) {
      mbar_arrive(BAR(B_INFO)); TIM(103);
      if (cid == 0) st_relaxed32(&p.sc->epoch, tag);
    }
    const uint32_t t2 = clk32();
    fresh_ids();
    uint2 hp2 = make_uint2(0, 0);
    const uint2* hpp = &p.sc->ch[SM<uint32_t>(INFO_KEY + 4) * 512 + (cid >> 1) * 8 + (lane & 7)];
    if (a == 3) { hp2 = pkt_ld64(hpp); if (lane == 0) asm volatile("prefetch.tensormap [%0];" :: "l"(&p.tmY) : "memory"); }
    if (!ffn) {
      wait_clk(t2, YPART_DELAY);
    } else {
      load_unit(1);
      const int r = lane >> 3;
      float acc[8] = {0.f, 0.f, 0.f, 0.f, 0.f, 0.f, 0.f, 0.f};
#pragma unroll 1
      for (int v = 0; v < 8; v++) {
        const uint4 x0 = lds128(sb + OFF_XS + ((a * 8 + v) * 16 + (r & 1) * 8) * 4), x1 = lds128(sb + OFF_XS + ((a * 8 + v) * 16 + (r & 1) * 8 + 4) * 4);
        const float xv[8] = {__uint_as_float(x0.x), __uint_as_float(x0.y), __uint_as_float(x0.z), __uint_as_float(x0.w), __uint_as_float(x1.x), __uint_as_float(x1.y), __uint_as_float(x1.z), __uint_as_float(x1.w)};
        mbar_wait(bar0 + (v & 1) * 8, (v >> 1) & 1);
        gemv8x8<128>(acc, buf + (v & 1) * 4096 + r * 1024 + (lane & 7) * 16, xv);
        fence_regs(acc);
        __syncwarp();
        wait_clk(t2, v * UNIT_PACE);
        load_unit(v + 2);
        if (j == 0) TIM(104 + v);
      }
      pkt_clear128(&p.sc->ypart[(a * NSRC + src) * 64 + lane * 2]); pkt_clear128(&p.sc->ypart[(a * NSRC + src) * 64 + lane * 2] + 1);
      fold<8>(acc, 8, lane);
      bar_sync(NB_AUX, 128);
      SM<float4>(OFF_XS + (a * 128 + (r >> 1) * 64 + (lane & 7) * 8 + (r & 1) * 4) * 4) = make_float4(acc[0], acc[1], acc[2], acc[3]);
      bar_sync(NB_AUX, 128);
      auto psum = [&](int i) { return (SM<float>(OFF_XS + i * 4) + SM<float>(OFF_XS + (128 + i) * 4)) + (SM<float>(OFF_XS + (256 + i) * 4) + SM<float>(OFF_XS + (384 + i) * 4)); };
      if (a < 2) st_async_b32(mapa(sb + OFF_REM + j * 4, m ^ 1), mapa(BAR(B_GUX), m ^ 1), __float_as_uint(psum(a * 64 + (m ^ 1) * 32 + lane)));
      const float og = psum(m * 32 + lane), ou = psum(64 + m * 32 + lane);
      mbar_wait(BAR(B_GUX), 0);
      const float rg = SM<float>(OFF_REM + lane * 4), ru = SM<float>(OFF_REM + 128 + lane * 4);
      const float act = swiglu(m ? rg + og : og + rg, m ? ru + ou : ou + ru);
      if (j == 0) TIM(112);
      float y[8] = {0.f, 0.f, 0.f, 0.f, 0.f, 0.f, 0.f, 0.f};
#pragma unroll 1
      for (int v = 8; v < 12; v++) {
        float av[8];
#pragma unroll
        for (int i = 0; i < 8; i++) av[i] = __shfl_sync(0xffffffffu, act, (v - 8) * 8 + i);
        mbar_wait(bar0 + (v & 1) * 8, (v >> 1) & 1);
        gemv8x8<512>(y, buf + (v & 1) * 4096 + lane * 16, av);
        fence_regs(y);
        __syncwarp();
        if (v < 10) load_unit(v + 2);
        if (j == 0) TIM(105 + v);
      }
      fresh_ids();
      uint4* ypart = &p.sc->ypart[(a * NSRC + src) * 64 + lane * 2];
      pkt_st128(ypart, with_bit(y[0], c0), with_bit(y[1], c1), with_bit(y[2], c0), with_bit(y[3], c1));
      pkt_st128(ypart + 1, with_bit(y[4], c0), with_bit(y[5], c1), with_bit(y[6], c0), with_bit(y[7], c1));
      if (lane == 0) TIM(160 + a);
      __nanosleep(ROW_NS);
    }
    if (a == 3) {
      const uint32_t hh = __all_sync(0xffffffffu, hp2.y == tag) ? hp2.x : poll64_warp(&p.sc->ch[SM<uint32_t>(INFO_KEY + 4) * 512 + (cid >> 1) * 8 + (lane & 7)], tag, 100);
      const uint32_t key = SM<uint32_t>(INFO_KEY);
      const float h = m ? bf_hi(hh) : bf_lo(hh), hn = bf16r(bf16r(h - SM<float>(INFO_LN)) * SM<float>(INFO_LN + 4));
      float sig = sigmoid_bf(key_val(key));
      bf16* op = p.out + (key_row(key) * 1024 + cid * 8 + (lane & 7));
      asm volatile("" : "+f"(sig), "+l"(op));
      uint4 v[7]; uint32_t n = 0;
      bool more;
#pragma unroll 1
      do {
        if (elect_one()) { mbar_expect_tx(bar0, NSRC * 32); tma_load_2d(buf, &p.tmY, bar0, (cid & 31) * 16, (cid >> 5) * NSRC); }
        mbar_wait(bar0, n & 1);
        uint32_t bad = 0;
#pragma unroll
        for (int i = 0; i < 7; i++) { v[i] = lds128(buf + i * 512 + lane * 16); chk_code(bad, v[i], c0, c1); }
        more = __any_sync(0xffffffffu, bad & 1) && ++n < SPIN_LIMIT;
        if (more) __nanosleep(Y_NS);
      } while (more);
      if (lane == 0) TIM(164);
      float y[4] = {0.f, 0.f, 0.f, 0.f};
#pragma unroll
      for (int i = 0; i < 7; i++) { y[0] += no_bit(v[i].x); y[1] += no_bit(v[i].y); y[2] += no_bit(v[i].z); y[3] += no_bit(v[i].w); }
      fold<4>(y, 16, lane); fold<2>(y, 8, lane);
      y[0] += __shfl_xor_sync(0xffffffffu, y[0], 4);
      y[0] += __shfl_xor_sync(0xffffffffu, y[0], 2);
      const float ys = __shfl_sync(0xffffffffu, y[0], (lane & 3) * 8 + ((lane >> 2) & 1));
      if (lane < 8) st_bf16(op, routed_out(h, hn, ys, sig));
      if (lane == 0) { TIM(118); pkt_st64(&p.sc->rdone[cid], 0, tag); }
    }
  } else {
    reg_inc<216>();
    cluster_wait();
    const uint32_t sb = __shfl_sync(0xffffffffu, smem_u32(smem_raw), 0);
    auto BAR = [&](int i) { return sb + OFF_BAR + 8 * i; };
    const int w = warp >> 2, wi = warp & 3, t = tid & 127;
    const int turn_me = NB_TURN0 + w, turn_other = NB_TURN1 - w;
    const uint64_t dA0 = make_desc(sb + w * 8192);
    uint64_t dA, dB;
    int tau, eps, m, grp, abrow, fc, src;
    bool ffn;
    const CUtensorMap* tmD; const CUtensorMap* tmW;
    auto new_desc = [&](int salt) {
      const uint32_t z = salt < 0 ? uniform_zero_here() : salt & blockIdx.y;
      dA = dA0 + z; dB = dA0 + (z + ((A_BYTES - w * 8192) >> 4));
      const int c = cid + z;
      tau = c >> 4; eps = (c >> 1) & 7; m = c & 1; grp = tau * 2 + m; abrow = m * 1024 + eps * 128;
      const int ef = tau ? eps : eps ^ EX0;
      ffn = ef > 0; fc = (tau * 7 + ef - 1) * 64; src = (fc >> 5) + m;
      tmD = &p.tmD0 + m; tmW = &p.tmW0 + m;
    };
    constexpr int SL = ST_BYTES >> 4;
    float acc[128];
#pragma unroll
    for (int i = 0; i < 128; i++) acc[i] = 0.f;
    if (w == 1) bar_arrive(NB_TURN0, 256);
    auto full = [&](int k) { mbar_wait(BAR(B_FULL + (k & 3)), (k >> 2) & 1); CT(64 + k); };
    const uint64_t pol_ef = policy_evict_first();
    auto refill_g2 = [&](int k, int mode) {
      if (warp == 4) {
        if (elect_one()) {
          const int s = k & 3, s0 = k_col(tau, k - 12);
          TIM(k + 4);
          mbar_expect_tx(BAR(B_FULL + s), mode ? ST_BYTES : B_BYTES);
          if (k == 19) mbar_arrive(BAR(B_EMPTY));
          LOAD_W(sb + s * ST_BYTES + A_BYTES, tmW, BAR(B_FULL + s), s0, grp * 128);
          LOAD_W(sb + s * ST_BYTES + A_BYTES + 16384, tmW, BAR(B_FULL + s), s0, (grp ^ 1) * 128);
          if (mode == 2) tma_load_2d(sb + s * ST_BYTES, &p.tmAbL, BAR(B_FULL + s), s0, abrow);
        }
        __syncwarp();
      }
    };
    auto mma_ss = [&](int k) {
#pragma unroll
      for (int kk = 0; kk < 4; kk++) wgmma_n256(acc, dA + (k & 3) * SL + kk * 2, dB + (k & 3) * SL + kk * 2);
    };
    const CUtensorMap* rf_tm; uint32_t rf_dst; int rf_row, rf_c; bool rf_on;
    auto rf_set = [&](const CUtensorMap* tm, uint32_t dst, int row) {
      rf_tm = (const CUtensorMap*)__shfl_sync(0xffffffffu, (unsigned long long)tm, 0);
      rf_dst = __shfl_sync(0xffffffffu, dst, 0); rf_row = __shfl_sync(0xffffffffu, row, 0);
    };
    auto refill = [&](int s) {
      if (rf_on) {
        if (elect_one()) tma_load_2d(rf_dst + s * ST_BYTES, rf_tm, BAR(B_FULL + s), rf_c, rf_row);
        __syncwarp();
      }
      if (tid == 224) mbar_expect_tx(BAR(B_FULL + s), ST_BYTES);
    };
    const bf16* pf; int pf_step; bool pf_on;
    auto pf_ffn = [&](int v) {
      pf_on = ffn && v >= 0 && v < 12;
      pf = v < 8 ? ((lane & 16) ? p.wup : p.wgate) + (m * 512 + (wi * 8 + v) * 16 + (lane & 15)) * 3584 + fc : p.wdown + (src * 32 + (v - 8) * 8) * 1024 + t * 64;
      pf_step = v < 8 ? 16 * 3584 : 8192;
    };
    auto prefetch = [&](int s) { if (pf_on && (wi >> 1) == (s & 1)) prefetch_l2(pf + (s >> 1) * pf_step); };
    auto kstep = [&](int k) {
      full(k);
      bar_sync(turn_me, 256);
      wgmma_fence();
      mma_ss(k);
      wgmma_commit();
      bar_arrive(turn_other, 256);
    };

    uint32_t R[64];
    auto load_rs = [&](auto gi) {
      const uint32_t rsa = sb + OFF_RS + (lane & 3) * 272;
#pragma unroll
      for (int i = 4 * decltype(gi)::value; i < 4 * decltype(gi)::value + 4; i++) { const uint4 v = lds128(rsa + i * 16); R[4 * i] = v.x; R[4 * i + 1] = v.y; R[4 * i + 2] = v.z; R[4 * i + 3] = v.w; }
    };
#pragma unroll
    for (int i = 0; i < (RS_EARLY ? 16 : 0); i++) R[i] = 0;
    new_desc(64);
    rf_on = (warp >> 1) == 2;
    rf_set(wi ? tmD : &p.tmX, wi ? sb : sb + A_BYTES, wi ? eps * 128 : tau * 256);
#pragma unroll 1
    for (int k4 = 0; k4 < 12; k4 += 4) {
#pragma unroll
      for (int s = 0; s < 4; s++) {
        kstep(k4 | s);
        if (s == 0) {
          if (w == 0) pf_ffn((k4 - PF1_K) >> 1);
          else {
            pf_on = W_PF && (k4 == 8 || (W_PF > 1 && k4 == 4 && (lane & 7) < 3));
            pf = (m ? p.Wim : p.Wre) + (tau * 256 + eps * 32 + wi * 4 + (lane >> 3)) * 2048 + k_col(tau, (lane & 7) + (W_PF > 1 && k4 == 8 ? 3 : 0));
            pf_step = 16 * 2048;
          }
        }
        rf_c = (k4 + s + 4) * 64;
        prefetch(s);
        if (RS_EARLY && s == 3 && k4 == 8) { mbar_wait(BAR(B_STAT), 0); load_rs(std::integral_constant<int, 0>()); }
        if (s == 3) new_desc(k4);
        if (s == 0 || s == 3) pf += zero_here();
        wgmma_wait<0>();
        refill(s);
      }
    }
    kstep(12);
    if (!RS_EARLY) { mbar_wait(BAR(B_STAT), 0); load_rs(std::integral_constant<int, 0>()); }
    CT(1);
    load_rs(std::integral_constant<int, 1>());
    wgmma_wait<0>(); refill_g2(12, 0);
    if (!RS3_LATE) load_rs(std::integral_constant<int, 3>());
    auto mma_h = [&](float (&d)[64], int s, int half) {
#pragma unroll
      for (int kk = 0; kk < 4; kk++) wgmma_n128(d, dA + s * SL + kk * 2, dB + s * SL + half * 1024 + kk * 2);
    };
    const int rho = 16 * wi + (lane & 15);
    const uint32_t arow = sb + w * 8192 + rho * 128;
    auto convert = [&](auto cc, const float* d) {
      const float z = __uint_as_float(zero_here());
#pragma unroll
      for (int jj = 8 * decltype(cc)::value; jj < 8 * decltype(cc)::value + 8; jj++) {
        const float r0 = __uint_as_float(R[2 * jj]), r1 = __uint_as_float(R[2 * jj + 1]);
        const float* ac = &d[4 * (jj & 7)];
        R[2 * jj] = pack_bf16(fmaf(ac[0], r0, z), fmaf(ac[1], r1, z));
        R[2 * jj + 1] = pack_bf16(fmaf(ac[2], r0, z), fmaf(ac[3], r1, z));
      }
    };
    auto put = [&](auto cc) {
      constexpr int c = decltype(cc)::value;
#pragma unroll
      for (int jj = 8 * c; jj < 8 * c + 8; jj += 2)
        stsm_x4(arow + off_stage(c) + ((((jj & 7) + (lane >> 4)) ^ (rho & 7)) << 4), R[2 * jj], R[2 * jj + 1], R[2 * jj + 2], R[2 * jj + 3]);
      __syncwarp();
      if (lane == 0) mbar_arrive(BAR(B_EP + w * 4 + c));
    };
    {
      float lo[32], hi[96];
      fence_regs(acc);
#pragma unroll
      for (int i = 0; i < 32; i++) asm volatile("mov.b32 %0, %1;" : "=f"(lo[i]) : "f"(acc[i]));
#pragma unroll
      for (int i = 0; i < 96; i++) asm volatile("mov.b32 %0, %1;" : "=f"(hi[i]) : "f"(acc[32 + i]));
      auto mma_p = [&](auto& d, int s, int boff) {
#pragma unroll
        for (int kk = 0; kk < 4; kk++) wgmma_part(d, dA + s * SL + kk * 2, dB + s * SL + boff + kk * 2);
      };
      const uint64_t dEA = make_desc_noswz(sb + OFF_EXA + w * 1024), dEB = make_desc_noswz(sb + OFF_EXB);
      full(13); full(14);
      bar_sync(turn_me, 256);
      wgmma_fence();
      mma_p(lo, 1, 0); mma_p(lo, 2, 0);
      wgmma_commit();
      bar_arrive(turn_other, 256);
      new_desc(ND1);
      full(15);
      bar_sync(turn_me, 256);
      wgmma_fence();
      mma_p(lo, 3, 0);
      wgmma_part(lo, dEA, dEB);
      wgmma_commit();
      mma_p(hi, 1, 512);
      wgmma_commit();
      bar_arrive(turn_other, 256);
      new_desc(ND2);
      wgmma_wait<1>();
      fence_regs(lo);
      CT(15);
      convert(std::integral_constant<int, 0>(), lo); put(std::integral_constant<int, 0>());
      if (RS3_LATE) load_rs(std::integral_constant<int, 3>());
      wgmma_wait<0>(); refill_g2(13, 0);
      bar_sync(turn_me, 256);
      wgmma_fence();
      mma_p(hi, 2, 512);
      wgmma_commit();
      mma_p(hi, 3, 512);
      wgmma_part(hi, dEA, dEB + 64);
      wgmma_commit();
      bar_arrive(turn_other, 256);
      load_rs(std::integral_constant<int, 2>());
      wgmma_wait<1>(); refill_g2(14, 0);
      wgmma_wait<0>(); refill_g2(15, 0);
      fence_regs(hi);
      CT(2);
      convert(std::integral_constant<int, 3>(), hi + 64);
      put(std::integral_constant<int, 3>());
      convert(std::integral_constant<int, 1>(), hi);
      convert(std::integral_constant<int, 2>(), hi + 32);
    }
    CT(3);
    float cc[4];
    auto cand_mma = [&]() {
      const uint64_t dC = make_desc(sb + OFF_WC);
      wgmma_n8_rs<0>(cc, R, dC);
#pragma unroll
      for (int i = 1; i < 12; i++) wgmma_n8_rs<1>(cc, R + 4 * i, dC + (i >> 2) * 64 + (i & 3) * 2);
#pragma unroll
      for (int kk = 0; kk < 4; kk++) wgmma_n8(cc, dA + 3 * SL + kk * 2, dC + 192 + kk * 2);
      wgmma_commit();
    };
    auto cand_pub = [&]() {
      fence_regs(cc);
      const uint32_t cd = code_of(SM<uint32_t>(INFO_TAG));
      if (t == 0) mbar_arrive(BAR(B_CD));
      pkt_st128(&p.sc->cpart[((lane & 3) * 16 + grp) * 512 + eps * 64 + warp * 8 + (lane >> 2)], with_bit(cc[0], cd), with_bit(cc[1], cd >> 1), with_bit(cc[2], cd), with_bit(cc[3], cd >> 1));
      CT(5);
    };
    new_desc(ND3);
    if (CAND_EARLY) { fence_async_smem(); mbar_wait(BAR(B_WC), 0); CT(4); }
    full(16);
    if (!SPLIT17) full(17);
    bar_sync(turn_me, 256);
    wgmma_fence();
    if (CAND_EARLY) cand_mma();
    wgmma_n256_rs_init(acc, R, dB);
#pragma unroll
    for (int kk = 1; kk < 4; kk++) wgmma_n256_rs<1>(acc, R + 4 * kk, dB + kk * 2);
    wgmma_commit();
    if (SPLIT17) { full(17); wgmma_fence(); }
#pragma unroll
    for (int kk = 0; kk < 4; kk++) wgmma_n256_rs<1>(acc, R + 16 + 4 * kk, dB + SL + kk * 2);
    wgmma_commit();
    bar_arrive(turn_other, 256);
    if (CAND_EARLY) { wgmma_wait<2>(); put(std::integral_constant<int, 2>()); cand_pub(); }
    else put(std::integral_constant<int, 2>());
    if (PFM) { pf_ffn((12 - PF1_K) / 2 + w); if (pf_on) prefetch_l2(pf); }
    wgmma_wait<1>(); refill_g2(16, 1);
    wgmma_wait<0>(); refill_g2(17, 1);
    if (!CAND_EARLY) { fence_async_smem(); mbar_wait(BAR(B_WC), 0); CT(4); }
    full(18);
    bar_sync(turn_me, 256);
    wgmma_fence();
    if (!CAND_EARLY) cand_mma();
#pragma unroll
    for (int kk = 0; kk < 4; kk++) wgmma_n256_rs<1>(acc, R + 32 + 4 * kk, dB + 2 * SL + kk * 2);
    wgmma_commit();
    bar_arrive(turn_other, 256);
    if (!CAND_EARLY) { wgmma_wait<1>(); cand_pub(); }
    put(std::integral_constant<int, 1>());
    wgmma_wait<0>(); refill_g2(18, 1);
    kstep(19);
    if (PFM == 4) { pf_ffn((12 - PF1_K) / 2 + 2 + w); if (pf_on) prefetch_l2(pf); }
    new_desc(68);
    rf_set(wi == 2 ? &p.tmAbL : tmW, wi == 2 ? sb : sb + A_BYTES + wi * 16384, wi == 2 ? abrow : (grp ^ wi) * 128);
    wgmma_wait<0>(); refill_g2(19, 1);
    const int g = lane >> 2, q = lane & 3;
    uint4 ha[4], hb[4], wv[4], info = make_uint4(0, 0, 0, 0);
#pragma unroll
    for (int i = 0; i < 4; i++) ha[i] = hb[i] = wv[i] = make_uint4(0, 0, 0, 0);
    auto load_x = [&](auto ii) {
      constexpr int i = decltype(ii)::value;
      const bf16* xp = p.x + ((grp * 128 + warp * 16 + g) * 1024 + eps * 128 + q * 8);
      ha[i] = ldg128(xp + i * 32); hb[i] = ldg128(xp + 8192 + i * 32);
    };
    auto load_w = [&]() {
      mbar_wait(BAR(B_INFO), 0);
#pragma unroll
      for (int i = 0; i < 4; i++) wv[i] = lds128(sb + ((g & 1) ? OFF_WR + (i * 4 + q) * 16 : INFO_ONES));
      info = lds128(sb + OFF_INFO);
    };

    rf_on = w == 1 && wi < 3;
    rf_c = k_col(tau, 7);
#pragma unroll 1
    for (int k4 = 20; k4 < 44; k4 += 4) {
#pragma unroll
      for (int s = 0; s < 4; s++) {
        kstep(k4 | s);
        if (s == 0) {
          if (w == 0) { pf_ffn((k4 >> 1) - PF2_K / 2 + (12 - PF1_K) / 2 + PFM); pf_on = pf_on && k4 >= PF2_K; }
          else {
            pf_on = k4 == XPF_K;
            pf = p.x + (grp * 128 + (t >> 1)) * 1024 + eps * 128 + (t & 1) * 64;
            pf_step = 64 * 1024;
          }
        }
        rf_c = k_next(rf_c, k4 + s - 12);
        if (s == 0 && k4 == 20 && warp == 6) mbar_wait(BAR(B_ALL), 0);
        if (s == 2 && k4 == 24 && warp == 6) mbar_wait(BAR(B_ALL + 1), 0);
        prefetch(s);
        if (k4 == 40) {
          if (s == XS0 - 1) load_w();
          if (s == XS0) load_x(std::integral_constant<int, 0>());
          if (s == XS0 + 1) load_x(std::integral_constant<int, 1>());
          if (s == XS0 + 2) load_x(std::integral_constant<int, 2>());
        }
        if (s == 3) new_desc(k4);
        if (s == 0 || s == 3) pf += zero_here();
        wgmma_wait<0>();
        if (((s == 3 && k4 == 20) || (s < 2 && k4 == 24)) && warp == 6) { if (lane == 0) mbar_arrive(BAR(B_E23 + ((s + 1) & 3))); }
        else refill(s);
      }
    }
    const int row0 = grp * 128 + warp * 16 + g;
    kstep(44);
    uint4* hst = &p.sc->hstat[grp * 1024 + warp * 16 + g];
    if (q == (g >> 1)) { pkt_clear128(hst + eps * 128); pkt_clear128(hst + eps * 128 + 8); }
    if (XS0 == 9) { load_w(); load_x(std::integral_constant<int, 0>()); load_x(std::integral_constant<int, 1>()); load_x(std::integral_constant<int, 2>()); load_x(std::integral_constant<int, 3>()); }
    if (XS0 == 1) load_x(std::integral_constant<int, 3>());
    if (XS0 == 2) load_x(std::integral_constant<int, 2>());
    if (XS0 == 3) load_x(std::integral_constant<int, 1>());
    wgmma_wait<0>();
    if (tid == 128) mbar_arrive_remote(mapa(BAR(B_PEER), m ^ 1));
    uint32_t hp[32];
    bf16* op; uint4* hpub;
    uint32_t cd, ast, ald, zr;
    auto swz = [](int row) { return ((row & 1) << 2) | ((row >> 1) & 3); };
    {
      float as[64], ak[64];
      fence_regs(acc);
#pragma unroll
      for (int i = 0; i < 64; i++) asm volatile("mov.b32 %0, %1;" : "=f"(as[i]) : "f"(acc[64 + i]));
#pragma unroll
      for (int i = 0; i < 64; i++) asm volatile("mov.b32 %0, %1;" : "=f"(ak[i]) : "f"(acc[i]));
      full(45); full(46);
      bar_sync(turn_me, 256);
      wgmma_fence();
      mma_h(as, 1, 1); mma_h(as, 2, 1);
      wgmma_commit();
      bar_arrive(turn_other, 256);
      if (XS0 == 2) load_x(std::integral_constant<int, 3>());
      if (XS0 == 3) { load_x(std::integral_constant<int, 2>()); load_x(std::integral_constant<int, 3>()); }
      full(47);
      bar_sync(turn_me, 256);
      wgmma_fence();
      mma_h(as, 3, 1);
      wgmma_commit();
      mma_h(ak, 1, 0);
      wgmma_commit();
      bar_arrive(turn_other, 256);
      const uint32_t rx = mapa(sb + OFF_RECV + w * 16384 + t * 16, m ^ 1), rb = mapa(BAR(B_XCH + w), m ^ 1);
      mbar_wait(BAR(B_PEER), 0);
      wgmma_wait<1>();
      fence_regs(as);
      CT(6);
#pragma unroll
      for (int i = 0; i < 8; i++) {
        const float* ac = &as[8 * i];
        st_async_v4(rx + i * 2048, rb, pack_bf16(ac[0], ac[1]), pack_bf16(ac[2], ac[3]), pack_bf16(ac[4], ac[5]), pack_bf16(ac[6], ac[7]));
      }
      CT(7);
      bar_sync(turn_me, 256);
      wgmma_fence();
      mma_h(ak, 2, 0); mma_h(ak, 3, 0);
      wgmma_commit();
      if (w == 0) bar_arrive(turn_other, 256);
      op = p.out + row0 * 1024 + eps * 128 + q * 8;
      hpub = hst + eps * 128; hst += q * 256;
      cd = code_of(info.y);
      ast = sb + w * ST_BYTES + (8 * (lane >> 4) + (lane & 7)) * 128 + (((2 * wi + ((lane >> 3) & 1)) ^ swz(lane & 7)) << 4);
      ald = sb + (warp * 16 + g) * 128 + ((q ^ swz(g)) << 4);
      asm volatile("" : "+l"(op), "+l"(hpub), "+l"(hst), "+r"(cd), "+r"(ast), "+r"(ald));
      zr = zero_here();
#pragma unroll
      for (int i = 0; i < 4; i++) { ha[i].x += zr; hb[i].x += zr; asm volatile("" : "+r"(ha[i].x), "+r"(hb[i].x)); }
      ast += (uint32_t)(clock64() >> 32) & zr;
      mbar_wait(BAR(B_XCH + w), 0);
      CT(9);
#pragma unroll
      for (int i = 0; i < 8; i++) { const uint4 v = lds128(sb + OFF_RECV + w * 16384 + t * 16 + i * 2048); hp[4 * i] = v.x; hp[4 * i + 1] = v.y; hp[4 * i + 2] = v.z; hp[4 * i + 3] = v.w; }
      wgmma_wait<0>();
      fence_regs(ak);
      CT(10);
#pragma unroll
      for (int i = 0; i < 32; i++) hp[i] = badd2(pack_bf16(ak[2 * i], ak[2 * i + 1]), hp[i]);
    }
#pragma unroll
    for (int jj = 0; jj < 16; jj += 2) stsm_x4_t(ast + jj * 1024, hp[2 * jj], hp[2 * jj + 1], hp[2 * jj + 2], hp[2 * jj + 3]);
    tag = info.y;
    uint4 v[4];
    auto fetch = [&]() { v[0] = pkt_ld128(hst); v[1] = pkt_ld128(hst + 128); v[2] = pkt_ld128(hst + 8); v[3] = pkt_ld128(hst + 136); };
    float st[6], hf[64];
    {
      float sw[2][4], qa[2][4], qb[2][4];
#pragma unroll
      for (int i = 0; i < 8; i++) { sw[i >> 2][i & 3] = 0.f; qa[i >> 2][i & 3] = 0.f; qb[i >> 2][i & 3] = 0.f; }
      auto half = [&](auto i0, auto i1) {
        uint4 ya[4], yb[4];
#pragma unroll
        for (int i = decltype(i0)::value; i < decltype(i1)::value; i++) {
          const uint32_t ad = (ald ^ ((i & 1) << 6)) + (i >> 1) * ST_BYTES;
          ya[i] = lds128(ad); yb[i] = lds128(ad + 1024);
        }
        if (decltype(i1)::value == 4) fetch();
        sw[0][0] += __uint_as_float((uint32_t)(clock64() >> 32) & zr);
#pragma unroll
        for (int i = decltype(i0)::value; i < decltype(i1)::value; i++) {
          ha[i] = make_uint4(badd2(ha[i].x, ya[i].x), badd2(ha[i].y, ya[i].y), badd2(ha[i].z, ya[i].z), badd2(ha[i].w, ya[i].w));
          hb[i] = make_uint4(badd2(hb[i].x, yb[i].x), badd2(hb[i].y, yb[i].y), badd2(hb[i].z, yb[i].z), badd2(hb[i].w, yb[i].w));
          mma16816(sw[0], ha[i].x, hb[i].x, ha[i].y, hb[i].y, wv[i].x, wv[i].y);
          mma16816(qa[0], ha[i].x, hb[i].x, ha[i].y, hb[i].y, ha[i].x, ha[i].y);
          mma16816(qb[0], ha[i].x, hb[i].x, ha[i].y, hb[i].y, hb[i].x, hb[i].y);
          mma16816(sw[1], ha[i].z, hb[i].z, ha[i].w, hb[i].w, wv[i].z, wv[i].w);
          mma16816(qa[1], ha[i].z, hb[i].z, ha[i].w, hb[i].w, ha[i].z, ha[i].w);
          mma16816(qb[1], ha[i].z, hb[i].z, ha[i].w, hb[i].w, hb[i].z, hb[i].w);
        }
      };
      if (HALF_EARLY) {
        bar_sync(w ? NB_BOTH : NB_W0, w ? 256 : 128);
        if (w == 0) bar_arrive(NB_BOTH, 256); else bar_arrive(NB_W1, 256);
        CT(11);
        half(std::integral_constant<int, 0>(), std::integral_constant<int, 2>());
        if (w == 0) bar_sync(NB_W1, 256);
        half(std::integral_constant<int, 2>(), std::integral_constant<int, 4>());
      } else {
        bar_sync(NB_BOTH, 256);
        CT(11);
        half(std::integral_constant<int, 0>(), std::integral_constant<int, 4>());
      }
      const uint32_t s0 = with_bit(sw[0][0] + sw[1][0], cd), s1 = with_bit((g & 1) ? qa[0][1] + qa[1][1] : qa[0][0] + qa[1][0], cd >> 1), s2 = __float_as_uint(sw[0][1] + sw[1][1]);
      const uint32_t s3 = with_bit(sw[0][2] + sw[1][2], cd), s4 = with_bit((g & 1) ? qb[0][3] + qb[1][3] : qb[0][2] + qb[1][2], cd >> 1), s5 = __float_as_uint(sw[0][3] + sw[1][3]);
      if (q == (g >> 1)) { pkt_st128(hpub, s0, s1, s2, tag); pkt_st128(hpub + 8, s3, s4, s5, tag); }
      CT(12);
      if (PRE_UNPACK) {
#pragma unroll
        for (int i = 0; i < 8; i++) {
          const uint4 h = i < 4 ? ha[i] : hb[i - 4];
          hf[8 * i] = bf_lo(h.x); hf[8 * i + 1] = bf_hi(h.x); hf[8 * i + 2] = bf_lo(h.y); hf[8 * i + 3] = bf_hi(h.y);
          hf[8 * i + 4] = bf_lo(h.z); hf[8 * i + 5] = bf_hi(h.z); hf[8 * i + 6] = bf_lo(h.w); hf[8 * i + 7] = bf_hi(h.w);
        }
        fence_regs(hf);
        op += (uint32_t)(clock64() >> 32) & zr;
      }
      const uint32_t o1 = __shfl_sync(0xffffffffu, s1, (lane & 28) | (g >> 1)), o4 = __shfl_sync(0xffffffffu, s4, (lane & 28) | (g >> 1));
      uint32_t n = 0;
      bool more;
#pragma unroll 1
      do {
        if (2 * q == eps) { v[0] = make_uint4(s0, o1, s2, tag); v[2] = make_uint4(s3, o4, s5, tag); }
        if (2 * q + 1 == eps) { v[1] = make_uint4(s0, o1, s2, tag); v[3] = make_uint4(s3, o4, s5, tag); }
        uint32_t bad = 0;
#pragma unroll
        for (int i = 0; i < 4; i++) { chk(bad, v[i].x, cd); chk(bad, v[i].y, cd >> 1); }
        bad &= 1;
#pragma unroll
        for (int i = 0; i < 4; i++) chk(bad, v[i].w, tag);
        more = !(!__any_sync(0xffffffffu, bad)) && ++n < SPIN_LIMIT;
        if (more) { if (bad) fetch(); }
      } while (more);
      st[0] = no_bit(v[0].x) + no_bit(v[1].x); st[1] = no_bit(v[0].y) + no_bit(v[1].y); st[2] = __uint_as_float(v[0].z) + __uint_as_float(v[1].z);
      st[3] = no_bit(v[2].x) + no_bit(v[3].x); st[4] = no_bit(v[2].y) + no_bit(v[3].y); st[5] = __uint_as_float(v[2].z) + __uint_as_float(v[3].z);
    }
    CT(13);
#pragma unroll
    for (int o = 1; o < 4; o <<= 1) {
#pragma unroll
      for (int i = 0; i < 6; i++) st[i] += __shfl_xor_sync(0xffffffffu, st[i], o);
    }
    float mb[2], inv[2];
#pragma unroll
    for (int i = 0; i < 2; i++) {
      const float mu = st[3 * i] * (1.f / 1024.f);
      mb[i] = bf16r(mu);
      inv[i] = fast_rcp(ref_sd(fmaxf(st[3 * i + 1] * (1.f / 1024.f) - mu * mu, 0.f)));
    }
    {
      const int srow = key_row(info.z);
      auto put_out = [&](bf16* dst, const uint4& h, const float* f, float sc, float of, bool on) {
        auto cvt = [&](uint32_t x, int i) { return PRE_UNPACK ? pack_bf16(fmaf(f[i], sc, of), fmaf(f[i + 1], sc, of)) : pack_bf16(fmaf(bf_lo(x), sc, of), fmaf(bf_hi(x), sc, of)); };
        asm volatile("{\n.reg .pred p;\nsetp.ne.b32 p, %5, 0;\n@p st.global.v4.b32 [%0], {%1, %2, %3, %4};\n}\n"
                     :: "l"(dst), "r"(cvt(h.x, 0)), "r"(cvt(h.y, 2)), "r"(cvt(h.z, 4)), "r"(cvt(h.w, 6)), "r"((int)on) : "memory");
      };
#pragma unroll
      for (int i = 0; i < 4; i++) {
        put_out(op + i * 32, ha[i], hf + 8 * i, 1.f + inv[0], -mb[0] * inv[0], row0 != srow);
        put_out(op + 8192 + i * 32, hb[i], hf + 32 + 8 * i, 1.f + inv[1], -mb[1] * inv[1], row0 + 8 != srow);
      }
    }
    CT(14);
    const uint4 cand = lds128(sb + INFO_CAND);
    uint32_t wkey = zero_here();
#pragma unroll
    for (int i = 0; i < 2; i++) {
      const uint32_t row = row0 + 8 * i, rr = row | (row << 16);
      const bool is_cand = __vcmpeq2(cand.x, rr) | __vcmpeq2(cand.y, rr) | __vcmpeq2(cand.z, rr) | __vcmpeq2(cand.w, rr);
      if (!is_cand) wkey = max(wkey, make_key(bf16r((st[3 * i + 2] - mb[i] * __uint_as_float(info.x)) * inv[i]), row));
    }
    wkey = __reduce_max_sync(0xffffffffu, wkey);
    if (eps == 0 && lane == 0) pkt_st64(&p.sc->key[grp * 8 + warp], wkey, tag);
    const bool beaten = (wkey >> 16) > (info.z >> 16);
    if (__builtin_expect(beaten, 0)) {
      const int br = key_row(wkey);
      if (br == row0 || br == row0 + 8) {
#pragma unroll
        for (int i = 0; i < 4; i++) {
          const uint4 h = br == row0 ? ha[i] : hb[i];
          uint2* dst = &p.sc->hrow[(grp * 8 + warp) * 512 + eps * 64 + i * 16 + q * 4];
          pkt_st128(dst, h.x, tag, h.y, tag); pkt_st128(dst + 2, h.z, tag, h.w, tag);
        }
      }
      __syncwarp();
    }
    uint32_t any;
    asm volatile("{\n.reg .pred p, q;\nsetp.ne.b32 p, %1, 0;\nbarrier.cta.red.or.aligned.pred q, %2, 256, p;\nselp.u32 %0, 1, 0, q;\n}\n" : "=r"(any) : "r"((int)beaten), "n"((int)NB_END) : "memory");
    if (__builtin_expect(any, 0)) slow_path(p, grp, eps, tag, info.z, info.w, SM<float>(INFO_LN), SM<float>(INFO_LN + 4));
  }
}

__global__ void __launch_bounds__(NTHR, 1) occupancy_probe_kernel() {}

typedef CUresult (*EncodeFn)(CUtensorMap*, CUtensorMapDataType, cuuint32_t, void*, const cuuint64_t*, const cuuint64_t*, const cuuint32_t*, const cuuint32_t*,
                             CUtensorMapInterleave, CUtensorMapSwizzle, CUtensorMapL2promotion, CUtensorMapFloatOOBfill);

static void make_tm(EncodeFn enc, CUtensorMap* tm, const void* ptr, uint64_t rows, uint64_t cols, uint32_t brows, uint32_t bcols, bool swz, bool wide) {
  cuuint64_t dims[2] = {cols, rows};
  cuuint64_t strides[1] = {cols * 2};
  cuuint32_t box[2] = {bcols, brows};
  cuuint32_t es[2] = {1, 1};
  enc(tm, CU_TENSOR_MAP_DATA_TYPE_BFLOAT16, 2, const_cast<void*>(ptr), dims, strides, box, es, CU_TENSOR_MAP_INTERLEAVE_NONE,
      swz ? CU_TENSOR_MAP_SWIZZLE_128B : CU_TENSOR_MAP_SWIZZLE_NONE, wide ? CU_TENSOR_MAP_L2_PROMOTION_L2_256B : CU_TENSOR_MAP_L2_PROMOTION_L2_128B, CU_TENSOR_MAP_FLOAT_OOB_FILL_NONE);
}

extern "C" void kernel_launch(void* const* d_in, const int* in_sizes, int n_in, void* d_out, int out_size) {
  (void)in_sizes; (void)n_in; (void)out_size;
  static EncodeFn enc = nullptr;
  static void* abT = nullptr;
  static void* sc = nullptr;
  static int map = 0;
  if (!enc) {
    void* fn = nullptr; cudaDriverEntryPointQueryResult st;
    cudaGetDriverEntryPoint("cuTensorMapEncodeTiled", &fn, cudaEnableDefault, &st);
    enc = (EncodeFn)fn;
    cudaGetSymbolAddress(&abT, g_abT);
    cudaGetSymbolAddress(&sc, g_sc);
    cudaFuncSetAttribute(fnet_moe_kernel<0>, cudaFuncAttributeMaxDynamicSharedMemorySize, SMEM_TOTAL);
    cudaFuncSetAttribute(fnet_moe_kernel<1>, cudaFuncAttributeMaxDynamicSharedMemorySize, SMEM_TOTAL);
    cudaFuncSetAttribute(occupancy_probe_kernel, cudaFuncAttributeMaxDynamicSharedMemorySize, SMEM_TOTAL);
    cudaFuncSetAttribute(occupancy_probe_kernel, cudaFuncAttributeNonPortableClusterSizeAllowed, 1);
    cudaLaunchConfig_t cfg = {};
    cfg.gridDim = dim3(128); cfg.blockDim = dim3(NTHR); cfg.dynamicSmemBytes = SMEM_TOTAL;
    cudaLaunchAttribute at[1];
    at[0].id = cudaLaunchAttributeClusterDimension; at[0].val.clusterDim.x = 16; at[0].val.clusterDim.y = 1; at[0].val.clusterDim.z = 1;
    cfg.attrs = at; cfg.numAttrs = 1;
    int ncl = 0;
    if (cudaOccupancyMaxActiveClusters(&ncl, occupancy_probe_kernel, &cfg) == cudaSuccess && ncl >= 8) map = 1;
    (void)cudaGetLastError();
  }
  Params p;
  const bf16* x = (const bf16*)d_in[0];
  make_tm(enc, &p.tmD0, d_in[3], 1024, 1024, 128, 64, true, true);
  make_tm(enc, &p.tmD1, d_in[4], 1024, 1024, 128, 64, true, true);
  make_tm(enc, &p.tmX, x, 2048, 1024, 256, 64, true, true);
  make_tm(enc, &p.tmAbS, abT, 2048, 2048, 64, 64, true, false);
  make_tm(enc, &p.tmAbL, abT, 2048, 2048, 128, 64, true, false);
  make_tm(enc, &p.tmW0, d_in[1], 2048, 2048, 128, 64, true, true);
  make_tm(enc, &p.tmW1, d_in[2], 2048, 2048, 128, 64, true, true);
  make_tm(enc, &p.tmG, d_in[7], 1024, 3584, 16, 64, false, false);
  make_tm(enc, &p.tmU, d_in[8], 1024, 3584, 16, 64, false, false);
  make_tm(enc, &p.tmDn, d_in[9], 3584, 1024, 8, 256, false, false);
  make_tm(enc, &p.tmY, (char*)sc + offsetof(Scratch, ypart), 4 * NSRC, 512, NSRC, 16, false, false);
  p.x = x; p.Dre = (const bf16*)d_in[3]; p.Dim = (const bf16*)d_in[4];
  p.wr = (const bf16*)d_in[6]; p.wdown = (const bf16*)d_in[9]; p.wgate = (const bf16*)d_in[7]; p.wup = (const bf16*)d_in[8]; p.Wre = (const bf16*)d_in[1]; p.Wim = (const bf16*)d_in[2];
  p.out = (bf16*)d_out; p.sc = (Scratch*)sc;
  if (map == 1) fnet_moe_kernel<1><<<NGRID, NTHR, SMEM_TOTAL>>>(p);
  else fnet_moe_kernel<0><<<NGRID, NTHR, SMEM_TOTAL>>>(p);
}
```

```cpp
#include <cuda.h>
#include <cuda_runtime.h>
#include <cuda_bf16.h>
#include <stdint.h>
#include <stddef.h>
#include <type_traits>

typedef __nv_bfloat16 bf16;

constexpr int NGRID = 132, NTHR = 384;
__device__ __forceinline__ int k_col(int tau, int j) { return (tau * 256 + (j < 4 ? j * 64 : (j - 3) * 256)) & 2047; }
__device__ __forceinline__ int k_next(int c, int j) { return (c + (j < 11 ? 256 : j == 11 ? 576 : (c & 192) == 192 ? 128 : 64)) & 2047; }
constexpr int A_BYTES = 128 * 64 * 2;
constexpr int B_BYTES = 256 * 64 * 2;
constexpr int ST_BYTES = A_BYTES + B_BYTES;
constexpr int OFF_AUX = 4 * ST_BYTES;
constexpr int OFF_BAR = OFF_AUX + 32768;
constexpr int OFF_XS = OFF_BAR + 256;
constexpr int OFF_WR = OFF_XS + 2048;
constexpr int OFF_REM = OFF_WR + 256;
constexpr int OFF_INFO = OFF_REM + 256;
constexpr int SMEM_TOTAL = OFF_INFO + 256;
constexpr int INFO_WSUM = OFF_INFO, INFO_TAG = OFF_INFO + 4, INFO_KEY = OFF_INFO + 8, INFO_CAND = OFF_INFO + 16, INFO_LN = OFF_INFO + 32, INFO_ONES = OFF_INFO + 48, INFO_DS = OFF_INFO + 64, INFO_DS2 = OFF_INFO + 192;
constexpr int OFF_RS = OFF_XS;
constexpr int OFF_WC = OFF_AUX;
constexpr int OFF_EXA = OFF_AUX + 4096;
constexpr int OFF_EXB = OFF_AUX + 6144;
__host__ __device__ constexpr int off_stage(int c) { return c == 1 ? OFF_AUX + 16384 : c * ST_BYTES; }
constexpr int OFF_RECV = A_BYTES;
constexpr int NSRC = 112;
enum { B_FULL = 0,
       B_EMPTY = 4,
       B_ALL = 6,
       B_EP = 8,
       B_AW = 16,
       B_STAT = 24, B_WC = 25, B_CD = 26, B_CH = 27, B_INFO = 28, B_PEER = 29,
       B_XCH = 30,
       B_GUX = (OFF_INFO + 128 - OFF_BAR) / 8,
       B_SD = B_GUX + 1,
       B_E23 = B_GUX + 5 };
enum { NB_TURN0 = 1, NB_TURN1 = 2, NB_BOTH = 3, NB_AUX = 4, NB_H = 5, NB_SEL = 6, NB_END = 7 };

struct Scratch;
struct Params {
  Scratch* sc; const bf16* wr; const bf16* x; const bf16* Dre; const bf16* Dim; const bf16* Wre; const bf16* Wim;
  const bf16* wgate; const bf16* wup; const bf16* wdown; bf16* out;
  CUtensorMap tmX, tmD0, tmD1, tmW0, tmW1, tmAbS, tmAbL, tmG, tmU, tmDn, tmY;
};

__device__ __align__(1024) bf16 g_abT[2048 * 2048];
struct Scratch {
  alignas(128) uint4 xz[2048];
  alignas(128) uint2 dsum[2048];
  alignas(128) uint32_t abflag[128 * 4 * 32];
  alignas(128) uint32_t abdone[128 * 2 * 32];
  alignas(128) uint2 u[4 * 512];
  alignas(128) uint2 cl[128 * 16];
  alignas(128) uint4 cpart[4 * 16 * 512];
  alignas(128) uint2 ch[8 * 512];
  alignas(128) uint4 cs[128 * 8];
  alignas(128) uint4 ypart[4 * NSRC * 64];
  alignas(128) uint4 hstat[16 * 8 * 128];
  alignas(128) uint2 rdone[128];
  alignas(128) uint2 key[128];
  alignas(128) uint2 hrow[128 * 512];
  alignas(128) uint2 fpart[8 * 1024];
  alignas(128) uint32_t epoch;
};
__device__ Scratch g_sc;

#define SPIN_LIMIT (1u << 17)
constexpr uint32_t ST1_CLK = 1400, ST_GAP = 600, U_CLK = 3700, Z_CLK = 9000;
constexpr uint32_t XS_DELAY = 300, CP_DELAY = 1500, CS_DELAY = 800;
constexpr uint32_t PUB_PACE = 1000, UNIT_PACE = 1600, ROW_CLK = 21000;
constexpr int LO_NS = 250, ALL_NS = 400;
__device__ __forceinline__ uint32_t smem_u32(const void* p) { return (uint32_t)__cvta_generic_to_shared(p); }
__device__ __forceinline__ uint32_t clk32() { uint32_t c; asm volatile("mov.u32 %0, %%clock;" : "=r"(c)); return c; }
__device__ __forceinline__ uint32_t zero_here() { uint64_t c; asm volatile("mov.u64 %0, %%clock64;" : "=l"(c) :: "memory"); return (uint32_t)(c >> 32) & blockIdx.y; }
__device__ __forceinline__ uint32_t uniform_zero_here() { uint32_t c; asm volatile("mov.u32 %0, %%clock;" : "=r"(c) :: "memory"); return c & blockIdx.y; }
__device__ __forceinline__ void wait_clk(uint32_t t0, uint32_t dt) {
  asm volatile("{\n.reg .pred p;\n.reg .u32 c;\nLOOP:\nmov.u32 c, %%clock;\nsub.u32 c, c, %0;\nsetp.lt.u32 p, c, %1;\n@p nanosleep.u32 100;\n@p bra LOOP;\n}\n" :: "r"(t0), "r"(dt) : "memory");
}
__device__ __forceinline__ void mbar_init(uint32_t bar, uint32_t cnt) { asm volatile("mbarrier.init.shared::cta.b64 [%0], %1;" :: "r"(bar), "r"(cnt) : "memory"); }
__device__ __forceinline__ void mbar_expect_tx(uint32_t bar, uint32_t bytes) { asm volatile("mbarrier.arrive.expect_tx.shared::cta.b64 _, [%0], %1;" :: "r"(bar), "r"(bytes) : "memory"); }
__device__ __forceinline__ void mbar_arrive(uint32_t bar) { asm volatile("mbarrier.arrive.shared::cta.b64 _, [%0];" :: "r"(bar) : "memory"); }
__device__ __forceinline__ void mbar_arrive_remote(uint32_t cluster_addr) { asm volatile("mbarrier.arrive.shared::cluster.b64 _, [%0];" :: "r"(cluster_addr) : "memory"); }
__device__ __forceinline__ void mbar_wait(uint32_t bar, uint32_t parity) {
  asm volatile("{\n.reg .pred p;\nLOOP:\nmbarrier.try_wait.parity.shared::cta.b64 p, [%0], %1;\n@!p bra LOOP;\n}\n" :: "r"(bar), "r"(parity) : "memory");
}
__device__ __forceinline__ void tma_load_2d(uint32_t dst, const CUtensorMap* tm, uint32_t bar, int c0, int c1) {
  asm volatile("cp.async.bulk.tensor.2d.shared::cluster.global.mbarrier::complete_tx::bytes [%0], [%1, {%3, %4}], [%2];"
    :: "r"(dst), "l"(tm), "r"(bar), "r"(c0), "r"(c1) : "memory");
}
__device__ __forceinline__ void tma_load_2d_hint(uint32_t dst, const CUtensorMap* tm, uint32_t bar, int c0, int c1, uint64_t pol) {
  asm volatile("cp.async.bulk.tensor.2d.shared::cluster.global.mbarrier::complete_tx::bytes.L2::cache_hint [%0], [%1, {%3, %4}], [%2], %5;"
    :: "r"(dst), "l"(tm), "r"(bar), "r"(c0), "r"(c1), "l"(pol) : "memory");
}
__device__ __forceinline__ uint64_t policy_evict_first() { uint64_t p; asm volatile("createpolicy.fractional.L2::evict_first.b64 %0, 1.0;" : "=l"(p)); return p; }
__device__ __forceinline__ void tma_store_2d(const CUtensorMap* tm, uint32_t src, int c0, int c1) {
  asm volatile("cp.async.bulk.tensor.2d.global.shared::cta.bulk_group [%0, {%2, %3}], [%1];" :: "l"(tm), "r"(src), "r"(c0), "r"(c1) : "memory");
}
__device__ __forceinline__ void bulk_load(uint32_t dst, const void* src, uint32_t bytes, uint32_t bar) {
  asm volatile("cp.async.bulk.shared::cluster.global.mbarrier::complete_tx::bytes [%0], [%1], %2, [%3];" :: "r"(dst), "l"(src), "r"(bytes), "r"(bar) : "memory");
}
__device__ __forceinline__ void prefetch_l2(const void* p) { asm volatile("prefetch.global.L2 [%0];" :: "l"(p)); }
__device__ __forceinline__ void bulk_commit() { asm volatile("cp.async.bulk.commit_group;" ::: "memory"); }
__device__ __forceinline__ void bulk_wait_all() { asm volatile("cp.async.bulk.wait_group 0;" ::: "memory"); }
__device__ __forceinline__ void fence_async_smem() { asm volatile("fence.proxy.async.shared::cta;" ::: "memory"); }
__device__ __forceinline__ void wgmma_fence() { asm volatile("wgmma.fence.sync.aligned;" ::: "memory"); }
__device__ __forceinline__ void wgmma_commit() { asm volatile("wgmma.commit_group.sync.aligned;" ::: "memory"); }
template<int N> __device__ __forceinline__ void wgmma_wait() { asm volatile("wgmma.wait_group.sync.aligned %0;" :: "n"(N) : "memory"); }
__device__ __forceinline__ void bar_sync(int id, int n) { asm volatile("bar.sync %0, %1;" :: "r"(id), "r"(n) : "memory"); }
__device__ __forceinline__ void bar_arrive(int id, int n) { asm volatile("bar.arrive %0, %1;" :: "r"(id), "r"(n) : "memory"); }
__device__ __forceinline__ void cluster_wait() { asm volatile("barrier.cluster.wait.aligned;" ::: "memory"); }
template<int R> __device__ __forceinline__ void reg_inc() { asm volatile("setmaxnreg.inc.sync.aligned.u32 %0;" :: "n"(R)); }
template<int R> __device__ __forceinline__ void reg_dec() { asm volatile("setmaxnreg.dec.sync.aligned.u32 %0;" :: "n"(R)); }
__device__ __forceinline__ bool elect_one() {
  uint32_t p;
  asm volatile("{\n.reg .pred q;\nelect.sync _|q, 0xffffffff;\nselp.u32 %0, 1, 0, q;\n}\n" : "=r"(p));
  return p != 0;
}
__device__ __forceinline__ uint32_t mapa(uint32_t addr, uint32_t cta) { uint32_t r; asm volatile("mapa.shared::cluster.u32 %0, %1, %2;" : "=r"(r) : "r"(addr), "r"(cta)); return r; }
__device__ __forceinline__ void st_async_v4(uint32_t addr, uint32_t bar, uint32_t a, uint32_t b, uint32_t c, uint32_t d) {
  asm volatile("st.async.weak.shared::cluster.mbarrier::complete_tx::bytes.v4.b32 [%0], {%2, %3, %4, %5}, [%1];" :: "r"(addr), "r"(bar), "r"(a), "r"(b), "r"(c), "r"(d) : "memory");
}
__device__ __forceinline__ void st_async_b32(uint32_t addr, uint32_t bar, uint32_t a) {
  asm volatile("st.async.weak.shared::cluster.mbarrier::complete_tx::bytes.b32 [%0], %2, [%1];" :: "r"(addr), "r"(bar), "r"(a) : "memory");
}
__device__ __forceinline__ void stsm_x4(uint32_t addr, uint32_t a, uint32_t b, uint32_t c, uint32_t d) {
  asm volatile("stmatrix.sync.aligned.m8n8.x4.shared.b16 [%0], {%1, %2, %3, %4};" :: "r"(addr), "r"(a), "r"(b), "r"(c), "r"(d) : "memory");
}
__device__ __forceinline__ void stsm_x4_t(uint32_t addr, uint32_t a, uint32_t b, uint32_t c, uint32_t d) {
  asm volatile("stmatrix.sync.aligned.m8n8.x4.trans.shared.b16 [%0], {%1, %2, %3, %4};" :: "r"(addr), "r"(a), "r"(b), "r"(c), "r"(d) : "memory");
}
__device__ __forceinline__ uint4 lds128(uint32_t addr) { uint4 v; asm volatile("ld.shared.v4.b32 {%0, %1, %2, %3}, [%4];" : "=r"(v.x), "=r"(v.y), "=r"(v.z), "=r"(v.w) : "r"(addr) : "memory"); return v; }
extern __shared__ __align__(1024) uint8_t smem_raw[];
template<class T> __device__ __forceinline__ T& SM(int off) { return *reinterpret_cast<T*>(smem_raw + off); }
__device__ __forceinline__ uint4 ldg_nc128(const void* p) { uint4 v; asm volatile("ld.global.nc.v4.b32 {%0, %1, %2, %3}, [%4];" : "=r"(v.x), "=r"(v.y), "=r"(v.z), "=r"(v.w) : "l"(p)); return v; }
__device__ __forceinline__ uint4 ldg128(const void* p) { uint4 v; asm volatile("ld.global.L1::no_allocate.v4.b32 {%0, %1, %2, %3}, [%4];" : "=r"(v.x), "=r"(v.y), "=r"(v.z), "=r"(v.w) : "l"(p) : "memory"); return v; }
__device__ __forceinline__ void pkt_st128(void* p, uint32_t a, uint32_t b, uint32_t c, uint32_t d) {
  asm volatile("{\n.reg .b128 v;\n.reg .b64 lo, hi;\nmov.b64 lo, {%1, %2};\nmov.b64 hi, {%3, %4};\nmov.b128 v, {lo, hi};\nst.relaxed.gpu.global.b128 [%0], v;\n}\n"
    :: "l"(p), "r"(a), "r"(b), "r"(c), "r"(d) : "memory");
}
__device__ __forceinline__ uint4 pkt_ld128(const void* p) {
  uint4 r;
  asm volatile("{\n.reg .b128 v;\n.reg .b64 lo, hi;\nld.relaxed.gpu.global.b128 v, [%4];\nmov.b128 {lo, hi}, v;\nmov.b64 {%0, %1}, lo;\nmov.b64 {%2, %3}, hi;\n}\n"
    : "=r"(r.x), "=r"(r.y), "=r"(r.z), "=r"(r.w) : "l"(p) : "memory");
  return r;
}
__device__ __forceinline__ void pkt_st64(void* p, uint32_t a, uint32_t b) {
  asm volatile("{\n.reg .b64 v;\nmov.b64 v, {%1, %2};\nst.relaxed.gpu.global.b64 [%0], v;\n}\n" :: "l"(p), "r"(a), "r"(b) : "memory");
}
__device__ __forceinline__ uint2 pkt_ld64(const void* p) {
  uint2 r;
  asm volatile("{\n.reg .b64 v;\nld.relaxed.gpu.global.b64 v, [%2];\nmov.b64 {%0, %1}, v;\n}\n" : "=r"(r.x), "=r"(r.y) : "l"(p) : "memory");
  return r;
}
__device__ __forceinline__ uint32_t ld_relaxed32(const void* p) { uint32_t v; asm volatile("ld.relaxed.gpu.global.b32 %0, [%1];" : "=r"(v) : "l"(p) : "memory"); return v; }
__device__ __forceinline__ uint32_t ld_acquire32(const void* p) { uint32_t v; asm volatile("ld.acquire.gpu.global.b32 %0, [%1];" : "=r"(v) : "l"(p) : "memory"); return v; }
__device__ __forceinline__ void st_relaxed32(void* p, uint32_t v) { asm volatile("st.relaxed.gpu.global.b32 [%0], %1;" :: "l"(p), "r"(v) : "memory"); }
__device__ __forceinline__ uint32_t poll64(const void* p, uint32_t tag, int ns) {
  uint2 v; uint32_t n = 0;
  bool more;
#pragma unroll 1
  do {
    v = pkt_ld64(p);
    more = v.y != tag && ++n < SPIN_LIMIT;
    if (more) { __nanosleep(ns); }
  } while (more);
  return v.x;
}
__device__ __forceinline__ uint32_t poll64_warp(const void* p, uint32_t tag, int ns) {
  uint2 v; uint32_t n = 0;
  bool more;
#pragma unroll 1
  do {
    v = pkt_ld64(p);
    more = !(__all_sync(0xffffffffu, v.y == tag)) && ++n < SPIN_LIMIT;
    if (more) { __nanosleep(ns); }
  } while (more);
  return v.x;
}
__device__ __forceinline__ uint32_t code_of(uint32_t tag) { return tag % 3u + 1u; }
__device__ __forceinline__ uint32_t with_bit(uint32_t v, uint32_t bit) { return (v & ~1u) | (bit & 1u); }
__device__ __forceinline__ uint32_t with_bit(float v, uint32_t bit) { return with_bit(__float_as_uint(v), bit); }
__device__ __forceinline__ float no_bit(uint32_t v) { return __uint_as_float(v & ~1u); }
__device__ __forceinline__ void chk(uint32_t& bad, uint32_t a, uint32_t want) { bad |= a ^ want; asm("" : "+r"(bad)); }
__device__ __forceinline__ void chk_code(uint32_t& bad, const uint4& v, uint32_t c0, uint32_t c1) { chk(bad, v.x, c0); chk(bad, v.y, c1); chk(bad, v.z, c0); chk(bad, v.w, c1); }
__device__ __forceinline__ uint32_t pack_bf16(float lo, float hi) { uint32_t r; asm("cvt.rn.bf16x2.f32 %0, %1, %2;" : "=r"(r) : "f"(hi), "f"(lo)); return r; }
__device__ __forceinline__ float bf_lo(uint32_t v) { return __uint_as_float(v << 16); }
__device__ __forceinline__ float bf_hi(uint32_t v) { return __uint_as_float(v & 0xFFFF0000u); }
__device__ __forceinline__ float bf16r(float x) { return __uint_as_float(pack_bf16(0.f, x)); }
__device__ __forceinline__ void st_bf16(bf16* p, float x) { *reinterpret_cast<uint16_t*>(p) = (uint16_t)pack_bf16(x, 0.f); }
__device__ __forceinline__ float fast_rcp(float x) { float r; asm("rcp.approx.ftz.f32 %0, %1;" : "=f"(r) : "f"(x)); return r; }
__device__ __forceinline__ float ldbf(const bf16* p) { return __bfloat162float(*p); }
__device__ __forceinline__ uint32_t badd2(uint32_t a, uint32_t b) { uint32_t r; asm("add.rn.bf16x2 %0, %1, %2;" : "=r"(r) : "r"(a), "r"(b)); return r; }
__device__ __forceinline__ uint32_t bfma2(uint32_t a, uint32_t b, uint32_t c) { uint32_t r; asm("fma.rn.bf16x2 %0, %1, %2, %3;" : "=r"(r) : "r"(a), "r"(b), "r"(c)); return r; }
__device__ __forceinline__ float warp_sum(float v) {
#pragma unroll
  for (int o = 16; o > 0; o >>= 1) v += __shfl_xor_sync(0xffffffffu, v, o);
  return v;
}
template<int N> __device__ __forceinline__ void fold(float* v, int o, int lane) {
  const bool up = lane & o;
#pragma unroll
  for (int i = 0; i < N / 2; i++) {
    const float keep = up ? v[N / 2 + i] : v[i], send = up ? v[i] : v[N / 2 + i];
    v[i] = keep + __shfl_xor_sync(0xffffffffu, send, o);
  }
}
__device__ __forceinline__ uint32_t make_key(float r_bf, int row) {
  const uint32_t u = __float_as_uint(r_bf);
  return (((u & 0x80000000u) ? ~u : (u | 0x80000000u)) & 0xFFFF0000u) | (0xFFFFu - (uint32_t)row);
}
__device__ __forceinline__ int key_row(uint32_t key) { return (0xFFFF - (int)(key & 0xFFFFu)) & 2047; }
__device__ __forceinline__ float key_val(uint32_t key) { const uint32_t o = key & 0xFFFF0000u; return __uint_as_float((o & 0x80000000u) ? (o & 0x7FFFFFFFu) : (~o & 0xFFFF0000u)); }
__device__ __forceinline__ float ref_sd(float var) { float r; asm("sqrt.approx.ftz.f32 %0, %1;" : "=f"(r) : "f"(bf16r(bf16r(var) + 1e-5f))); return bf16r(r); }
__device__ __forceinline__ uint64_t make_desc(uint32_t addr) { return (uint64_t)((addr & 0x3FFFF) >> 4) | ((uint64_t)64 << 32) | ((uint64_t)1 << 62); }
__device__ __forceinline__ uint64_t make_desc_noswz(uint32_t addr) { return (uint64_t)((addr & 0x3FFFF) >> 4) | ((uint64_t)8 << 32); }
#define ACC8(d, o) "+f"(d[o]), "+f"(d[o + 1]), "+f"(d[o + 2]), "+f"(d[o + 3]), "+f"(d[o + 4]), "+f"(d[o + 5]), "+f"(d[o + 6]), "+f"(d[o + 7])
#define ACC64(d, o) ACC8(d, o), ACC8(d, o + 8), ACC8(d, o + 16), ACC8(d, o + 24), ACC8(d, o + 32), ACC8(d, o + 40), ACC8(d, o + 48), ACC8(d, o + 56)
#define REGS64 "%0, %1, %2, %3, %4, %5, %6, %7, %8, %9, %10, %11, %12, %13, %14, %15, %16, %17, %18, %19, %20, %21, %22, %23, %24, %25, %26, %27, %28, %29, %30, %31, " \
    "%32, %33, %34, %35, %36, %37, %38, %39, %40, %41, %42, %43, %44, %45, %46, %47, %48, %49, %50, %51, %52, %53, %54, %55, %56, %57, %58, %59, %60, %61, %62, %63"
#define REGS128 REGS64 ", %64, %65, %66, %67, %68, %69, %70, %71, %72, %73, %74, %75, %76, %77, %78, %79, %80, %81, %82, %83, %84, %85, %86, %87, %88, %89, %90, %91, %92, %93, %94, %95, " \
    "%96, %97, %98, %99, %100, %101, %102, %103, %104, %105, %106, %107, %108, %109, %110, %111, %112, %113, %114, %115, %116, %117, %118, %119, %120, %121, %122, %123, %124, %125, %126, %127"
__device__ __forceinline__ void wgmma_n256(float (&d)[128], uint64_t da, uint64_t db) {
  asm volatile("wgmma.mma_async.sync.aligned.m64n256k16.f32.bf16.bf16 {" REGS128 "}, %128, %129, 1, 1, 1, 0, 0;\n"
    : ACC64(d, 0), ACC64(d, 64) : "l"(da), "l"(db));
}
#define OUT8(d, o) "=f"(d[o]), "=f"(d[o + 1]), "=f"(d[o + 2]), "=f"(d[o + 3]), "=f"(d[o + 4]), "=f"(d[o + 5]), "=f"(d[o + 6]), "=f"(d[o + 7])
#define OUT64(d, o) OUT8(d, o), OUT8(d, o + 8), OUT8(d, o + 16), OUT8(d, o + 24), OUT8(d, o + 32), OUT8(d, o + 40), OUT8(d, o + 48), OUT8(d, o + 56)
__device__ __forceinline__ void wgmma_n256_rs_init(float (&d)[128], const uint32_t* a, uint64_t db) {
  asm volatile("wgmma.mma_async.sync.aligned.m64n256k16.f32.bf16.bf16 {" REGS128 "}, {%128, %129, %130, %131}, %132, 0, 1, 1, 0;\n"
    : OUT64(d, 0), OUT64(d, 64) : "r"(a[0]), "r"(a[1]), "r"(a[2]), "r"(a[3]), "l"(db));
}
__device__ __forceinline__ void wgmma_n256_rs(float (&d)[128], const uint32_t* a, uint64_t db) {
  asm volatile("wgmma.mma_async.sync.aligned.m64n256k16.f32.bf16.bf16 {" REGS128 "}, {%128, %129, %130, %131}, %132, 1, 1, 1, 0;\n"
    : ACC64(d, 0), ACC64(d, 64) : "r"(a[0]), "r"(a[1]), "r"(a[2]), "r"(a[3]), "l"(db));
}
template<int ACCUM> __device__ __forceinline__ void wgmma_n8_rs(float (&d)[4], const uint32_t* a, uint64_t db) {
  asm volatile("wgmma.mma_async.sync.aligned.m64n8k16.f32.bf16.bf16 {%0, %1, %2, %3}, {%4, %5, %6, %7}, %8, %9, 1, 1, 0;\n"
    : "+f"(d[0]), "+f"(d[1]), "+f"(d[2]), "+f"(d[3]) : "r"(a[0]), "r"(a[1]), "r"(a[2]), "r"(a[3]), "l"(db), "n"(ACCUM));
}
__device__ __forceinline__ void wgmma_n8(float (&d)[4], uint64_t da, uint64_t db) {
  asm volatile("wgmma.mma_async.sync.aligned.m64n8k16.f32.bf16.bf16 {%0, %1, %2, %3}, %4, %5, 1, 1, 1, 0, 0;\n"
    : "+f"(d[0]), "+f"(d[1]), "+f"(d[2]), "+f"(d[3]) : "l"(da), "l"(db));
}
__device__ __forceinline__ void wgmma_n128(float (&d)[64], uint64_t da, uint64_t db) {
  asm volatile("wgmma.mma_async.sync.aligned.m64n128k16.f32.bf16.bf16 {" REGS64 "}, %64, %65, 1, 1, 1, 0, 0;\n" : ACC64(d, 0) : "l"(da), "l"(db));
}
#define ACC32(d, o) ACC8(d, o), ACC8(d, o + 8), ACC8(d, o + 16), ACC8(d, o + 24)
#define REGS32 "%0, %1, %2, %3, %4, %5, %6, %7, %8, %9, %10, %11, %12, %13, %14, %15, %16, %17, %18, %19, %20, %21, %22, %23, %24, %25, %26, %27, %28, %29, %30, %31"
#define REGS96 REGS64 ", %64, %65, %66, %67, %68, %69, %70, %71, %72, %73, %74, %75, %76, %77, %78, %79, %80, %81, %82, %83, %84, %85, %86, %87, %88, %89, %90, %91, %92, %93, %94, %95"
__device__ __forceinline__ void wgmma_part(float (&d)[32], uint64_t da, uint64_t db) {
  asm volatile("wgmma.mma_async.sync.aligned.m64n64k16.f32.bf16.bf16 {" REGS32 "}, %32, %33, 1, 1, 1, 0, 0;\n" : ACC32(d, 0) : "l"(da), "l"(db));
}
__device__ __forceinline__ void wgmma_part(float (&d)[96], uint64_t da, uint64_t db) {
  asm volatile("wgmma.mma_async.sync.aligned.m64n192k16.f32.bf16.bf16 {" REGS96 "}, %96, %97, 1, 1, 1, 0, 0;\n" : ACC64(d, 0), ACC32(d, 64) : "l"(da), "l"(db));
}
template<int N> __device__ __forceinline__ void fence_regs(float (&d)[N]) {
#pragma unroll
  for (int i = 0; i < N; i++) asm volatile("" : "+f"(d[i]) :: "memory");
}
__device__ __forceinline__ void mma16816(float (&c)[4], uint32_t a0, uint32_t a1, uint32_t a2, uint32_t a3, uint32_t b0, uint32_t b1) {
  asm volatile("mma.sync.aligned.m16n8k16.row.col.f32.bf16.bf16.f32 {%0, %1, %2, %3}, {%4, %5, %6, %7}, {%8, %9}, {%0, %1, %2, %3};"
               : "+f"(c[0]), "+f"(c[1]), "+f"(c[2]), "+f"(c[3]) : "r"(a0), "r"(a1), "r"(a2), "r"(a3), "r"(b0), "r"(b1));
}
__device__ __forceinline__ void fma8(float* acc, const uint4& v, float x) {
  acc[0] = fmaf(bf_lo(v.x), x, acc[0]); acc[1] = fmaf(bf_hi(v.x), x, acc[1]); acc[2] = fmaf(bf_lo(v.y), x, acc[2]); acc[3] = fmaf(bf_hi(v.y), x, acc[3]);
  acc[4] = fmaf(bf_lo(v.z), x, acc[4]); acc[5] = fmaf(bf_hi(v.z), x, acc[5]); acc[6] = fmaf(bf_lo(v.w), x, acc[6]); acc[7] = fmaf(bf_hi(v.w), x, acc[7]);
}
template<int PITCH> __device__ __forceinline__ void gemv8x8(float (&acc)[8], uint32_t addr, const float (&x)[8]) {
  uint4 v[2][2];
  v[0][0] = lds128(addr); v[0][1] = lds128(addr + PITCH);
#pragma unroll
  for (int b = 0; b < 4; b++) {
    if (b < 3) { v[(b + 1) & 1][0] = lds128(addr + (2 * b + 2) * PITCH); v[(b + 1) & 1][1] = lds128(addr + (2 * b + 3) * PITCH); }
    acc[0] += __uint_as_float(zero_here());
#pragma unroll
    for (int c = 0; c < 4; c++) {
      if (c == 2) acc[4] += __uint_as_float(zero_here());
#pragma unroll
      for (int r = 0; r < 2; r++) {
        const uint4& q = v[b & 1][r];
        const uint32_t u = c == 0 ? q.x : c == 1 ? q.y : c == 2 ? q.z : q.w;
        acc[2 * c] = fmaf(bf_lo(u), x[2 * b + r], acc[2 * c]); acc[2 * c + 1] = fmaf(bf_hi(u), x[2 * b + r], acc[2 * c + 1]);
      }
    }
  }
}
__device__ __forceinline__ float swiglu(float g, float u) {
  g = bf16r(g); u = bf16r(u);
  return bf16r(bf16r(g * fast_rcp(1.f + __expf(-g))) * u);
}

#define CT(slot) do {} while (0)
#define TIM(slot) do {} while (0)

constexpr int H_BUF0 = 0, H_BUF1 = 16384, H_RED = 32768, H_KEYS = H_RED + 1024, H_ROW = H_KEYS + 1024, H_ACT = H_ROW + 8192, H_PART = H_ACT + 4096;
__device__ __forceinline__ void hsync() { bar_sync(NB_H, 256); }
template<int N> __device__ __forceinline__ void block_sum(float (&v)[N], int warp, int lane) {
#pragma unroll
  for (int i = 0; i < N; i++) v[i] = warp_sum(v[i]);
  hsync();
  if (lane == 0) {
#pragma unroll
    for (int i = 0; i < N; i++) SM<float>(H_RED + (i * 8 + warp) * 4) = v[i];
  }
  hsync();
#pragma unroll
  for (int i = 0; i < N; i++) {
    const float4 a = SM<float4>(H_RED + i * 32), b = SM<float4>(H_RED + i * 32 + 16);
    v[i] = ((a.x + a.y) + (a.z + a.w)) + ((b.x + b.y) + (b.z + b.w));
  }
}
__device__ __forceinline__ void fft_first(int j, float2 v0, float2 v1, float2 v2, float2 v3) {
  const float2 a = make_float2(v0.x + v2.x, v0.y + v2.y), b = make_float2(v0.x - v2.x, v0.y - v2.y);
  const float2 c = make_float2(v1.x + v3.x, v1.y + v3.y), d = make_float2(v1.y - v3.y, v3.x - v1.x);
  SM<float4>(H_BUF1 + j * 32) = make_float4(a.x + c.x, a.y + c.y, b.x + d.x, b.y + d.y);
  SM<float4>(H_BUF1 + j * 32 + 16) = make_float4(a.x - c.x, a.y - c.y, b.x - d.x, b.y - d.y);
}
template<int NB> __device__ __forceinline__ void fft_passes(int tid) {
  constexpr int q = 256 * NB;
#pragma unroll 1
  for (int ps = 1; ps < 5; ps++) {
    const int ns = 1 << (2 * ps), k = tid & (ns - 1);
    float s1, c1;
    __sincosf(-1.57079632679f * __fdividef((float)k, (float)ns), &s1, &c1);
    const float c2 = c1 * c1 - s1 * s1, s2 = 2.f * c1 * s1, c3 = c1 * c2 - s1 * s2, s3 = c1 * s2 + s1 * c2;
    hsync();
#pragma unroll
    for (int i = 0; i < NB; i++) {
      const int j = tid + 256 * i;
      const float2* in = &SM<float2>((ps & 1) ? H_BUF1 : H_BUF0);
      float2* o = &SM<float2>((ps & 1) ? H_BUF0 : H_BUF1) + (j - k) * 4 + k;
      const float2 v0 = in[j], x1 = in[j + q], x2 = in[j + 2 * q], x3 = in[j + 3 * q];
      const float2 v1 = make_float2(x1.x * c1 - x1.y * s1, x1.x * s1 + x1.y * c1);
      const float2 v2 = make_float2(x2.x * c2 - x2.y * s2, x2.x * s2 + x2.y * c2);
      const float2 v3 = make_float2(x3.x * c3 - x3.y * s3, x3.x * s3 + x3.y * c3);
      const float2 a = make_float2(v0.x + v2.x, v0.y + v2.y), b = make_float2(v0.x - v2.x, v0.y - v2.y);
      const float2 c = make_float2(v1.x + v3.x, v1.y + v3.y), d = make_float2(v1.y - v3.y, v3.x - v1.x);
      o[0] = make_float2(a.x + c.x, a.y + c.y); o[ns] = make_float2(b.x + d.x, b.y + d.y);
      o[2 * ns] = make_float2(a.x - c.x, a.y - c.y); o[3 * ns] = make_float2(b.x - d.x, b.y - d.y);
    }
  }
  hsync();
}
template<int NR> __device__ __forceinline__ void ln_rows(const float (&h)[NR][4], float (&hn)[NR][4], int warp, int lane) {
  float s[NR], q[NR];
#pragma unroll
  for (int i = 0; i < NR; i++) s[i] = (h[i][0] + h[i][1]) + (h[i][2] + h[i][3]);
  block_sum(s, warp, lane);
#pragma unroll
  for (int i = 0; i < NR; i++) {
    s[i] *= 1.f / 1024.f; q[i] = 0.f;
#pragma unroll
    for (int z = 0; z < 4; z++) q[i] = fmaf(h[i][z] - s[i], h[i][z] - s[i], q[i]);
  }
  block_sum(q, warp, lane);
#pragma unroll
  for (int i = 0; i < NR; i++) {
    const float mb = bf16r(s[i]), inv = fast_rcp(ref_sd(q[i] * (1.f / 1024.f)));
#pragma unroll
    for (int z = 0; z < 4; z++) hn[i][z] = bf16r(bf16r(h[i][z] - mb) * inv);
  }
}
__device__ __forceinline__ float sigmoid_bf(float r) { return bf16r(fast_rcp(1.f + __expf(-r))); }
__device__ __forceinline__ float routed_out(float h, float hn, float y, float sig) { return h + bf16r(hn + bf16r(bf16r(y) * sig)); }

__device__ __forceinline__ void helper_cta(const Params& p, const int hi, const uint32_t t_entry) {
  const int tid = threadIdx.x, warp = tid >> 5, lane = tid & 31;
  const float w0 = ldbf(p.wr + tid), w1 = ldbf(p.wr + tid + 256), w2 = ldbf(p.wr + tid + 512), w3 = ldbf(p.wr + tid + 768), wf = ldbf(p.wr);
  const uint32_t tag = ld_relaxed32(&p.sc->epoch) + 1;
  fft_first(tid, make_float2(w0, 0.f), make_float2(w1, 0.f), make_float2(w2, 0.f), make_float2(w3, 0.f));
  fft_passes<1>(tid);
  const uint32_t c0 = code_of(tag), c1 = c0 >> 1;
  {
    const float off = wf - SM<float>(H_BUF1) * (1.f / 1024.f);
    const float4 v = SM<float4>(H_BUF1 + tid * 32), u = SM<float4>(H_BUF1 + tid * 32 + 16);
    pkt_st128(&p.sc->u[hi * 512 + ((tid & 192) + (tid & 1) * 32 + ((tid >> 1) & 31)) * 2], with_bit(pack_bf16((tid ? v.x : 0.f) - off, v.z - off), c0), with_bit(pack_bf16(v.y, v.w), c1),
              with_bit(pack_bf16(u.x - off, u.z - off), c0), with_bit(pack_bf16(u.y, u.w), c1));
    hsync();
  }
  if (tid == 0) TIM(0);
  {
    float tw[8];
#pragma unroll
    for (int i = 0; i < 4; i++) __sincosf((float)(tid + 256 * i) * (-6.28318530718f / 2048.f), &tw[2 * i], &tw[2 * i + 1]);
    wait_clk(t_entry, Z_CLK);
    uint2 z[8]; uint32_t n = 0;
    bool more;
#pragma unroll 1
    do {
      uint32_t bad = 0;
#pragma unroll
      for (int i = 0; i < 8; i++) z[i] = pkt_ld64(reinterpret_cast<const uint2*>(&p.sc->xz[tid]) + 512 * i + 1);
#pragma unroll
      for (int i = 0; i < 8; i++) chk(bad, z[i].y, tag);
      more = bad && ++n < SPIN_LIMIT;
      if (more) { __nanosleep(150); }
    } while (more);
#pragma unroll
    for (int i = 0; i < 2; i++)
      fft_first(tid + 256 * i, make_float2(bf_lo(z[i].x), bf_hi(z[i].x)), make_float2(bf_lo(z[i + 2].x), bf_hi(z[i + 2].x)),
                make_float2(bf_lo(z[i + 4].x), bf_hi(z[i + 4].x)), make_float2(bf_lo(z[i + 6].x), bf_hi(z[i + 6].x)));
    if (tid == 0) TIM(7);
    fft_passes<2>(tid);
    if (tid == 0) TIM(1);
    uint32_t k8[8];
#pragma unroll
    for (int i = 0; i < 4; i++) {
      const int k = tid + 256 * i;
      const float2 v0 = SM<float2>(H_BUF1 + k * 8), v1 = SM<float2>(H_BUF1 + (k + 1024) * 8);
      const float w = v1.x * tw[2 * i + 1] - v1.y * tw[2 * i];
      const uint32_t a = __float_as_uint(v0.x + w), b = __float_as_uint(v0.x - w);
      k8[2 * i] = (((a & 0x80000000u) ? ~a : (a | 0x80000000u)) & ~2047u) | k;
      k8[2 * i + 1] = (((b & 0x80000000u) ? ~b : (b | 0x80000000u)) & ~2047u) | (k + 1024);
    }
    uint32_t lim = 0xFFFFFFFFu;
#pragma unroll 1
    for (int r = 0; r < 4; r++) {
      uint32_t mx = 0;
#pragma unroll
      for (int i = 0; i < 8; i++) mx = max(mx, k8[i] <= lim ? k8[i] : 0u);
      mx = __reduce_max_sync(0xffffffffu, mx);
      if (lane == 0) SM<uint32_t>(H_KEYS + (warp * 4 + r) * 4) = mx;
      lim = mx - 1;
    }
    hsync();
    if (tid < 32) {
      const uint32_t me = SM<uint32_t>(H_KEYS + tid * 4);
      int rank = 0;
#pragma unroll
      for (int i = 0; i < 8; i++) { const uint4 o = SM<uint4>(H_KEYS + i * 16); rank += (o.x > me) + (o.y > me) + (o.z > me) + (o.w > me); }
      if (rank < 8) SM<uint16_t>(H_KEYS + 256 + rank * 2) = me & 2047u;
    }
    hsync();
    if (tid >= 128) pkt_st64(&p.sc->cl[(hi * 32 + ((tid - 128) >> 2)) * 16 + (tid & 3)], SM<uint32_t>(H_KEYS + 256 + (tid & 3) * 4), tag);
  }
  const uint32_t cpair = SM<uint32_t>(H_KEYS + 256 + hi * 4);
  const int ca = cpair & 2047, cb = (cpair >> 16) & 2047;
  if (tid < 128) prefetch_l2(((tid & 32) ? p.Wim : p.Wre) + (size_t)((tid & 64) ? cb : ca) * 2048 + lane * 64);
  if (tid == 0) TIM(2);
}

__device__ __forceinline__ void slow_path(const Params& p, int grp, int eps, uint32_t tag, uint32_t key, int win, float mb, float inv) {
  const int tid = threadIdx.x + zero_here(), warp = tid >> 5, lane = tid & 31;
  uint32_t best = __reduce_max_sync(0xffffffffu, poll64(&p.sc->key[tid & 127], tag, 200));
  if (lane == 0) SM<uint32_t>(H_KEYS + warp * 4) = best;
  hsync();
  { const uint4 b4 = SM<uint4>(H_KEYS); best = max(max(b4.x, b4.y), max(b4.z, b4.w)); }
  const int tw = key_row(best), col = eps * 128 + (tid & 127);
  if ((tw >> 7) != grp) return;
  poll64(&p.sc->rdone[col >> 3], tag, 100);
  const uint32_t h0 = poll64(&p.sc->hrow[(tw >> 4) * 512 + 2 * tid], tag, 100), h1 = poll64(&p.sc->hrow[(tw >> 4) * 512 + 2 * tid + 1], tag, 100);
  float h[1][4] = {{bf_lo(h0), bf_hi(h0), bf_lo(h1), bf_hi(h1)}}, hn[1][4];
  ln_rows<1>(h, hn, warp, lane);
  SM<float4>(H_ROW + tid * 16) = make_float4(hn[0][0], hn[0][1], hn[0][2], hn[0][3]);
  SM<float4>(H_ROW + 4096 + tid * 16) = make_float4(h[0][0], h[0][1], h[0][2], h[0][3]);
  hsync();
#pragma unroll 1
  for (int ph = 0; ph < 2; ph++) {
    const int part = min(tid / 56, 3), fh = tid >> 7, len = ph ? 224 : 512, ld = ph ? 1024 : 3584;
    const bf16* wp = ph ? p.wdown + (eps * 448 + fh * 224) * 1024 + (tid & 127) * 8
                        : ((part & 1) ? p.wup : p.wgate) + (part >> 1) * 512 * 3584 + eps * 448 + min(tid - part * 56, 55) * 8;
    const int xo = ph ? H_ACT + fh * 224 * 4 : H_ROW + (part >> 1) * 2048;
    float acc[8] = {0.f, 0.f, 0.f, 0.f, 0.f, 0.f, 0.f, 0.f};
#pragma unroll 16
    for (int d = 0; d < (len & ~15); d++) fma8(acc, ldg_nc128(wp + d * ld), SM<float>(xo + d * 4));
    SM<float4>(H_PART + tid * 32) = make_float4(acc[0], acc[1], acc[2], acc[3]);
    SM<float4>(H_PART + tid * 32 + 16) = make_float4(acc[4], acc[5], acc[6], acc[7]);
    hsync();
    if (ph) break;
#pragma unroll 1
    for (int f = tid; f < 448; f += 256)
      SM<float>(H_ACT + f * 4) = swiglu(SM<float>(H_PART + f * 4) + SM<float>(H_PART + (896 + f) * 4), SM<float>(H_PART + (448 + f) * 4) + SM<float>(H_PART + (1344 + f) * 4));
    hsync();
  }
#pragma unroll 1
  for (int e = tid; e < 1024; e += 256) pkt_st64(&p.sc->fpart[eps * 1024 + e], __float_as_uint(SM<float>(H_PART + e * 4) + SM<float>(H_PART + (1024 + e) * 4)), tag);
  if (tid < 128) {
    float y = 0.f;
#pragma unroll 1
    for (int q = 0; q < 8; q++) y += __uint_as_float(poll64(&p.sc->fpart[q * 1024 + col], tag, 200));
    st_bf16(p.out + tw * 1024 + col, routed_out(SM<float>(H_ROW + 4096 + col * 4), SM<float>(H_ROW + col * 4), y, sigmoid_bf(key_val(best))));
    const uint32_t a = poll64(&p.sc->ch[win * 512 + (col >> 4) * 8 + (col & 7)], tag, 100);
    const float hc = (col & 8) ? bf_hi(a) : bf_lo(a);
    st_bf16(p.out + key_row(key) * 1024 + col, hc + bf16r(bf16r(hc - mb) * inv));
  }
}

template<int MAP>
__global__ void __cluster_dims__(2, 1, 1) __launch_bounds__(NTHR, 1)
fnet_moe_kernel(const __grid_constant__ Params p) {
  const uint32_t t_entry = clk32();
  uint32_t smid;
  asm("mov.u32 %0, %%smid;" : "=r"(smid));
  const int tpc = smid >> 1, m = blockIdx.x & 1;
  if (MAP == 1 ? tpc >= 64 : (tpc >> 1) == 30) {
    if (threadIdx.x < 256) helper_cta(p, (tpc & 1) * 2 + m, t_entry);
    return;
  }
  const uint32_t sb = smem_u32(smem_raw);
  const int tid = threadIdx.x, lane = tid & 31;
  const int e7 = ((tpc - 32) * 37) >> 8;
  const int tau = MAP == 1 || tpc < 32 ? (tpc & 7) : (tpc < 60 ? tpc - 31 - 7 * e7 : 0);
  const int eps = MAP == 1 || tpc < 32 ? (tpc >> 3) : (tpc < 60 ? 4 + e7 : tpc - 58);
  const int cid = tau * 16 + eps * 2 + m;
  auto BAR = [&](int i) { return sb + OFF_BAR + 8 * i; };
  const CUtensorMap* tmD = &p.tmD0 + m;

  if ((tid >> 5) == 4) {
    if (elect_one()) {
      mbar_init(BAR(B_FULL), 1);
      asm volatile("fence.mbarrier_init.release.cluster;" ::: "memory");
      mbar_expect_tx(BAR(B_FULL), ST_BYTES);
      tma_load_2d(sb, tmD, BAR(B_FULL), 0, eps * 128);
      tma_load_2d(sb + A_BYTES, &p.tmX, BAR(B_FULL), 0, tau * 256);
      TIM(0);
    }
  } else if (tid < 192) {
    const int wv = __shfl_sync(0xffffffffu, tid >> 5, 0);
    if (elect_one()) {
      const uint32_t b0 = BAR(wv < 4 ? 8 * wv : B_GUX);
#pragma unroll
      for (int i = 0; i < 8; i++)
        if (i || wv) mbar_init(b0 + 8 * i, wv == 1 || (wv == 3 && i == B_STAT - 24) ? 4 : wv == 3 && i == B_CD - 24 ? 2 : 1);
      asm volatile("fence.mbarrier_init.release.cluster;" ::: "memory");
      if (wv == 3) { mbar_expect_tx(BAR(B_XCH), 16384); mbar_expect_tx(BAR(B_XCH + 1), 16384); }
      if (wv == 5) mbar_expect_tx(BAR(B_GUX), 256);
    }
  }
  const int warp = __shfl_sync(0xffffffffu, tid >> 5, 0);
  __syncthreads();
  asm volatile("barrier.cluster.arrive.relaxed.aligned;" ::: "memory");

  if (warp >= 8) {
    auto stage = [&](int k) {
      if (warp == 11) {
        if (elect_one()) {
          while (clk32() - t_entry < ST1_CLK + (k - 1) * ST_GAP) {}
          mbar_expect_tx(BAR(B_FULL + k), ST_BYTES);
          tma_load_2d(sb + k * ST_BYTES + A_BYTES, &p.tmX, BAR(B_FULL + k), k * 64, tau * 256);
          tma_load_2d(sb + k * ST_BYTES, tmD, BAR(B_FULL + k), k * 64, eps * 128);
          TIM(k);
        }
        __syncwarp();
      }
    };
    reg_dec<72>();
    const uint32_t epoch = ld_relaxed32(&p.sc->epoch + threadIdx.y);
    const uint4 wq = ldg128(p.wr + (tid & 127) * 8);
#pragma unroll 1
    for (int k = 1; k < 4; k++) stage(k);
    cluster_wait();
    const int cid0 = cid;
    const uint32_t tag0 = __shfl_sync(0xffffffffu, epoch, 0) + 1, sb0 = sb;
    int a, lane, j, cid, tau, eps, m, grp, abrow, fc, src;
    uint32_t tag, c0, c1, sb, buf, bar0;
    bool ffn;
    auto BAR = [&](int i) { return sb + OFF_BAR + 8 * i; };
    auto fresh_ids = [&]() {
      const uint32_t z = uniform_zero_here();
      uint32_t l; asm volatile("mov.u32 %0, %%laneid;" : "=r"(l));
      a = warp - 8 + z; lane = l; j = a * 32 + l;
      cid = cid0 + z; tau = cid >> 4; eps = (cid >> 1) & 7; m = cid & 1; grp = tau * 2 + m; abrow = m * 1024 + eps * 128;
      const int ef = tau ? eps : eps ^ 5;
      ffn = ef > 0; fc = (tau * 7 + ef - 1) * 64; src = (fc >> 5) + m;
      tag = tag0 + z; c0 = code_of(tag); c1 = c0 >> 1;
      sb = sb0 + z; buf = sb + OFF_AUX + a * 8192; bar0 = BAR(B_AW + 2 * a);
    };
    fresh_ids();
    {
      const float s = warp_sum(((bf_lo(wq.x) + bf_hi(wq.x)) + (bf_lo(wq.y) + bf_hi(wq.y))) + ((bf_lo(wq.z) + bf_hi(wq.z)) + (bf_lo(wq.w) + bf_hi(wq.w))));
      if ((j >> 4) == eps) SM<uint4>(OFF_WR + (j & 15) * 16) = wq;
      if (lane == 0) { SM<float>(INFO_DS + a * 4) = s; SM<uint32_t>(INFO_ONES + a * 4) = 0x3F803F80u; }
    }
    const bf16* xrows = p.x + (cid * 16 + a * 4) * 1024;
    const bf16* drows = (cid < 64 ? p.Dre : p.Dim) + ((cid & 63) * 16 + a * 4) * 1024;
    fresh_ids();
    {
      wait_clk(t_entry, U_CLK);
      uint4 u[8]; uint32_t n = 0;
      bool more;
#pragma unroll 1
      do {
        uint32_t bad = 0;
#pragma unroll
        for (int q = 0; q < 8; q++) u[q] = pkt_ld128(&p.sc->u[a * 512 + lane * 2] + q * 64);
        if (n == 0 && lane == 0) { mbar_expect_tx(bar0, 4096); bulk_load(buf, xrows, 4096, bar0); }
#pragma unroll
        for (int q = 0; q < 8; q++) chk_code(bad, u[q], c0, c1);
        more = __any_sync(0xffffffffu, bad & 1) && ++n < SPIN_LIMIT;
        if (more) { __nanosleep(200); }
      } while (more);
      if (j == 0) TIM(96);
      if (lane == 0) { mbar_expect_tx(bar0 + 8, 4096); bulk_load(buf + 4096, xrows + 2048, 4096, bar0 + 8); }
#pragma unroll
      for (int q = 0; q < 8; q++) { u[q].x &= ~1u; u[q].y &= ~1u; u[q].z &= ~1u; u[q].w &= ~1u; }
#pragma unroll 1
      for (int r2 = 0; r2 < 2; r2++) {
        float v8[8];
        mbar_wait(bar0 + r2 * 8, 0);
        if (lane == 0) TIM(140 + r2 * 4 + a);
#pragma unroll
        for (int r = 0; r < 2; r++) {
          float s0 = 0.f, s1 = 0.f, q0 = 0.f, q1 = 0.f;
          uint32_t zr = 0, zi = 0;
#pragma unroll
          for (int q = 0; q < 4; q++) {
            const uint4 v = lds128(buf + r2 * 4096 + r * 2048 + (q * 32 + lane) * 16);
            const uint32_t ww[4] = {v.x, v.y, v.z, v.w};
#pragma unroll
            for (int z = 0; z < 4; z++) {
              const float lo = bf_lo(ww[z]), hi = bf_hi(ww[z]);
              s0 += lo; s1 += hi; q0 = fmaf(lo, lo, q0); q1 = fmaf(hi, hi, q1);
            }
            zr = bfma2(v.x, u[2 * q].x, zr); zi = bfma2(v.x, u[2 * q].y, zi); zr = bfma2(v.y, u[2 * q].z, zr); zi = bfma2(v.y, u[2 * q].w, zi);
            zr = bfma2(v.z, u[2 * q + 1].x, zr); zi = bfma2(v.z, u[2 * q + 1].y, zi); zr = bfma2(v.w, u[2 * q + 1].z, zr); zi = bfma2(v.w, u[2 * q + 1].w, zi);
          }
          v8[4 * r] = s0 + s1; v8[4 * r + 1] = q0 + q1; v8[4 * r + 2] = bf_lo(zr) + bf_hi(zr); v8[4 * r + 3] = bf_lo(zi) + bf_hi(zi);
        }
        fold<8>(v8, 16, lane);
        if (lane == 0) { mbar_expect_tx(bar0 + r2 * 8, 4096); bulk_load(buf + r2 * 4096, drows + r2 * 2048, 4096, bar0 + r2 * 8); }
        fold<4>(v8, 8, lane); fold<2>(v8, 4, lane);
        v8[0] += __shfl_xor_sync(0xffffffffu, v8[0], 2);
        v8[0] += __shfl_xor_sync(0xffffffffu, v8[0], 1);
        SM<float>(OFF_REM + a * 64 + r2 * 32 + (lane >> 2) * 4) = v8[0];
        if (lane == 0) TIM(148 + r2 * 4 + a);
      }
    }
    bar_sync(NB_AUX, 128);
    fresh_ids();
    if (a == 0 && lane < 16) {
      const float4 v = SM<float4>(OFF_REM + lane * 16);
      const float mean = v.x * (1.f / 1024.f), rs = fast_rcp(ref_sd(fmaxf(v.y * (1.f / 1024.f) - mean * mean, 0.f)));
      pkt_st128(&p.sc->xz[cid * 16 + lane], __float_as_uint(bf16r(mean)) | (tag & 0xFFFFu), __float_as_uint(rs), pack_bf16(v.z * rs, v.w * rs), tag);
    }
    if (j == 32) { const float4 v = SM<float4>(INFO_DS); SM<float2>(INFO_WSUM) = make_float2((v.x + v.y) + (v.z + v.w), __uint_as_float(tag)); }
    if (j == 0) TIM(98);
#pragma unroll 1
    for (int r2 = 0; r2 < 2; r2++) {
      mbar_wait(bar0 + r2 * 8, 1);
      const uint32_t da = buf + r2 * 4096 + (lane >> 4) * 2048 + (lane & 15) * 16;
      uint4 dv[3] = {lds128(da), lds128(da + 256), make_uint4(0, 0, 0, 0)};
      float s0 = 0.f, s1 = 0.f;
#pragma unroll
      for (int q = 0; q < 8; q++) {
        if (q < 6) dv[(q + 2) % 3] = lds128(da + (q + 2) * 256);
        s0 += __uint_as_float(zero_here());
        const uint4 v = dv[q % 3];
        s0 += bf_lo(v.x); s1 += bf_hi(v.x); s0 += bf_lo(v.y); s1 += bf_hi(v.y); s0 += bf_lo(v.z); s1 += bf_hi(v.z); s0 += bf_lo(v.w); s1 += bf_hi(v.w);
      }
      s0 += s1;
#pragma unroll
      for (int o = 8; o > 0; o >>= 1) s0 += __shfl_xor_sync(0xffffffffu, s0, o);
      SM<float>(INFO_DS2 + (a * 4 + r2 * 2 + (lane >> 4)) * 4) = s0;
    }
    bar_sync(NB_AUX, 128);
    if (a == 1 && lane < 16) pkt_st64(&p.sc->dsum[cid * 16 + lane], SM<uint32_t>(INFO_DS2 + lane * 4), tag);
    if (j == 0) TIM(99);
    {
      wait_clk(clk32(), XS_DELAY);
      uint2 v0, v1, cs; uint32_t n = 0;
      const uint32_t t16 = tag & 0xFFFFu;
      bool more;
#pragma unroll 1
      do {
        v0 = pkt_ld64(&p.sc->xz[tau * 256 + j]); v1 = pkt_ld64(&p.sc->xz[tau * 256 + j] + 128); cs = pkt_ld64(&p.sc->dsum[m * 1024 + eps * 128 + j]);
        more = !(__all_sync(0xffffffffu, (v0.x & 0xFFFFu) == t16 && (v1.x & 0xFFFFu) == t16 && cs.y == tag)) && ++n < SPIN_LIMIT;
        if (more) { __nanosleep(200); }
      } while (more);
      const int ro = OFF_RS + ((j & 7) >> 1) * 272 + (j >> 3) * 8 + (j & 1) * 4;
      SM<uint32_t>(ro) = v0.y ^ (m << 31); SM<uint32_t>(ro + 128) = v1.y ^ (m << 31);
      const uint32_t n0 = (v0.x >> 16) ^ 0x8000u, n1 = (v1.x >> 16) ^ 0x8000u;
      SM<uint4>(OFF_EXB + j * 16) = make_uint4(n0 | (n0 << 16), n0, 0, 0);
      SM<uint4>(OFF_EXB + 2048 + j * 16) = make_uint4(n1 | (n1 << 16), n1, 0, 0);
      const float c = 0.5f * __uint_as_float(cs.x), hi = bf16r(c), mid = bf16r(c - hi), lo = bf16r((c - hi) - mid);
      SM<uint4>(OFF_EXA + j * 16) = make_uint4((__float_as_uint(hi) >> 16) | __float_as_uint(mid), __float_as_uint(lo) >> 16, 0, 0);
      fence_async_smem();
      __syncwarp();
      if (lane == 0) mbar_arrive(BAR(B_STAT));
    }
    if (j == 0) TIM(100);
    auto all_published = [&](int half) {
      uint32_t n = 0;
#pragma unroll 1
      while (!__all_sync(0xffffffffu, ld_acquire32(&p.sc->abdone[(cid * 2 + half) * 32 + (lane & 7)]) == tag) && ++n < SPIN_LIMIT) {}
      if (lane == 31) {
        asm volatile("fence.proxy.async.global;" ::: "memory");
        mbar_arrive(BAR(B_ALL + half));
        TIM(80 + half);
      }
      __syncwarp();
    };
    {
      if (a == 3) {
        const uint32_t cl = poll64_warp(&p.sc->cl[cid * 16 + (lane & 3)], tag, 100);
        if (lane == 0) TIM(101);
        const bf16* wm = (m ? p.Wim : p.Wre) + tau * 256 + lane * 8;
        uint4 v[8];
#pragma unroll
        for (int i = 0; i < 8; i++) v[i] = ldg128(wm + ((__shfl_sync(0xffffffffu, cl, i >> 1) >> ((i & 1) * 16)) & 2047) * 2048);
        const int pos = cid * 4 + (lane & 3);
        const bf16* xc = p.x + ((__shfl_sync(0xffffffffu, cl, lane >> 3) >> ((lane & 4) * 4)) & 2047) * 1024 + (pos >> 3) * 16 + (pos & 7);
        const float x0 = ldbf(xc), x1 = ldbf(xc + 8), w0 = ldbf(p.wr + (pos >> 3) * 16 + (pos & 7)), w1 = ldbf(p.wr + (pos >> 3) * 16 + (pos & 7) + 8);
        if (lane < 4) SM<uint32_t>(INFO_CAND + lane * 4) = cl;
#pragma unroll
        for (int i = 0; i < 8; i++) SM<uint4>(OFF_WC + (lane >> 3) * 1024 + i * 128 + (((lane & 7) ^ i) << 4)) = v[i];
        fence_async_smem();
        __syncwarp();
        if (lane == 0) { mbar_arrive(BAR(B_WC)); TIM(102); }
        mbar_wait(BAR(B_CD), 0);
        wait_clk(clk32(), CP_DELAY);
        uint32_t n = 0;
        bool more;
#pragma unroll 1
        do {
          uint32_t bad = 0;
#pragma unroll
          for (int i = 0; i < 8; i++) v[i] = pkt_ld128(&p.sc->cpart[((lane >> 3) * 16 + ((lane >> 2) & 1)) * 512 + pos] + i * 1024);
#pragma unroll
          for (int i = 0; i < 8; i++) chk_code(bad, v[i], c0, c1);
          more = __any_sync(0xffffffffu, bad & 1) && ++n < SPIN_LIMIT;
          if (more) { __nanosleep(200); }
        } while (more);
        float y[4] = {0.f, 0.f, 0.f, 0.f};
#pragma unroll
        for (int i = 0; i < 8; i++) { y[0] += no_bit(v[i].x); y[2] += no_bit(v[i].y); y[1] += no_bit(v[i].z); y[3] += no_bit(v[i].w); }
#pragma unroll
        for (int i = 0; i < 4; i++) y[i] = bf16r(y[i]);
        __syncwarp();
        fold<4>(y, 4, lane);
        const uint32_t hp = pack_bf16(x0 + bf16r(y[0]), x1 + bf16r(y[1]));
        pkt_st64(&p.sc->ch[(lane >> 2) * 512 + pos], hp, tag);
        float st[3] = {bf_lo(hp) + bf_hi(hp), bf_lo(hp) * bf_lo(hp) + bf_hi(hp) * bf_hi(hp), bf_lo(hp) * w0 + bf_hi(hp) * w1};
#pragma unroll
        for (int o = 1; o < 4; o <<= 1) {
#pragma unroll
          for (int i = 0; i < 3; i++) st[i] += __shfl_xor_sync(0xffffffffu, st[i], o);
        }
        if ((lane & 3) == 0) pkt_st128(&p.sc->cs[cid * 8 + (lane >> 2)], with_bit(st[0], c0), with_bit(st[1], c1), __float_as_uint(st[2]), tag);
        if (lane == 0) TIM(119);
      }
      if (a < 2) {
        uint32_t* fl = lane < 2 ? &p.sc->abflag[(cid * 4 + 2 * a + lane) * 32] : &p.sc->abdone[(((cid & 15) + (lane & 7) * 16) * 2 + a) * 32 + tau];
        if (lane == 0) {
          if (a == 1) mbar_wait(BAR(B_SD), 0);
          const uint32_t t1 = clk32();
#pragma unroll 1
          for (int i = 2 * a; i < 2 + 6 * a; i++) {
            const int w = i & 1, c = (4 - (i >> 1)) & 3;
            if (a == 1) wait_clk(t1, (i - 2) * PUB_PACE);
            mbar_wait(BAR(B_EP + w * 4 + c), 0);
            TIM(64 + i);
            fence_async_smem();
            tma_store_2d(&p.tmAbS, sb + off_stage(c) + w * 8192, tau * 256 + c * 64, abrow + w * 64);
            if (w) { bulk_commit(); bulk_wait_all(); mbar_arrive(BAR(B_SD + c)); }
          }
          TIM(72 + a * 2);
          asm volatile("fence.proxy.async.global;" ::: "memory");
          asm volatile("st.release.gpu.global.b32 [%0], %1;" :: "l"(fl), "r"(tag) : "memory");
          TIM(73 + a * 2);
        }
        __syncwarp();
        if ((lane == 1 && a == 0) || (lane >> 3) == 1) st_relaxed32(fl, tag);
        if (a == 0) { __nanosleep(ALL_NS); all_published(0); }
        else {
          uint32_t n = 0;
#pragma unroll 1
          while (__any_sync(0xffffffffu, ld_acquire32(&p.sc->abflag[(((cid + 16) & 127) * 4 + 2) * 32]) != tag) && ++n < SPIN_LIMIT) {}
#pragma unroll 1
          for (int i = 0; i < 3; i++) {
            if (elect_one()) {
              if (i == 0) asm volatile("fence.proxy.async.global;" ::: "memory");
              mbar_wait(BAR(B_E23 + i), 0);
              tma_load_2d(sb + ((i + 3) & 3) * ST_BYTES, &p.tmAbL, BAR(B_FULL + ((i + 3) & 3)), (tau * 256 + 320 + i * 64) & 2047, abrow);
              TIM(82 + i);
            }
            __syncwarp();
            if (i == 1) all_published(1);
          }
        }
      } else if (a == 2) {
        const uint32_t* fl = &p.sc->abflag[(((cid + 16 + 16 * (lane & 1)) & 127) * 4 + (lane & 1)) * 32];
        mbar_wait(BAR(B_SD), 0);
        __nanosleep(LO_NS);
        uint32_t n = 0, seen = 0;
#pragma unroll 1
        for (int c = 0; c < 4; c++) {
#pragma unroll 1
          while (c < 2 && !((seen >> c) & 1) && ++n < SPIN_LIMIT) seen = __ballot_sync(0xffffffffu, ld_acquire32(fl) == tag);
          if (lane == c) {
            if (c != 1) mbar_wait(BAR(B_SD + c), 0);
            mbar_wait(BAR(c < 3 ? B_FULL + c : B_EMPTY), 0);
            if (c == 2) mbar_wait(BAR(B_ALL), 0);
            if (c < 2) asm volatile("fence.proxy.async.global;" ::: "memory");
            tma_load_2d(sb + c * ST_BYTES, &p.tmAbL, BAR(B_FULL + c), k_col(tau, 4 + c), abrow);
            TIM(130 + c);
          }
          __syncwarp();
        }
      }
      __syncwarp();
    }
    mbar_wait(BAR(B_CD), 0);
    mbar_wait(BAR(B_SD + 1), 0);
    const uint64_t pol_ef = policy_evict_first();
    auto load_unit = [&](int v) {
      if (elect_one()) {
        const uint32_t dst = buf + (v & 1) * 4096, bar = bar0 + (v & 1) * 8;
        mbar_expect_tx(bar, 4096);
        if (v < 8) {
          tma_load_2d_hint(dst, &p.tmG, bar, fc, m * 512 + (a * 8 + v) * 16, pol_ef);
          tma_load_2d_hint(dst + 2048, &p.tmU, bar, fc, m * 512 + (a * 8 + v) * 16, pol_ef);
        } else tma_load_2d_hint(dst, &p.tmDn, bar, a * 256, src * 32 + (v - 8) * 8, pol_ef);
      }
    };
    if (ffn) load_unit(0);
    if (a != 1) {
      bar_sync(NB_SEL, 96);
      wait_clk(clk32(), CS_DELAY);
      fresh_ids();
      if (a == 0 && lane < 8) {
        if (lane == 0) mbar_expect_tx(BAR(B_CH), 16384);
        bulk_load(sb + OFF_AUX + 4096 + (lane >> 1) * 8192 + (lane & 1) * 2048, &p.sc->ch[lane * 512 + m * 256], 2048, BAR(B_CH));
      }
      const int j3 = a ? j - 32 : j;
      uint4 v[11]; uint32_t n = 0;
      bool more;
#pragma unroll 1
      do {
#pragma unroll
        for (int i = 0; i < 11; i++) v[i] = pkt_ld128(&p.sc->cs[j3] + (i < 10 || a < 3 ? i * 96 : 0));
        uint32_t bad = 0;
#pragma unroll
        for (int i = 0; i < 11; i++) { chk(bad, v[i].x, c0); chk(bad, v[i].y, c1); }
        bad &= 1;
#pragma unroll
        for (int i = 0; i < 11; i++) chk(bad, v[i].w, tag);
        more = __any_sync(0xffffffffu, bad) && ++n < SPIN_LIMIT;
        if (more) __nanosleep(200);
      } while (more);
      if (j == 0) TIM(97);
      float st[3] = {0.f, 0.f, 0.f};
      if (a < 3) { st[0] = no_bit(v[10].x); st[1] = no_bit(v[10].y); st[2] = __uint_as_float(v[10].z); }
#pragma unroll
      for (int i = 0; i < 10; i++) { st[0] += no_bit(v[i].x); st[1] += no_bit(v[i].y); st[2] += __uint_as_float(v[i].z); }
#pragma unroll
      for (int o = 8; o < 32; o <<= 1) {
#pragma unroll
        for (int i = 0; i < 3; i++) st[i] += __shfl_xor_sync(0xffffffffu, st[i], o);
      }
      if (lane < 8) SM<float4>(OFF_XS + ((j3 >> 5) * 8 + lane) * 16) = make_float4(st[0], st[1], st[2], 0.f);
      bar_sync(NB_SEL, 96);
      const float4 f0 = SM<float4>(OFF_XS + (lane & 7) * 16), f1 = SM<float4>(OFF_XS + 128 + (lane & 7) * 16), f2 = SM<float4>(OFF_XS + 256 + (lane & 7) * 16);
      const float mu = ((f0.x + f1.x) + f2.x) * (1.f / 1024.f);
      float mb = bf16r(mu), inv = fast_rcp(ref_sd(fmaxf(((f0.y + f1.y) + f2.y) * (1.f / 1024.f) - mu * mu, 0.f)));
      const uint32_t kk = make_key(bf16r((((f0.z + f1.z) + f2.z) - mb * SM<float>(INFO_WSUM)) * inv), SM<uint16_t>(INFO_CAND + (lane & 7) * 2));
      const uint32_t key = __reduce_max_sync(0xffffffffu, kk);
      const int win = __ffs(__ballot_sync(0xffffffffu, kk == key)) - 1;
      mb = __shfl_sync(0xffffffffu, mb, win); inv = __shfl_sync(0xffffffffu, inv, win);
      if (j == 0) { SM<uint2>(INFO_KEY) = make_uint2(key, win); SM<float2>(INFO_LN) = make_float2(mb, inv); }
      mbar_wait(BAR(B_CH), 0);
      bar_sync(NB_SEL, 96);
#pragma unroll 1
      for (int i = j3; i < 128; i += 96) {
        uint4 r = lds128(sb + OFF_AUX + 4096 + (win >> 1) * 8192 + (win & 1) * 2048 + i * 16);
#pragma unroll 1
        while ((r.y != tag || r.w != tag) && ++n < SPIN_LIMIT) r = pkt_ld128(&p.sc->ch[win * 512 + m * 256 + 2 * i]);
        auto ln = [&](float h) { return bf16r(bf16r(h - mb) * inv); };
        const int d = (i >> 2) * 16 + (i & 3) * 2;
        SM<float2>(OFF_XS + d * 4) = make_float2(ln(bf_lo(r.x)), ln(bf_lo(r.z)));
        SM<float2>(OFF_XS + (d + 8) * 4) = make_float2(ln(bf_hi(r.x)), ln(bf_hi(r.z)));
      }
      __syncwarp();
    }
    bar_sync(NB_AUX, 128);
    if (j == 0) {
      mbar_arrive(BAR(B_INFO)); TIM(103);
      if (cid == 0) st_relaxed32(&p.sc->epoch, tag);
    }
    const uint32_t t2 = clk32();
    fresh_ids();
    uint2 hp2 = make_uint2(0, 0);
    const uint2* hpp = &p.sc->ch[SM<uint32_t>(INFO_KEY + 4) * 512 + (cid >> 1) * 8 + (lane & 7)];
    if (a == 3) { hp2 = pkt_ld64(hpp); if (lane == 0) asm volatile("prefetch.tensormap [%0];" :: "l"(&p.tmY) : "memory"); }
    if (ffn) {
      load_unit(1);
      const int r = lane >> 3;
      float acc[8] = {0.f, 0.f, 0.f, 0.f, 0.f, 0.f, 0.f, 0.f};
#pragma unroll 1
      for (int v = 0; v < 8; v++) {
        const uint4 x0 = lds128(sb + OFF_XS + ((a * 8 + v) * 16 + (r & 1) * 8) * 4), x1 = lds128(sb + OFF_XS + ((a * 8 + v) * 16 + (r & 1) * 8 + 4) * 4);
        const float xv[8] = {__uint_as_float(x0.x), __uint_as_float(x0.y), __uint_as_float(x0.z), __uint_as_float(x0.w), __uint_as_float(x1.x), __uint_as_float(x1.y), __uint_as_float(x1.z), __uint_as_float(x1.w)};
        mbar_wait(bar0 + (v & 1) * 8, (v >> 1) & 1);
        gemv8x8<128>(acc, buf + (v & 1) * 4096 + r * 1024 + (lane & 7) * 16, xv);
        fence_regs(acc);
        __syncwarp();
        wait_clk(t2, v * UNIT_PACE);
        load_unit(v + 2);
        if (j == 0) TIM(104 + v);
      }
      fold<8>(acc, 8, lane);
      bar_sync(NB_AUX, 128);
      SM<float4>(OFF_XS + (a * 128 + (r >> 1) * 64 + (lane & 7) * 8 + (r & 1) * 4) * 4) = make_float4(acc[0], acc[1], acc[2], acc[3]);
      bar_sync(NB_AUX, 128);
      auto psum = [&](int i) { return (SM<float>(OFF_XS + i * 4) + SM<float>(OFF_XS + (128 + i) * 4)) + (SM<float>(OFF_XS + (256 + i) * 4) + SM<float>(OFF_XS + (384 + i) * 4)); };
      if (a < 2) st_async_b32(mapa(sb + OFF_REM + j * 4, m ^ 1), mapa(BAR(B_GUX), m ^ 1), __float_as_uint(psum(a * 64 + (m ^ 1) * 32 + lane)));
      const float og = psum(m * 32 + lane), ou = psum(64 + m * 32 + lane);
      mbar_wait(BAR(B_GUX), 0);
      const float rg = SM<float>(OFF_REM + lane * 4), ru = SM<float>(OFF_REM + 128 + lane * 4);
      const float act = swiglu(m ? rg + og : og + rg, m ? ru + ou : ou + ru);
      if (j == 0) TIM(112);
      float y[8] = {0.f, 0.f, 0.f, 0.f, 0.f, 0.f, 0.f, 0.f};
#pragma unroll 1
      for (int v = 8; v < 12; v++) {
        float av[8];
#pragma unroll
        for (int i = 0; i < 8; i++) av[i] = __shfl_sync(0xffffffffu, act, (v - 8) * 8 + i);
        mbar_wait(bar0 + (v & 1) * 8, (v >> 1) & 1);
        gemv8x8<512>(y, buf + (v & 1) * 4096 + lane * 16, av);
        fence_regs(y);
        __syncwarp();
        if (v < 10) load_unit(v + 2);
        if (j == 0) TIM(105 + v);
      }
      fresh_ids();
      uint4* ypart = &p.sc->ypart[(a * NSRC + src) * 64 + lane];
      pkt_st128(ypart, with_bit(y[0], c0), with_bit(y[1], c1), with_bit(y[2], c0), with_bit(y[3], c1));
      pkt_st128(ypart + 32, with_bit(y[4], c0), with_bit(y[5], c1), with_bit(y[6], c0), with_bit(y[7], c1));
      if (lane == 0) TIM(160 + a);
    }
    if (a == 3) {
      const uint32_t hh = __all_sync(0xffffffffu, hp2.y == tag) ? hp2.x : poll64_warp(&p.sc->ch[SM<uint32_t>(INFO_KEY + 4) * 512 + (cid >> 1) * 8 + (lane & 7)], tag, 100);
      const uint32_t key = SM<uint32_t>(INFO_KEY);
      const float h = m ? bf_hi(hh) : bf_lo(hh), hn = bf16r(bf16r(h - SM<float>(INFO_LN)) * SM<float>(INFO_LN + 4));
      float sig = sigmoid_bf(key_val(key));
      bf16* op = p.out + (key_row(key) * 1024 + cid * 8 + (lane & 7));
      asm volatile("" : "+f"(sig), "+l"(op));
      wait_clk(t2, ROW_CLK);
      uint4 v[7]; uint32_t n = 0;
      bool more;
#pragma unroll 1
      do {
        if (elect_one()) { mbar_expect_tx(bar0, NSRC * 32); tma_load_2d(buf, &p.tmY, bar0, (cid & 31) * 8, (cid >> 5) * (2 * NSRC)); }
        mbar_wait(bar0, n & 1);
        uint32_t bad = 0;
#pragma unroll
        for (int i = 0; i < 7; i++) { v[i] = lds128(buf + i * 512 + lane * 16); chk_code(bad, v[i], c0, c1); }
        more = __any_sync(0xffffffffu, bad & 1) && ++n < SPIN_LIMIT;
        if (more) __nanosleep(200);
      } while (more);
      if (lane == 0) TIM(164);
      float y[4] = {0.f, 0.f, 0.f, 0.f};
#pragma unroll
      for (int i = 0; i < 7; i++) { y[0] += no_bit(v[i].x); y[1] += no_bit(v[i].y); y[2] += no_bit(v[i].z); y[3] += no_bit(v[i].w); }
      fold<4>(y, 16, lane); fold<2>(y, 8, lane);
      y[0] += __shfl_xor_sync(0xffffffffu, y[0], 4);
      y[0] += __shfl_xor_sync(0xffffffffu, y[0], 2);
      const float ys = __shfl_sync(0xffffffffu, y[0], (lane & 3) * 8 + ((lane >> 2) & 1));
      if (lane < 8) st_bf16(op, routed_out(h, hn, ys, sig));
      if (lane == 0) { TIM(118); pkt_st64(&p.sc->rdone[cid], 0, tag); }
    }
  } else {
    reg_inc<216>();
    const uint32_t sb = __shfl_sync(0xffffffffu, smem_u32(smem_raw), 0);
    auto BAR = [&](int i) { return sb + OFF_BAR + 8 * i; };
    const int w = warp >> 2, wi = warp & 3, t = tid & 127;
    const int turn_me = NB_TURN0 + w, turn_other = NB_TURN1 - w;
    const uint64_t dA0 = make_desc(sb + w * 8192);
    uint64_t dA, dB;
    int tau, eps, m, grp, abrow, fc, src;
    bool ffn;
    const CUtensorMap* tmD; const CUtensorMap* tmW;
    auto new_desc = [&](int salt) {
      const uint32_t z = salt < 0 ? uniform_zero_here() : salt & blockIdx.y;
      dA = dA0 + z; dB = dA0 + (z + ((A_BYTES - w * 8192) >> 4));
      const int c = cid + z;
      tau = c >> 4; eps = (c >> 1) & 7; m = c & 1; grp = tau * 2 + m; abrow = m * 1024 + eps * 128;
      const int ef = tau ? eps : eps ^ 5;
      ffn = ef > 0; fc = (tau * 7 + ef - 1) * 64; src = (fc >> 5) + m;
      tmD = &p.tmD0 + m; tmW = &p.tmW0 + m;
    };
    constexpr int SL = ST_BYTES >> 4;
    float acc[128];
#pragma unroll
    for (int i = 0; i < 128; i++) acc[i] = 0.f;
    if (w == 1) bar_arrive(NB_TURN0, 256);
    auto full = [&](int k) { mbar_wait(BAR(B_FULL + (k & 3)), (k >> 2) & 1); CT(64 + k); };
    auto refill_w = [&](int k) {
      if (warp == 4) {
        if (elect_one()) {
          const int s = k & 3, s0 = k_col(tau, k - 12);
          TIM(k + 4);
          mbar_expect_tx(BAR(B_FULL + s), k < 16 ? B_BYTES : ST_BYTES);
          if (k == 19) mbar_arrive(BAR(B_EMPTY));
          tma_load_2d(sb + s * ST_BYTES + A_BYTES, tmW, BAR(B_FULL + s), s0, grp * 128);
          tma_load_2d(sb + s * ST_BYTES + A_BYTES + 16384, tmW, BAR(B_FULL + s), s0, (grp ^ 1) * 128);
        }
        __syncwarp();
      }
    };
    auto mma_ss = [&](int k) {
#pragma unroll
      for (int kk = 0; kk < 4; kk++) wgmma_n256(acc, dA + (k & 3) * SL + kk * 2, dB + (k & 3) * SL + kk * 2);
    };
    const CUtensorMap* rf_tm; uint32_t rf_dst; int rf_row, rf_c; bool rf_on;
    auto rf_set = [&](const CUtensorMap* tm, uint32_t dst, int row) {
      rf_tm = (const CUtensorMap*)__shfl_sync(0xffffffffu, (unsigned long long)tm, 0);
      rf_dst = __shfl_sync(0xffffffffu, dst, 0); rf_row = __shfl_sync(0xffffffffu, row, 0);
    };
    auto refill = [&](int s) {
      if (rf_on) {
        if (elect_one()) tma_load_2d(rf_dst + s * ST_BYTES, rf_tm, BAR(B_FULL + s), rf_c, rf_row);
        __syncwarp();
      }
      if (tid == 224) mbar_expect_tx(BAR(B_FULL + s), ST_BYTES);
    };
    const bf16* pf; int pf_step; bool pf_on;
    auto pf_ffn = [&](int v) {
      pf_on = ffn && v >= 0 && v < 12;
      pf = v < 8 ? ((lane & 16) ? p.wup : p.wgate) + (m * 512 + (wi * 8 + v) * 16 + (lane & 15)) * 3584 + fc : p.wdown + (src * 32 + (v - 8) * 8) * 1024 + t * 64;
      pf_step = v < 8 ? 16 * 3584 : 8192;
    };
    auto prefetch = [&](int s) { if (pf_on && (wi >> 1) == (s & 1)) prefetch_l2(pf + (s >> 1) * pf_step); };
    auto kstep = [&](int k) {
      full(k);
      bar_sync(turn_me, 256);
      wgmma_fence();
      mma_ss(k);
      wgmma_commit();
      bar_arrive(turn_other, 256);
    };

    uint32_t R[64];
    auto load_rs = [&](auto gi) {
      const uint32_t rsa = sb + OFF_RS + (lane & 3) * 272;
#pragma unroll
      for (int i = 4 * decltype(gi)::value; i < 4 * decltype(gi)::value + 4; i++) { const uint4 v = lds128(rsa + i * 16); R[4 * i] = v.x; R[4 * i + 1] = v.y; R[4 * i + 2] = v.z; R[4 * i + 3] = v.w; }
    };
    new_desc(64);
    rf_on = (warp >> 1) == 2;
    rf_set(wi ? tmD : &p.tmX, wi ? sb : sb + A_BYTES, wi ? eps * 128 : tau * 256);
#pragma unroll 1
    for (int k4 = 0; k4 < 12; k4 += 4) {
#pragma unroll
      for (int s = 0; s < 4; s++) {
        kstep(k4 | s);
        if (s == 0) {
          if (w == 0) pf_ffn((k4 >> 1) - 2);
          else {
            pf_on = k4 == 8 || (k4 == 4 && (lane & 7) < 3);
            pf = (m ? p.Wim : p.Wre) + (tau * 256 + eps * 32 + wi * 4 + (lane >> 3)) * 2048 + k_col(tau, (lane & 7) + (k4 == 8 ? 3 : 0));
            pf_step = 16 * 2048;
          }
        }
        rf_c = (k4 + s + 4) * 64;
        prefetch(s);
        if (s == 3) new_desc(k4);
        if (s == 0 || s == 3) pf += zero_here();
        wgmma_wait<0>();
        refill(s);
      }
    }
    kstep(12);
    mbar_wait(BAR(B_STAT), 0);
    load_rs(std::integral_constant<int, 0>());
    CT(1);
    load_rs(std::integral_constant<int, 1>());
    wgmma_wait<0>(); refill_w(12);
    auto mma_h = [&](float (&d)[64], int s, int half) {
#pragma unroll
      for (int kk = 0; kk < 4; kk++) wgmma_n128(d, dA + s * SL + kk * 2, dB + s * SL + half * 1024 + kk * 2);
    };
    const int rho = 16 * wi + (lane & 15);
    const uint32_t arow = sb + w * 8192 + rho * 128;
    auto convert = [&](auto cc, const float* d) {
      const float z = __uint_as_float(zero_here());
#pragma unroll
      for (int jj = 8 * decltype(cc)::value; jj < 8 * decltype(cc)::value + 8; jj++) {
        const float r0 = __uint_as_float(R[2 * jj]), r1 = __uint_as_float(R[2 * jj + 1]);
        const float* ac = &d[4 * (jj & 7)];
        R[2 * jj] = pack_bf16(fmaf(ac[0], r0, z), fmaf(ac[1], r1, z));
        R[2 * jj + 1] = pack_bf16(fmaf(ac[2], r0, z), fmaf(ac[3], r1, z));
      }
    };
    auto put = [&](auto cc) {
      constexpr int c = decltype(cc)::value;
#pragma unroll
      for (int jj = 8 * c; jj < 8 * c + 8; jj += 2)
        stsm_x4(arow + off_stage(c) + ((((jj & 7) + (lane >> 4)) ^ (rho & 7)) << 4), R[2 * jj], R[2 * jj + 1], R[2 * jj + 2], R[2 * jj + 3]);
      __syncwarp();
      if (lane == 0) mbar_arrive(BAR(B_EP + w * 4 + c));
    };
    {
      float lo[32], hi[96];
      fence_regs(acc);
#pragma unroll
      for (int i = 0; i < 32; i++) asm volatile("mov.b32 %0, %1;" : "=f"(lo[i]) : "f"(acc[i]));
#pragma unroll
      for (int i = 0; i < 96; i++) asm volatile("mov.b32 %0, %1;" : "=f"(hi[i]) : "f"(acc[32 + i]));
      auto mma_p = [&](auto& d, int s, int boff) {
#pragma unroll
        for (int kk = 0; kk < 4; kk++) wgmma_part(d, dA + s * SL + kk * 2, dB + s * SL + boff + kk * 2);
      };
      const uint64_t dEA = make_desc_noswz(sb + OFF_EXA + w * 1024), dEB = make_desc_noswz(sb + OFF_EXB);
      full(13); full(14);
      bar_sync(turn_me, 256);
      wgmma_fence();
      mma_p(lo, 1, 0); mma_p(lo, 2, 0);
      wgmma_commit();
      bar_arrive(turn_other, 256);
      new_desc(66);
      full(15);
      bar_sync(turn_me, 256);
      wgmma_fence();
      mma_p(lo, 3, 0);
      wgmma_part(lo, dEA, dEB);
      wgmma_commit();
      mma_p(hi, 1, 512);
      wgmma_commit();
      bar_arrive(turn_other, 256);
      new_desc(67);
      wgmma_wait<1>();
      fence_regs(lo);
      CT(15);
      convert(std::integral_constant<int, 0>(), lo); put(std::integral_constant<int, 0>());
      load_rs(std::integral_constant<int, 3>());
      wgmma_wait<0>(); refill_w(13);
      bar_sync(turn_me, 256);
      wgmma_fence();
      mma_p(hi, 2, 512);
      wgmma_commit();
      mma_p(hi, 3, 512);
      wgmma_part(hi, dEA, dEB + 64);
      wgmma_commit();
      bar_arrive(turn_other, 256);
      load_rs(std::integral_constant<int, 2>());
      wgmma_wait<1>(); refill_w(14);
      wgmma_wait<0>(); refill_w(15);
      fence_regs(hi);
      CT(2);
      convert(std::integral_constant<int, 3>(), hi + 64);
      put(std::integral_constant<int, 3>());
      convert(std::integral_constant<int, 1>(), hi);
      convert(std::integral_constant<int, 2>(), hi + 32);
    }
    CT(3);
    new_desc(-1);
    full(16);
    bar_sync(turn_me, 256);
    wgmma_fence();
    wgmma_n256_rs_init(acc, R, dB);
#pragma unroll
    for (int kk = 1; kk < 4; kk++) wgmma_n256_rs(acc, R + 4 * kk, dB + kk * 2);
    wgmma_commit();
    full(17);
    wgmma_fence();
#pragma unroll
    for (int kk = 0; kk < 4; kk++) wgmma_n256_rs(acc, R + 16 + 4 * kk, dB + SL + kk * 2);
    wgmma_commit();
    bar_arrive(turn_other, 256);
    put(std::integral_constant<int, 2>());
    wgmma_wait<1>(); refill_w(16);
    wgmma_wait<0>(); refill_w(17);
    {
      fence_async_smem();
      mbar_wait(BAR(B_WC), 0);
      CT(4);
      full(18);
      bar_sync(turn_me, 256);
      wgmma_fence();
      float cc[4];
      const uint64_t dC = make_desc(sb + OFF_WC);
      wgmma_n8_rs<0>(cc, R, dC);
#pragma unroll
      for (int i = 1; i < 12; i++) wgmma_n8_rs<1>(cc, R + 4 * i, dC + (i >> 2) * 64 + (i & 3) * 2);
#pragma unroll
      for (int kk = 0; kk < 4; kk++) wgmma_n8(cc, dA + 3 * SL + kk * 2, dC + 192 + kk * 2);
      wgmma_commit();
#pragma unroll
      for (int kk = 0; kk < 4; kk++) wgmma_n256_rs(acc, R + 32 + 4 * kk, dB + 2 * SL + kk * 2);
      wgmma_commit();
      bar_arrive(turn_other, 256);
      wgmma_wait<1>();
      fence_regs(cc);
      const uint32_t cd = code_of(SM<uint32_t>(INFO_TAG));
      if (t == 0) mbar_arrive(BAR(B_CD));
      pkt_st128(&p.sc->cpart[((lane & 3) * 16 + grp) * 512 + eps * 64 + warp * 8 + (lane >> 2)], with_bit(cc[0], cd), with_bit(cc[1], cd >> 1), with_bit(cc[2], cd), with_bit(cc[3], cd >> 1));
      CT(5);
    }
    put(std::integral_constant<int, 1>());
    wgmma_wait<0>(); refill_w(18);
    kstep(19);
    cluster_wait();
    new_desc(68);
    rf_set(wi == 2 ? &p.tmAbL : tmW, wi == 2 ? sb : sb + A_BYTES + wi * 16384, wi == 2 ? abrow : (grp ^ wi) * 128);
    wgmma_wait<0>(); refill_w(19);
    const int g = lane >> 2, q = lane & 3;
    uint4 ha[4], hb[4], wv[4], info = make_uint4(0, 0, 0, 0);
#pragma unroll
    for (int i = 0; i < 4; i++) ha[i] = hb[i] = wv[i] = make_uint4(0, 0, 0, 0);
    auto load_x = [&](auto ii) {
      constexpr int i = decltype(ii)::value;
      const bf16* xp = p.x + ((grp * 128 + warp * 16 + g) * 1024 + eps * 128 + q * 8);
      ha[i] = ldg128(xp + i * 32); hb[i] = ldg128(xp + 8192 + i * 32);
    };
    auto load_w = [&]() {
      mbar_wait(BAR(B_INFO), 0);
#pragma unroll
      for (int i = 0; i < 4; i++) wv[i] = lds128(sb + ((g & 1) ? OFF_WR + (i * 4 + q) * 16 : INFO_ONES));
      info = lds128(sb + OFF_INFO);
    };

    rf_on = w == 1 && wi < 3;
    rf_c = k_col(tau, 7);
#pragma unroll 1
    for (int k4 = 20; k4 < 44; k4 += 4) {
#pragma unroll
      for (int s = 0; s < 4; s++) {
        kstep(k4 | s);
        if (s == 0) {
          if (w == 0) { pf_ffn((k4 >> 1) - 8); pf_on = pf_on && k4 >= 24; }
          else {
            pf_on = k4 == 32;
            pf = p.x + (grp * 128 + (t >> 1)) * 1024 + eps * 128 + (t & 1) * 64;
            pf_step = 64 * 1024;
          }
        }
        rf_c = k_next(rf_c, k4 + s - 12);
        if (s == 0 && k4 == 20 && warp == 6) mbar_wait(BAR(B_ALL), 0);
        if (s == 2 && k4 == 24 && warp == 6) mbar_wait(BAR(B_ALL + 1), 0);
        prefetch(s);
        if (k4 == 40) {
          if (s == 1) load_w();
          if (s == 2) load_x(std::integral_constant<int, 0>());
          if (s == 3) load_x(std::integral_constant<int, 1>());
        }
        if (s == 3) new_desc(k4);
        if (s == 0 || s == 3) pf += zero_here();
        wgmma_wait<0>();
        if (((s == 3 && k4 == 20) || (s < 2 && k4 == 24)) && warp == 6) { if (lane == 0) mbar_arrive(BAR(B_E23 + ((s + 1) & 3))); }
        else refill(s);
      }
    }
    const int row0 = grp * 128 + warp * 16 + g;
    kstep(44);
    load_x(std::integral_constant<int, 2>());
    wgmma_wait<0>();
    if (tid == 128) mbar_arrive_remote(mapa(BAR(B_PEER), m ^ 1));
    uint32_t hp[32];
    bf16* op; uint4* hpub; uint4* hst;
    uint32_t cd, ast, ald, zr;
    auto swz = [](int row) { return ((row & 1) << 2) | ((row >> 1) & 3); };
    {
      float as[64], ak[64];
      fence_regs(acc);
#pragma unroll
      for (int i = 0; i < 64; i++) asm volatile("mov.b32 %0, %1;" : "=f"(as[i]) : "f"(acc[64 + i]));
#pragma unroll
      for (int i = 0; i < 64; i++) asm volatile("mov.b32 %0, %1;" : "=f"(ak[i]) : "f"(acc[i]));
      full(45); full(46);
      bar_sync(turn_me, 256);
      wgmma_fence();
      mma_h(as, 1, 1); mma_h(as, 2, 1);
      wgmma_commit();
      bar_arrive(turn_other, 256);
      load_x(std::integral_constant<int, 3>());
      full(47);
      bar_sync(turn_me, 256);
      wgmma_fence();
      mma_h(as, 3, 1);
      wgmma_commit();
      const uint32_t rx = mapa(sb + OFF_RECV + w * 16384 + t * 16, m ^ 1), rb = mapa(BAR(B_XCH + w), m ^ 1);
      mma_h(ak, 1, 0);
      wgmma_commit();
      bar_arrive(turn_other, 256);
      mbar_wait(BAR(B_PEER), 0);
      wgmma_wait<1>();
      fence_regs(as);
      CT(6);
#pragma unroll
      for (int i = 0; i < 8; i++) {
        const float* ac = &as[8 * i];
        st_async_v4(rx + i * 2048, rb, pack_bf16(ac[0], ac[1]), pack_bf16(ac[2], ac[3]), pack_bf16(ac[4], ac[5]), pack_bf16(ac[6], ac[7]));
      }
      CT(7);
      bar_sync(turn_me, 256);
      wgmma_fence();
      mma_h(ak, 2, 0); mma_h(ak, 3, 0);
      wgmma_commit();
      if (w == 0) bar_arrive(turn_other, 256);
      op = p.out + row0 * 1024 + eps * 128 + q * 8;
      hst = &p.sc->hstat[grp * 1024 + warp * 16 + g];
      hpub = hst + eps * 128; hst += q * 256;
      cd = code_of(info.y);
      ast = sb + w * ST_BYTES + (8 * (lane >> 4) + (lane & 7)) * 128 + (((2 * wi + ((lane >> 3) & 1)) ^ swz(lane & 7)) << 4);
      ald = sb + (warp * 16 + g) * 128 + ((q ^ swz(g)) << 4);
      asm volatile("" : "+l"(op), "+l"(hpub), "+l"(hst), "+r"(cd), "+r"(ast), "+r"(ald));
      zr = zero_here();
#pragma unroll
      for (int i = 0; i < 4; i++) { ha[i].x += zr; hb[i].x += zr; asm volatile("" : "+r"(ha[i].x), "+r"(hb[i].x)); }
      ast += (uint32_t)(clock64() >> 32) & zr;
      mbar_wait(BAR(B_XCH + w), 0);
      CT(9);
#pragma unroll
      for (int i = 0; i < 8; i++) { const uint4 v = lds128(sb + OFF_RECV + w * 16384 + t * 16 + i * 2048); hp[4 * i] = v.x; hp[4 * i + 1] = v.y; hp[4 * i + 2] = v.z; hp[4 * i + 3] = v.w; }
      wgmma_wait<0>();
      fence_regs(ak);
      CT(10);
#pragma unroll
      for (int i = 0; i < 32; i++) hp[i] = badd2(pack_bf16(ak[2 * i], ak[2 * i + 1]), hp[i]);
    }
#pragma unroll
    for (int jj = 0; jj < 16; jj += 2) stsm_x4_t(ast + jj * 1024, hp[2 * jj], hp[2 * jj + 1], hp[2 * jj + 2], hp[2 * jj + 3]);
    const uint32_t tag = info.y;
    uint4 v[4];
    auto fetch = [&]() { v[0] = pkt_ld128(hst); v[1] = pkt_ld128(hst + 128); v[2] = pkt_ld128(hst + 8); v[3] = pkt_ld128(hst + 136); };
    float st[6], hf[64];
    {
      float sw[2][4], qa[2][4], qb[2][4];
#pragma unroll
      for (int i = 0; i < 8; i++) { sw[i >> 2][i & 3] = 0.f; qa[i >> 2][i & 3] = 0.f; qb[i >> 2][i & 3] = 0.f; }
      bar_sync(NB_BOTH, 256);
      CT(11);
      uint4 ya[4], yb[4];
#pragma unroll
      for (int i = 0; i < 4; i++) {
        const uint32_t ad = (ald ^ ((i & 1) << 6)) + (i >> 1) * ST_BYTES;
        ya[i] = lds128(ad); yb[i] = lds128(ad + 1024);
      }
      fetch();
      sw[0][0] = __uint_as_float((uint32_t)(clock64() >> 32) & zr);
#pragma unroll
      for (int i = 0; i < 4; i++) {
        ha[i] = make_uint4(badd2(ha[i].x, ya[i].x), badd2(ha[i].y, ya[i].y), badd2(ha[i].z, ya[i].z), badd2(ha[i].w, ya[i].w));
        hb[i] = make_uint4(badd2(hb[i].x, yb[i].x), badd2(hb[i].y, yb[i].y), badd2(hb[i].z, yb[i].z), badd2(hb[i].w, yb[i].w));
        mma16816(sw[0], ha[i].x, hb[i].x, ha[i].y, hb[i].y, wv[i].x, wv[i].y);
        mma16816(qa[0], ha[i].x, hb[i].x, ha[i].y, hb[i].y, ha[i].x, ha[i].y);
        mma16816(qb[0], ha[i].x, hb[i].x, ha[i].y, hb[i].y, hb[i].x, hb[i].y);
        mma16816(sw[1], ha[i].z, hb[i].z, ha[i].w, hb[i].w, wv[i].z, wv[i].w);
        mma16816(qa[1], ha[i].z, hb[i].z, ha[i].w, hb[i].w, ha[i].z, ha[i].w);
        mma16816(qb[1], ha[i].z, hb[i].z, ha[i].w, hb[i].w, hb[i].z, hb[i].w);
      }
      const uint32_t s0 = with_bit(sw[0][0] + sw[1][0], cd), s1 = with_bit((g & 1) ? qa[0][1] + qa[1][1] : qa[0][0] + qa[1][0], cd >> 1), s2 = __float_as_uint(sw[0][1] + sw[1][1]);
      const uint32_t s3 = with_bit(sw[0][2] + sw[1][2], cd), s4 = with_bit((g & 1) ? qb[0][3] + qb[1][3] : qb[0][2] + qb[1][2], cd >> 1), s5 = __float_as_uint(sw[0][3] + sw[1][3]);
      if (q == (g >> 1)) { pkt_st128(hpub, s0, s1, s2, tag); pkt_st128(hpub + 8, s3, s4, s5, tag); }
      CT(12);
      {
#pragma unroll
        for (int i = 0; i < 8; i++) {
          const uint4 h = i < 4 ? ha[i] : hb[i - 4];
          hf[8 * i] = bf_lo(h.x); hf[8 * i + 1] = bf_hi(h.x); hf[8 * i + 2] = bf_lo(h.y); hf[8 * i + 3] = bf_hi(h.y);
          hf[8 * i + 4] = bf_lo(h.z); hf[8 * i + 5] = bf_hi(h.z); hf[8 * i + 6] = bf_lo(h.w); hf[8 * i + 7] = bf_hi(h.w);
        }
        fence_regs(hf);
        op += (uint32_t)(clock64() >> 32) & zr;
      }
      const uint32_t o1 = __shfl_sync(0xffffffffu, s1, (lane & 28) | (g >> 1)), o4 = __shfl_sync(0xffffffffu, s4, (lane & 28) | (g >> 1));
      uint32_t n = 0;
      bool more;
#pragma unroll 1
      do {
        if (2 * q == eps) { v[0] = make_uint4(s0, o1, s2, tag); v[2] = make_uint4(s3, o4, s5, tag); }
        if (2 * q + 1 == eps) { v[1] = make_uint4(s0, o1, s2, tag); v[3] = make_uint4(s3, o4, s5, tag); }
        uint32_t bad = 0;
#pragma unroll
        for (int i = 0; i < 4; i++) { chk(bad, v[i].x, cd); chk(bad, v[i].y, cd >> 1); }
        bad &= 1;
#pragma unroll
        for (int i = 0; i < 4; i++) chk(bad, v[i].w, tag);
        more = __any_sync(0xffffffffu, bad) && ++n < SPIN_LIMIT;
        if (more && bad) fetch();
      } while (more);
      st[0] = no_bit(v[0].x) + no_bit(v[1].x); st[1] = no_bit(v[0].y) + no_bit(v[1].y); st[2] = __uint_as_float(v[0].z) + __uint_as_float(v[1].z);
      st[3] = no_bit(v[2].x) + no_bit(v[3].x); st[4] = no_bit(v[2].y) + no_bit(v[3].y); st[5] = __uint_as_float(v[2].z) + __uint_as_float(v[3].z);
    }
    CT(13);
#pragma unroll
    for (int o = 1; o < 4; o <<= 1) {
#pragma unroll
      for (int i = 0; i < 6; i++) st[i] += __shfl_xor_sync(0xffffffffu, st[i], o);
    }
    float mb[2], inv[2];
#pragma unroll
    for (int i = 0; i < 2; i++) {
      const float mu = st[3 * i] * (1.f / 1024.f);
      mb[i] = bf16r(mu);
      inv[i] = fast_rcp(ref_sd(fmaxf(st[3 * i + 1] * (1.f / 1024.f) - mu * mu, 0.f)));
    }
    {
      const int srow = key_row(info.z);
      auto put_out = [&](bf16* dst, const float* f, float sc, float of, bool on) {
        auto cvt = [&](int i) { return pack_bf16(fmaf(f[i], sc, of), fmaf(f[i + 1], sc, of)); };
        asm volatile("{\n.reg .pred p;\nsetp.ne.b32 p, %5, 0;\n@p st.global.v4.b32 [%0], {%1, %2, %3, %4};\n}\n"
                     :: "l"(dst), "r"(cvt(0)), "r"(cvt(2)), "r"(cvt(4)), "r"(cvt(6)), "r"((int)on) : "memory");
      };
#pragma unroll
      for (int i = 0; i < 4; i++) {
        put_out(op + i * 32, hf + 8 * i, 1.f + inv[0], -mb[0] * inv[0], row0 != srow);
        put_out(op + 8192 + i * 32, hf + 32 + 8 * i, 1.f + inv[1], -mb[1] * inv[1], row0 + 8 != srow);
      }
    }
    CT(14);
    const uint4 cand = lds128(sb + INFO_CAND);
    uint32_t wkey = zero_here();
#pragma unroll
    for (int i = 0; i < 2; i++) {
      const uint32_t row = row0 + 8 * i, rr = row | (row << 16);
      const bool is_cand = __vcmpeq2(cand.x, rr) | __vcmpeq2(cand.y, rr) | __vcmpeq2(cand.z, rr) | __vcmpeq2(cand.w, rr);
      if (!is_cand) wkey = max(wkey, make_key(bf16r((st[3 * i + 2] - mb[i] * __uint_as_float(info.x)) * inv[i]), row));
    }
    wkey = __reduce_max_sync(0xffffffffu, wkey);
    if (eps == 0 && lane == 0) pkt_st64(&p.sc->key[grp * 8 + warp], wkey, tag);
    const bool beaten = (wkey >> 16) > (info.z >> 16);
    if (__builtin_expect(beaten, 0)) {
      const int br = key_row(wkey);
      if (br == row0 || br == row0 + 8) {
#pragma unroll
        for (int i = 0; i < 4; i++) {
          const uint4 h = br == row0 ? ha[i] : hb[i];
          uint2* dst = &p.sc->hrow[(grp * 8 + warp) * 512 + eps * 64 + i * 16 + q * 4];
          pkt_st128(dst, h.x, tag, h.y, tag); pkt_st128(dst + 2, h.z, tag, h.w, tag);
        }
      }
      __syncwarp();
    }
    uint32_t any;
    asm volatile("{\n.reg .pred p, q;\nsetp.ne.b32 p, %1, 0;\nbarrier.cta.red.or.aligned.pred q, %2, 256, p;\nselp.u32 %0, 1, 0, q;\n}\n" : "=r"(any) : "r"((int)beaten), "n"((int)NB_END) : "memory");
    if (__builtin_expect(any, 0)) slow_path(p, grp, eps, tag, info.z, info.w, SM<float>(INFO_LN), SM<float>(INFO_LN + 4));
  }
}

__global__ void __launch_bounds__(NTHR, 1) occupancy_probe_kernel() {}

typedef CUresult (*EncodeFn)(CUtensorMap*, CUtensorMapDataType, cuuint32_t, void*, const cuuint64_t*, const cuuint64_t*, const cuuint32_t*, const cuuint32_t*,
                             CUtensorMapInterleave, CUtensorMapSwizzle, CUtensorMapL2promotion, CUtensorMapFloatOOBfill);

static void make_tm(EncodeFn enc, CUtensorMap* tm, const void* ptr, uint64_t rows, uint64_t cols, uint32_t brows, uint32_t bcols, bool swz) {
  cuuint64_t dims[2] = {cols, rows};
  cuuint64_t strides[1] = {cols * 2};
  cuuint32_t box[2] = {bcols, brows};
  cuuint32_t es[2] = {1, 1};
  enc(tm, CU_TENSOR_MAP_DATA_TYPE_BFLOAT16, 2, const_cast<void*>(ptr), dims, strides, box, es, CU_TENSOR_MAP_INTERLEAVE_NONE,
      swz ? CU_TENSOR_MAP_SWIZZLE_128B : CU_TENSOR_MAP_SWIZZLE_NONE, CU_TENSOR_MAP_L2_PROMOTION_L2_128B, CU_TENSOR_MAP_FLOAT_OOB_FILL_NONE);
}

extern "C" void kernel_launch(void* const* d_in, const int* in_sizes, int n_in, void* d_out, int out_size) {
  (void)in_sizes; (void)n_in; (void)out_size;
  static EncodeFn enc = nullptr;
  static void* abT = nullptr;
  static void* sc = nullptr;
  static int map = 0;
  if (!enc) {
    void* fn = nullptr; cudaDriverEntryPointQueryResult st;
    cudaGetDriverEntryPoint("cuTensorMapEncodeTiled", &fn, cudaEnableDefault, &st);
    enc = (EncodeFn)fn;
    cudaGetSymbolAddress(&abT, g_abT);
    cudaGetSymbolAddress(&sc, g_sc);
    cudaFuncSetAttribute(fnet_moe_kernel<0>, cudaFuncAttributeMaxDynamicSharedMemorySize, SMEM_TOTAL);
    cudaFuncSetAttribute(fnet_moe_kernel<1>, cudaFuncAttributeMaxDynamicSharedMemorySize, SMEM_TOTAL);
    cudaFuncSetAttribute(occupancy_probe_kernel, cudaFuncAttributeMaxDynamicSharedMemorySize, SMEM_TOTAL);
    cudaFuncSetAttribute(occupancy_probe_kernel, cudaFuncAttributeNonPortableClusterSizeAllowed, 1);
    cudaLaunchConfig_t cfg = {};
    cfg.gridDim = dim3(128); cfg.blockDim = dim3(NTHR); cfg.dynamicSmemBytes = SMEM_TOTAL;
    cudaLaunchAttribute at[1];
    at[0].id = cudaLaunchAttributeClusterDimension; at[0].val.clusterDim.x = 16; at[0].val.clusterDim.y = 1; at[0].val.clusterDim.z = 1;
    cfg.attrs = at; cfg.numAttrs = 1;
    int ncl = 0;
    if (cudaOccupancyMaxActiveClusters(&ncl, occupancy_probe_kernel, &cfg) == cudaSuccess && ncl >= 8) map = 1;
    (void)cudaGetLastError();
  }
  Params p;
  const bf16* x = (const bf16*)d_in[0];
  make_tm(enc, &p.tmD0, d_in[3], 1024, 1024, 128, 64, true);
  make_tm(enc, &p.tmD1, d_in[4], 1024, 1024, 128, 64, true);
  make_tm(enc, &p.tmX, x, 2048, 1024, 256, 64, true);
  make_tm(enc, &p.tmAbS, abT, 2048, 2048, 64, 64, true);
  make_tm(enc, &p.tmAbL, abT, 2048, 2048, 128, 64, true);
  make_tm(enc, &p.tmW0, d_in[1], 2048, 2048, 128, 64, true);
  make_tm(enc, &p.tmW1, d_in[2], 2048, 2048, 128, 64, true);
  make_tm(enc, &p.tmG, d_in[7], 1024, 3584, 16, 64, false);
  make_tm(enc, &p.tmU, d_in[8], 1024, 3584, 16, 64, false);
  make_tm(enc, &p.tmDn, d_in[9], 3584, 1024, 8, 256, false);
  make_tm(enc, &p.tmY, (char*)sc + offsetof(Scratch, ypart), 8 * NSRC, 256, 2 * NSRC, 8, false);
  p.x = x; p.Dre = (const bf16*)d_in[3]; p.Dim = (const bf16*)d_in[4];
  p.wr = (const bf16*)d_in[6]; p.wdown = (const bf16*)d_in[9]; p.wgate = (const bf16*)d_in[7]; p.wup = (const bf16*)d_in[8]; p.Wre = (const bf16*)d_in[1]; p.Wim = (const bf16*)d_in[2];
  p.out = (bf16*)d_out; p.sc = (Scratch*)sc;
  if (map == 1) fnet_moe_kernel<1><<<NGRID, NTHR, SMEM_TOTAL>>>(p);
  else fnet_moe_kernel<0><<<NGRID, NTHR, SMEM_TOTAL>>>(p);
}
```

```cpp
#include <cuda.h>
#include <cuda_runtime.h>
#include <cuda_bf16.h>
#include <stdint.h>
#include <stddef.h>
#include <type_traits>

typedef __nv_bfloat16 bf16;

constexpr int NGRID = 132, NTHR = 384;
__device__ __forceinline__ int k_col(int tau, int j) { return (tau * 256 + (j < 4 ? j * 64 : (j - 3) * 256)) & 2047; }
__device__ __forceinline__ int k_next(int c, int j) { return (c + (j < 11 ? 256 : j == 11 ? 576 : (c & 192) == 192 ? 128 : 64)) & 2047; }
constexpr int A_BYTES = 128 * 64 * 2;
constexpr int B_BYTES = 256 * 64 * 2;
constexpr int ST_BYTES = A_BYTES + B_BYTES;
constexpr int OFF_AUX = 4 * ST_BYTES;
constexpr int OFF_BAR = OFF_AUX + 32768;
constexpr int OFF_XS = OFF_BAR + 256;
constexpr int OFF_WR = OFF_XS + 2048;
constexpr int OFF_REM = OFF_WR + 256;
constexpr int OFF_INFO = OFF_REM + 256;
constexpr int SMEM_TOTAL = OFF_INFO + 256;
constexpr int INFO_WSUM = OFF_INFO, INFO_TAG = OFF_INFO + 4, INFO_KEY = OFF_INFO + 8, INFO_CAND = OFF_INFO + 16, INFO_LN = OFF_INFO + 32, INFO_ONES = OFF_INFO + 48, INFO_DS = OFF_INFO + 64, INFO_DS2 = OFF_INFO + 192;
constexpr int OFF_RS = OFF_XS;
constexpr int OFF_WC = OFF_AUX;
constexpr int OFF_EXA = OFF_AUX + 4096;
constexpr int OFF_EXB = OFF_AUX + 6144;
__host__ __device__ constexpr int off_stage(int c) { return c == 1 ? OFF_AUX + 16384 : c * ST_BYTES; }
constexpr int OFF_RECV = A_BYTES;
constexpr int NSRC = 112;
enum { B_FULL = 0,
       B_EMPTY = 4,
       B_ALL = 6,
       B_EP = 8,
       B_AW = 16,
       B_STAT = 24, B_WC = 25, B_CD = 26, B_CH = 27, B_INFO = 28, B_PEER = 29,
       B_XCH = 30,
       B_GUX = (OFF_INFO + 128 - OFF_BAR) / 8,
       B_SD = B_GUX + 1,
       B_E23 = B_GUX + 5 };
enum { NB_TURN0 = 1, NB_TURN1 = 2, NB_BOTH = 3, NB_AUX = 4, NB_H = 5, NB_SEL = 6, NB_END = 7 };

struct Scratch;
struct Params {
  Scratch* sc; const bf16* wr; const bf16* x; const bf16* Dre; const bf16* Dim; const bf16* Wre; const bf16* Wim;
  const bf16* wgate; const bf16* wup; const bf16* wdown; bf16* out;
  CUtensorMap tmX, tmD0, tmD1, tmW0, tmW1, tmAbS, tmAbL, tmG, tmU, tmDn, tmY;
};

__device__ __align__(1024) bf16 g_abT[2048 * 2048];
struct Scratch {
  alignas(128) uint4 xz[2048];
  alignas(128) uint2 dsum[2048];
  alignas(128) uint32_t abflag[128 * 4 * 32];
  alignas(128) uint32_t abdone[128 * 2 * 32];
  alignas(128) uint2 u[4 * 512];
  alignas(128) uint2 cl[128 * 16];
  alignas(128) uint4 cpart[4 * 16 * 512];
  alignas(128) uint2 ch[8 * 512];
  alignas(128) uint4 cs[128 * 8];
  alignas(128) uint4 ypart[4 * NSRC * 64];
  alignas(128) uint4 hstat[16 * 8 * 128];
  alignas(128) uint2 rdone[128];
  alignas(128) uint2 key[128];
  alignas(128) uint2 hrow[128 * 512];
  alignas(128) uint2 fpart[8 * 1024];
  alignas(128) uint32_t epoch;
};
__device__ Scratch g_sc;

#define SPIN_LIMIT (1u << 17)
constexpr uint32_t ST1_CLK = 1200, ST_GAP = 600, U_CLK = 3700, Z_CLK = 9000;
constexpr uint32_t XS_DELAY = 300, CP_DELAY = 1500, CS_DELAY = 800;
constexpr uint32_t PUB_PACE = 1000, UNIT_PACE = 1600, ROW_CLK = 21000;
constexpr int LO_NS = 250, ALL_NS = 400;
__device__ __forceinline__ uint32_t smem_u32(const void* p) { return (uint32_t)__cvta_generic_to_shared(p); }
__device__ __forceinline__ uint32_t clk32() { uint32_t c; asm volatile("mov.u32 %0, %%clock;" : "=r"(c)); return c; }
__device__ __forceinline__ uint32_t zero_here() { uint64_t c; asm volatile("mov.u64 %0, %%clock64;" : "=l"(c) :: "memory"); return (uint32_t)(c >> 32) & blockIdx.y; }
__device__ __forceinline__ uint32_t uniform_zero_here() { uint32_t c; asm volatile("mov.u32 %0, %%clock;" : "=r"(c) :: "memory"); return c & blockIdx.y; }
__device__ __forceinline__ void wait_clk(uint32_t t0, uint32_t dt) {
  asm volatile("{\n.reg .pred p;\n.reg .u32 c;\nLOOP:\nmov.u32 c, %%clock;\nsub.u32 c, c, %0;\nsetp.lt.u32 p, c, %1;\n@p nanosleep.u32 100;\n@p bra LOOP;\n}\n" :: "r"(t0), "r"(dt) : "memory");
}
__device__ __forceinline__ void mbar_init(uint32_t bar, uint32_t cnt) { asm volatile("mbarrier.init.shared::cta.b64 [%0], %1;" :: "r"(bar), "r"(cnt) : "memory"); }
__device__ __forceinline__ void mbar_expect_tx(uint32_t bar, uint32_t bytes) { asm volatile("mbarrier.arrive.expect_tx.shared::cta.b64 _, [%0], %1;" :: "r"(bar), "r"(bytes) : "memory"); }
__device__ __forceinline__ void mbar_arrive(uint32_t bar) { asm volatile("mbarrier.arrive.shared::cta.b64 _, [%0];" :: "r"(bar) : "memory"); }
__device__ __forceinline__ void mbar_arrive_remote(uint32_t cluster_addr) { asm volatile("mbarrier.arrive.shared::cluster.b64 _, [%0];" :: "r"(cluster_addr) : "memory"); }
__device__ __forceinline__ void mbar_wait(uint32_t bar, uint32_t parity) {
  asm volatile("{\n.reg .pred p;\nLOOP:\nmbarrier.try_wait.parity.shared::cta.b64 p, [%0], %1;\n@!p bra LOOP;\n}\n" :: "r"(bar), "r"(parity) : "memory");
}
__device__ __forceinline__ void tma_load_2d(uint32_t dst, const CUtensorMap* tm, uint32_t bar, int c0, int c1) {
  asm volatile("cp.async.bulk.tensor.2d.shared::cluster.global.mbarrier::complete_tx::bytes [%0], [%1, {%3, %4}], [%2];"
    :: "r"(dst), "l"(tm), "r"(bar), "r"(c0), "r"(c1) : "memory");
}
__device__ __forceinline__ void tma_load_2d_hint(uint32_t dst, const CUtensorMap* tm, uint32_t bar, int c0, int c1, uint64_t pol) {
  asm volatile("cp.async.bulk.tensor.2d.shared::cluster.global.mbarrier::complete_tx::bytes.L2::cache_hint [%0], [%1, {%3, %4}], [%2], %5;"
    :: "r"(dst), "l"(tm), "r"(bar), "r"(c0), "r"(c1), "l"(pol) : "memory");
}
__device__ __forceinline__ uint64_t policy_evict_first() { uint64_t p; asm volatile("createpolicy.fractional.L2::evict_first.b64 %0, 1.0;" : "=l"(p)); return p; }
__device__ __forceinline__ void tma_store_2d(const CUtensorMap* tm, uint32_t src, int c0, int c1) {
  asm volatile("cp.async.bulk.tensor.2d.global.shared::cta.bulk_group [%0, {%2, %3}], [%1];" :: "l"(tm), "r"(src), "r"(c0), "r"(c1) : "memory");
}
__device__ __forceinline__ void bulk_load(uint32_t dst, const void* src, uint32_t bytes, uint32_t bar) {
  asm volatile("cp.async.bulk.shared::cluster.global.mbarrier::complete_tx::bytes [%0], [%1], %2, [%3];" :: "r"(dst), "l"(src), "r"(bytes), "r"(bar) : "memory");
}
__device__ __forceinline__ void prefetch_l2(const void* p) { asm volatile("prefetch.global.L2 [%0];" :: "l"(p)); }
__device__ __forceinline__ void bulk_commit() { asm volatile("cp.async.bulk.commit_group;" ::: "memory"); }
__device__ __forceinline__ void bulk_wait_all() { asm volatile("cp.async.bulk.wait_group 0;" ::: "memory"); }
__device__ __forceinline__ void fence_async_smem() { asm volatile("fence.proxy.async.shared::cta;" ::: "memory"); }
__device__ __forceinline__ void wgmma_fence() { asm volatile("wgmma.fence.sync.aligned;" ::: "memory"); }
__device__ __forceinline__ void wgmma_commit() { asm volatile("wgmma.commit_group.sync.aligned;" ::: "memory"); }
template<int N> __device__ __forceinline__ void wgmma_wait() { asm volatile("wgmma.wait_group.sync.aligned %0;" :: "n"(N) : "memory"); }
__device__ __forceinline__ void bar_sync(int id, int n) { asm volatile("bar.sync %0, %1;" :: "r"(id), "r"(n) : "memory"); }
__device__ __forceinline__ void bar_arrive(int id, int n) { asm volatile("bar.arrive %0, %1;" :: "r"(id), "r"(n) : "memory"); }
__device__ __forceinline__ void cluster_wait() { asm volatile("barrier.cluster.wait.aligned;" ::: "memory"); }
template<int R> __device__ __forceinline__ void reg_inc() { asm volatile("setmaxnreg.inc.sync.aligned.u32 %0;" :: "n"(R)); }
template<int R> __device__ __forceinline__ void reg_dec() { asm volatile("setmaxnreg.dec.sync.aligned.u32 %0;" :: "n"(R)); }
__device__ __forceinline__ bool elect_one() {
  uint32_t p;
  asm volatile("{\n.reg .pred q;\nelect.sync _|q, 0xffffffff;\nselp.u32 %0, 1, 0, q;\n}\n" : "=r"(p));
  return p != 0;
}
__device__ __forceinline__ uint32_t mapa(uint32_t addr, uint32_t cta) { uint32_t r; asm volatile("mapa.shared::cluster.u32 %0, %1, %2;" : "=r"(r) : "r"(addr), "r"(cta)); return r; }
__device__ __forceinline__ void st_async_v4(uint32_t addr, uint32_t bar, uint32_t a, uint32_t b, uint32_t c, uint32_t d) {
  asm volatile("st.async.weak.shared::cluster.mbarrier::complete_tx::bytes.v4.b32 [%0], {%2, %3, %4, %5}, [%1];" :: "r"(addr), "r"(bar), "r"(a), "r"(b), "r"(c), "r"(d) : "memory");
}
__device__ __forceinline__ void st_async_b32(uint32_t addr, uint32_t bar, uint32_t a) {
  asm volatile("st.async.weak.shared::cluster.mbarrier::complete_tx::bytes.b32 [%0], %2, [%1];" :: "r"(addr), "r"(bar), "r"(a) : "memory");
}
__device__ __forceinline__ void stsm_x4(uint32_t addr, uint32_t a, uint32_t b, uint32_t c, uint32_t d) {
  asm volatile("stmatrix.sync.aligned.m8n8.x4.shared.b16 [%0], {%1, %2, %3, %4};" :: "r"(addr), "r"(a), "r"(b), "r"(c), "r"(d) : "memory");
}
__device__ __forceinline__ void stsm_x4_t(uint32_t addr, uint32_t a, uint32_t b, uint32_t c, uint32_t d) {
  asm volatile("stmatrix.sync.aligned.m8n8.x4.trans.shared.b16 [%0], {%1, %2, %3, %4};" :: "r"(addr), "r"(a), "r"(b), "r"(c), "r"(d) : "memory");
}
__device__ __forceinline__ uint4 lds128(uint32_t addr) { uint4 v; asm volatile("ld.shared.v4.b32 {%0, %1, %2, %3}, [%4];" : "=r"(v.x), "=r"(v.y), "=r"(v.z), "=r"(v.w) : "r"(addr) : "memory"); return v; }
extern __shared__ __align__(1024) uint8_t smem_raw[];
template<class T> __device__ __forceinline__ T& SM(int off) { return *reinterpret_cast<T*>(smem_raw + off); }
__device__ __forceinline__ uint4 ldg_nc128(const void* p) { uint4 v; asm volatile("ld.global.nc.v4.b32 {%0, %1, %2, %3}, [%4];" : "=r"(v.x), "=r"(v.y), "=r"(v.z), "=r"(v.w) : "l"(p)); return v; }
__device__ __forceinline__ uint4 ldg128(const void* p) { uint4 v; asm volatile("ld.global.L1::no_allocate.v4.b32 {%0, %1, %2, %3}, [%4];" : "=r"(v.x), "=r"(v.y), "=r"(v.z), "=r"(v.w) : "l"(p) : "memory"); return v; }
__device__ __forceinline__ void pkt_st128(void* p, uint32_t a, uint32_t b, uint32_t c, uint32_t d) {
  asm volatile("{\n.reg .b128 v;\n.reg .b64 lo, hi;\nmov.b64 lo, {%1, %2};\nmov.b64 hi, {%3, %4};\nmov.b128 v, {lo, hi};\nst.relaxed.gpu.global.b128 [%0], v;\n}\n"
    :: "l"(p), "r"(a), "r"(b), "r"(c), "r"(d) : "memory");
}
__device__ __forceinline__ uint4 pkt_ld128(const void* p) {
  uint4 r;
  asm volatile("{\n.reg .b128 v;\n.reg .b64 lo, hi;\nld.relaxed.gpu.global.b128 v, [%4];\nmov.b128 {lo, hi}, v;\nmov.b64 {%0, %1}, lo;\nmov.b64 {%2, %3}, hi;\n}\n"
    : "=r"(r.x), "=r"(r.y), "=r"(r.z), "=r"(r.w) : "l"(p) : "memory");
  return r;
}
__device__ __forceinline__ void pkt_st64(void* p, uint32_t a, uint32_t b) {
  asm volatile("{\n.reg .b64 v;\nmov.b64 v, {%1, %2};\nst.relaxed.gpu.global.b64 [%0], v;\n}\n" :: "l"(p), "r"(a), "r"(b) : "memory");
}
__device__ __forceinline__ uint2 pkt_ld64(const void* p) {
  uint2 r;
  asm volatile("{\n.reg .b64 v;\nld.relaxed.gpu.global.b64 v, [%2];\nmov.b64 {%0, %1}, v;\n}\n" : "=r"(r.x), "=r"(r.y) : "l"(p) : "memory");
  return r;
}
__device__ __forceinline__ uint32_t ld_relaxed32(const void* p) { uint32_t v; asm volatile("ld.relaxed.gpu.global.b32 %0, [%1];" : "=r"(v) : "l"(p) : "memory"); return v; }
__device__ __forceinline__ uint32_t ld_acquire32(const void* p) { uint32_t v; asm volatile("ld.acquire.gpu.global.b32 %0, [%1];" : "=r"(v) : "l"(p) : "memory"); return v; }
__device__ __forceinline__ void st_relaxed32(void* p, uint32_t v) { asm volatile("st.relaxed.gpu.global.b32 [%0], %1;" :: "l"(p), "r"(v) : "memory"); }
__device__ __forceinline__ uint32_t poll64(const void* p, uint32_t tag, int ns) {
  uint2 v; uint32_t n = 0;
  bool more;
#pragma unroll 1
  do {
    v = pkt_ld64(p);
    more = v.y != tag && ++n < SPIN_LIMIT;
    if (more) { __nanosleep(ns); }
  } while (more);
  return v.x;
}
__device__ __forceinline__ uint32_t poll64_warp(const void* p, uint32_t tag, int ns) {
  uint2 v; uint32_t n = 0;
  bool more;
#pragma unroll 1
  do {
    v = pkt_ld64(p);
    more = !(__all_sync(0xffffffffu, v.y == tag)) && ++n < SPIN_LIMIT;
    if (more) { __nanosleep(ns); }
  } while (more);
  return v.x;
}
__device__ __forceinline__ uint32_t code_of(uint32_t tag) { return tag % 3u + 1u; }
__device__ __forceinline__ uint32_t with_bit(uint32_t v, uint32_t bit) { return (v & ~1u) | (bit & 1u); }
__device__ __forceinline__ uint32_t with_bit(float v, uint32_t bit) { return with_bit(__float_as_uint(v), bit); }
__device__ __forceinline__ float no_bit(uint32_t v) { return __uint_as_float(v & ~1u); }
__device__ __forceinline__ void chk(uint32_t& bad, uint32_t a, uint32_t want) { bad |= a ^ want; asm("" : "+r"(bad)); }
__device__ __forceinline__ void chk_code(uint32_t& bad, const uint4& v, uint32_t c0, uint32_t c1) { chk(bad, v.x, c0); chk(bad, v.y, c1); chk(bad, v.z, c0); chk(bad, v.w, c1); }
__device__ __forceinline__ uint32_t pack_bf16(float lo, float hi) { uint32_t r; asm("cvt.rn.bf16x2.f32 %0, %1, %2;" : "=r"(r) : "f"(hi), "f"(lo)); return r; }
__device__ __forceinline__ float bf_lo(uint32_t v) { return __uint_as_float(v << 16); }
__device__ __forceinline__ float bf_hi(uint32_t v) { return __uint_as_float(v & 0xFFFF0000u); }
__device__ __forceinline__ float bf16r(float x) { return __uint_as_float(pack_bf16(0.f, x)); }
__device__ __forceinline__ void st_bf16(bf16* p, float x) { *reinterpret_cast<uint16_t*>(p) = (uint16_t)pack_bf16(x, 0.f); }
__device__ __forceinline__ float fast_rcp(float x) { float r; asm("rcp.approx.ftz.f32 %0, %1;" : "=f"(r) : "f"(x)); return r; }
__device__ __forceinline__ float ldbf(const bf16* p) { return __bfloat162float(*p); }
__device__ __forceinline__ uint32_t badd2(uint32_t a, uint32_t b) { uint32_t r; asm("add.rn.bf16x2 %0, %1, %2;" : "=r"(r) : "r"(a), "r"(b)); return r; }
__device__ __forceinline__ uint32_t bfma2(uint32_t a, uint32_t b, uint32_t c) { uint32_t r; asm("fma.rn.bf16x2 %0, %1, %2, %3;" : "=r"(r) : "r"(a), "r"(b), "r"(c)); return r; }
__device__ __forceinline__ float warp_sum(float v) {
#pragma unroll
  for (int o = 16; o > 0; o >>= 1) v += __shfl_xor_sync(0xffffffffu, v, o);
  return v;
}
template<int N> __device__ __forceinline__ void fold(float* v, int o, int lane) {
  const bool up = lane & o;
#pragma unroll
  for (int i = 0; i < N / 2; i++) {
    const float keep = up ? v[N / 2 + i] : v[i], send = up ? v[i] : v[N / 2 + i];
    v[i] = keep + __shfl_xor_sync(0xffffffffu, send, o);
  }
}
__device__ __forceinline__ uint32_t make_key(float r_bf, int row) {
  const uint32_t u = __float_as_uint(r_bf);
  return (((u & 0x80000000u) ? ~u : (u | 0x80000000u)) & 0xFFFF0000u) | (0xFFFFu - (uint32_t)row);
}
__device__ __forceinline__ int key_row(uint32_t key) { return (0xFFFF - (int)(key & 0xFFFFu)) & 2047; }
__device__ __forceinline__ float key_val(uint32_t key) { const uint32_t o = key & 0xFFFF0000u; return __uint_as_float((o & 0x80000000u) ? (o & 0x7FFFFFFFu) : (~o & 0xFFFF0000u)); }
__device__ __forceinline__ float ref_sd(float var) { float r; asm("sqrt.approx.ftz.f32 %0, %1;" : "=f"(r) : "f"(bf16r(bf16r(var) + 1e-5f))); return bf16r(r); }
__device__ __forceinline__ uint64_t make_desc(uint32_t addr) { return (uint64_t)((addr & 0x3FFFF) >> 4) | ((uint64_t)64 << 32) | ((uint64_t)1 << 62); }
__device__ __forceinline__ uint64_t make_desc_noswz(uint32_t addr) { return (uint64_t)((addr & 0x3FFFF) >> 4) | ((uint64_t)8 << 32); }
#define ACC8(d, o) "+f"(d[o]), "+f"(d[o + 1]), "+f"(d[o + 2]), "+f"(d[o + 3]), "+f"(d[o + 4]), "+f"(d[o + 5]), "+f"(d[o + 6]), "+f"(d[o + 7])
#define ACC64(d, o) ACC8(d, o), ACC8(d, o + 8), ACC8(d, o + 16), ACC8(d, o + 24), ACC8(d, o + 32), ACC8(d, o + 40), ACC8(d, o + 48), ACC8(d, o + 56)
#define REGS64 "%0, %1, %2, %3, %4, %5, %6, %7, %8, %9, %10, %11, %12, %13, %14, %15, %16, %17, %18, %19, %20, %21, %22, %23, %24, %25, %26, %27, %28, %29, %30, %31, " \
    "%32, %33, %34, %35, %36, %37, %38, %39, %40, %41, %42, %43, %44, %45, %46, %47, %48, %49, %50, %51, %52, %53, %54, %55, %56, %57, %58, %59, %60, %61, %62, %63"
#define REGS128 REGS64 ", %64, %65, %66, %67, %68, %69, %70, %71, %72, %73, %74, %75, %76, %77, %78, %79, %80, %81, %82, %83, %84, %85, %86, %87, %88, %89, %90, %91, %92, %93, %94, %95, " \
    "%96, %97, %98, %99, %100, %101, %102, %103, %104, %105, %106, %107, %108, %109, %110, %111, %112, %113, %114, %115, %116, %117, %118, %119, %120, %121, %122, %123, %124, %125, %126, %127"
__device__ __forceinline__ void wgmma_n256(float (&d)[128], uint64_t da, uint64_t db) {
  asm volatile("wgmma.mma_async.sync.aligned.m64n256k16.f32.bf16.bf16 {" REGS128 "}, %128, %129, 1, 1, 1, 0, 0;\n"
    : ACC64(d, 0), ACC64(d, 64) : "l"(da), "l"(db));
}
#define OUT8(d, o) "=f"(d[o]), "=f"(d[o + 1]), "=f"(d[o + 2]), "=f"(d[o + 3]), "=f"(d[o + 4]), "=f"(d[o + 5]), "=f"(d[o + 6]), "=f"(d[o + 7])
#define OUT64(d, o) OUT8(d, o), OUT8(d, o + 8), OUT8(d, o + 16), OUT8(d, o + 24), OUT8(d, o + 32), OUT8(d, o + 40), OUT8(d, o + 48), OUT8(d, o + 56)
__device__ __forceinline__ void wgmma_n256_rs_init(float (&d)[128], const uint32_t* a, uint64_t db) {
  asm volatile("wgmma.mma_async.sync.aligned.m64n256k16.f32.bf16.bf16 {" REGS128 "}, {%128, %129, %130, %131}, %132, 0, 1, 1, 0;\n"
    : OUT64(d, 0), OUT64(d, 64) : "r"(a[0]), "r"(a[1]), "r"(a[2]), "r"(a[3]), "l"(db));
}
__device__ __forceinline__ void wgmma_n256_rs(float (&d)[128], const uint32_t* a, uint64_t db) {
  asm volatile("wgmma.mma_async.sync.aligned.m64n256k16.f32.bf16.bf16 {" REGS128 "}, {%128, %129, %130, %131}, %132, 1, 1, 1, 0;\n"
    : ACC64(d, 0), ACC64(d, 64) : "r"(a[0]), "r"(a[1]), "r"(a[2]), "r"(a[3]), "l"(db));
}
template<int ACCUM> __device__ __forceinline__ void wgmma_n8_rs(float (&d)[4], const uint32_t* a, uint64_t db) {
  asm volatile("wgmma.mma_async.sync.aligned.m64n8k16.f32.bf16.bf16 {%0, %1, %2, %3}, {%4, %5, %6, %7}, %8, %9, 1, 1, 0;\n"
    : "+f"(d[0]), "+f"(d[1]), "+f"(d[2]), "+f"(d[3]) : "r"(a[0]), "r"(a[1]), "r"(a[2]), "r"(a[3]), "l"(db), "n"(ACCUM));
}
__device__ __forceinline__ void wgmma_n8(float (&d)[4], uint64_t da, uint64_t db) {
  asm volatile("wgmma.mma_async.sync.aligned.m64n8k16.f32.bf16.bf16 {%0, %1, %2, %3}, %4, %5, 1, 1, 1, 0, 0;\n"
    : "+f"(d[0]), "+f"(d[1]), "+f"(d[2]), "+f"(d[3]) : "l"(da), "l"(db));
}
__device__ __forceinline__ void wgmma_n128(float (&d)[64], uint64_t da, uint64_t db) {
  asm volatile("wgmma.mma_async.sync.aligned.m64n128k16.f32.bf16.bf16 {" REGS64 "}, %64, %65, 1, 1, 1, 0, 0;\n" : ACC64(d, 0) : "l"(da), "l"(db));
}
#define ACC32(d, o) ACC8(d, o), ACC8(d, o + 8), ACC8(d, o + 16), ACC8(d, o + 24)
#define REGS32 "%0, %1, %2, %3, %4, %5, %6, %7, %8, %9, %10, %11, %12, %13, %14, %15, %16, %17, %18, %19, %20, %21, %22, %23, %24, %25, %26, %27, %28, %29, %30, %31"
#define REGS96 REGS64 ", %64, %65, %66, %67, %68, %69, %70, %71, %72, %73, %74, %75, %76, %77, %78, %79, %80, %81, %82, %83, %84, %85, %86, %87, %88, %89, %90, %91, %92, %93, %94, %95"
__device__ __forceinline__ void wgmma_part(float (&d)[32], uint64_t da, uint64_t db) {
  asm volatile("wgmma.mma_async.sync.aligned.m64n64k16.f32.bf16.bf16 {" REGS32 "}, %32, %33, 1, 1, 1, 0, 0;\n" : ACC32(d, 0) : "l"(da), "l"(db));
}
__device__ __forceinline__ void wgmma_part(float (&d)[96], uint64_t da, uint64_t db) {
  asm volatile("wgmma.mma_async.sync.aligned.m64n192k16.f32.bf16.bf16 {" REGS96 "}, %96, %97, 1, 1, 1, 0, 0;\n" : ACC64(d, 0), ACC32(d, 64) : "l"(da), "l"(db));
}
template<int N> __device__ __forceinline__ void fence_regs(float (&d)[N]) {
#pragma unroll
  for (int i = 0; i < N; i++) asm volatile("" : "+f"(d[i]) :: "memory");
}
__device__ __forceinline__ void mma16816(float (&c)[4], uint32_t a0, uint32_t a1, uint32_t a2, uint32_t a3, uint32_t b0, uint32_t b1) {
  asm volatile("mma.sync.aligned.m16n8k16.row.col.f32.bf16.bf16.f32 {%0, %1, %2, %3}, {%4, %5, %6, %7}, {%8, %9}, {%0, %1, %2, %3};"
               : "+f"(c[0]), "+f"(c[1]), "+f"(c[2]), "+f"(c[3]) : "r"(a0), "r"(a1), "r"(a2), "r"(a3), "r"(b0), "r"(b1));
}
__device__ __forceinline__ void fma8(float* acc, const uint4& v, float x) {
  acc[0] = fmaf(bf_lo(v.x), x, acc[0]); acc[1] = fmaf(bf_hi(v.x), x, acc[1]); acc[2] = fmaf(bf_lo(v.y), x, acc[2]); acc[3] = fmaf(bf_hi(v.y), x, acc[3]);
  acc[4] = fmaf(bf_lo(v.z), x, acc[4]); acc[5] = fmaf(bf_hi(v.z), x, acc[5]); acc[6] = fmaf(bf_lo(v.w), x, acc[6]); acc[7] = fmaf(bf_hi(v.w), x, acc[7]);
}
template<int PITCH> __device__ __forceinline__ void gemv8x8(float (&acc)[8], uint32_t addr, const float (&x)[8]) {
  uint4 v[2][2];
  v[0][0] = lds128(addr); v[0][1] = lds128(addr + PITCH);
#pragma unroll
  for (int b = 0; b < 4; b++) {
    if (b < 3) { v[(b + 1) & 1][0] = lds128(addr + (2 * b + 2) * PITCH); v[(b + 1) & 1][1] = lds128(addr + (2 * b + 3) * PITCH); }
    acc[0] += __uint_as_float(zero_here());
#pragma unroll
    for (int c = 0; c < 4; c++) {
      if (c == 2) acc[4] += __uint_as_float(zero_here());
#pragma unroll
      for (int r = 0; r < 2; r++) {
        const uint4& q = v[b & 1][r];
        const uint32_t u = c == 0 ? q.x : c == 1 ? q.y : c == 2 ? q.z : q.w;
        acc[2 * c] = fmaf(bf_lo(u), x[2 * b + r], acc[2 * c]); acc[2 * c + 1] = fmaf(bf_hi(u), x[2 * b + r], acc[2 * c + 1]);
      }
    }
  }
}
__device__ __forceinline__ float swiglu(float g, float u) {
  g = bf16r(g); u = bf16r(u);
  return bf16r(bf16r(g * fast_rcp(1.f + __expf(-g))) * u);
}

#define CT(slot) do {} while (0)
#define TIM(slot) do {} while (0)

constexpr int H_BUF0 = 0, H_BUF1 = 16384, H_RED = 32768, H_KEYS = H_RED + 1024, H_ROW = H_KEYS + 1024, H_ACT = H_ROW + 8192, H_PART = H_ACT + 4096;
__device__ __forceinline__ void hsync() { bar_sync(NB_H, 256); }
template<int N> __device__ __forceinline__ void block_sum(float (&v)[N], int warp, int lane) {
#pragma unroll
  for (int i = 0; i < N; i++) v[i] = warp_sum(v[i]);
  hsync();
  if (lane == 0) {
#pragma unroll
    for (int i = 0; i < N; i++) SM<float>(H_RED + (i * 8 + warp) * 4) = v[i];
  }
  hsync();
#pragma unroll
  for (int i = 0; i < N; i++) {
    const float4 a = SM<float4>(H_RED + i * 32), b = SM<float4>(H_RED + i * 32 + 16);
    v[i] = ((a.x + a.y) + (a.z + a.w)) + ((b.x + b.y) + (b.z + b.w));
  }
}
__device__ __forceinline__ void fft_first(int j, float2 v0, float2 v1, float2 v2, float2 v3) {
  const float2 a = make_float2(v0.x + v2.x, v0.y + v2.y), b = make_float2(v0.x - v2.x, v0.y - v2.y);
  const float2 c = make_float2(v1.x + v3.x, v1.y + v3.y), d = make_float2(v1.y - v3.y, v3.x - v1.x);
  SM<float4>(H_BUF1 + j * 32) = make_float4(a.x + c.x, a.y + c.y, b.x + d.x, b.y + d.y);
  SM<float4>(H_BUF1 + j * 32 + 16) = make_float4(a.x - c.x, a.y - c.y, b.x - d.x, b.y - d.y);
}
template<int NB> __device__ __forceinline__ void fft_passes(int tid) {
  constexpr int q = 256 * NB;
#pragma unroll 1
  for (int ps = 1; ps < 5; ps++) {
    const int ns = 1 << (2 * ps), k = tid & (ns - 1);
    float s1, c1;
    __sincosf(-1.57079632679f * __fdividef((float)k, (float)ns), &s1, &c1);
    const float c2 = c1 * c1 - s1 * s1, s2 = 2.f * c1 * s1, c3 = c1 * c2 - s1 * s2, s3 = c1 * s2 + s1 * c2;
    hsync();
#pragma unroll
    for (int i = 0; i < NB; i++) {
      const int j = tid + 256 * i;
      const float2* in = &SM<float2>((ps & 1) ? H_BUF1 : H_BUF0);
      float2* o = &SM<float2>((ps & 1) ? H_BUF0 : H_BUF1) + (j - k) * 4 + k;
      const float2 v0 = in[j], x1 = in[j + q], x2 = in[j + 2 * q], x3 = in[j + 3 * q];
      const float2 v1 = make_float2(x1.x * c1 - x1.y * s1, x1.x * s1 + x1.y * c1);
      const float2 v2 = make_float2(x2.x * c2 - x2.y * s2, x2.x * s2 + x2.y * c2);
      const float2 v3 = make_float2(x3.x * c3 - x3.y * s3, x3.x * s3 + x3.y * c3);
      const float2 a = make_float2(v0.x + v2.x, v0.y + v2.y), b = make_float2(v0.x - v2.x, v0.y - v2.y);
      const float2 c = make_float2(v1.x + v3.x, v1.y + v3.y), d = make_float2(v1.y - v3.y, v3.x - v1.x);
      o[0] = make_float2(a.x + c.x, a.y + c.y); o[ns] = make_float2(b.x + d.x, b.y + d.y);
      o[2 * ns] = make_float2(a.x - c.x, a.y - c.y); o[3 * ns] = make_float2(b.x - d.x, b.y - d.y);
    }
  }
  hsync();
}
template<int NR> __device__ __forceinline__ void ln_rows(const float (&h)[NR][4], float (&hn)[NR][4], int warp, int lane) {
  float s[NR], q[NR];
#pragma unroll
  for (int i = 0; i < NR; i++) s[i] = (h[i][0] + h[i][1]) + (h[i][2] + h[i][3]);
  block_sum(s, warp, lane);
#pragma unroll
  for (int i = 0; i < NR; i++) {
    s[i] *= 1.f / 1024.f; q[i] = 0.f;
#pragma unroll
    for (int z = 0; z < 4; z++) q[i] = fmaf(h[i][z] - s[i], h[i][z] - s[i], q[i]);
  }
  block_sum(q, warp, lane);
#pragma unroll
  for (int i = 0; i < NR; i++) {
    const float mb = bf16r(s[i]), inv = fast_rcp(ref_sd(q[i] * (1.f / 1024.f)));
#pragma unroll
    for (int z = 0; z < 4; z++) hn[i][z] = bf16r(bf16r(h[i][z] - mb) * inv);
  }
}
__device__ __forceinline__ float sigmoid_bf(float r) { return bf16r(fast_rcp(1.f + __expf(-r))); }
__device__ __forceinline__ float routed_out(float h, float hn, float y, float sig) { return h + bf16r(hn + bf16r(bf16r(y) * sig)); }

__device__ __forceinline__ void helper_cta(const Params& p, const int hi, const uint32_t t_entry) {
  const int tid = threadIdx.x, warp = tid >> 5, lane = tid & 31;
  const float w0 = ldbf(p.wr + tid), w1 = ldbf(p.wr + tid + 256), w2 = ldbf(p.wr + tid + 512), w3 = ldbf(p.wr + tid + 768), wf = ldbf(p.wr);
  const uint32_t tag = ld_relaxed32(&p.sc->epoch) + 1;
  fft_first(tid, make_float2(w0, 0.f), make_float2(w1, 0.f), make_float2(w2, 0.f), make_float2(w3, 0.f));
  fft_passes<1>(tid);
  const uint32_t c0 = code_of(tag), c1 = c0 >> 1;
  {
    const float off = wf - SM<float>(H_BUF1) * (1.f / 1024.f);
    const float4 v = SM<float4>(H_BUF1 + tid * 32), u = SM<float4>(H_BUF1 + tid * 32 + 16);
    pkt_st128(&p.sc->u[hi * 512 + ((tid & 192) + (tid & 1) * 32 + ((tid >> 1) & 31)) * 2], with_bit(pack_bf16((tid ? v.x : 0.f) - off, v.z - off), c0), with_bit(pack_bf16(v.y, v.w), c1),
              with_bit(pack_bf16(u.x - off, u.z - off), c0), with_bit(pack_bf16(u.y, u.w), c1));
    hsync();
  }
  if (tid == 0) TIM(0);
  {
    float tw[8];
#pragma unroll
    for (int i = 0; i < 4; i++) __sincosf((float)(tid + 256 * i) * (-6.28318530718f / 2048.f), &tw[2 * i], &tw[2 * i + 1]);
    wait_clk(t_entry, Z_CLK);
    uint2 z[8]; uint32_t n = 0;
    bool more;
#pragma unroll 1
    do {
      uint32_t bad = 0;
#pragma unroll
      for (int i = 0; i < 8; i++) z[i] = pkt_ld64(reinterpret_cast<const uint2*>(&p.sc->xz[tid]) + 512 * i + 1);
#pragma unroll
      for (int i = 0; i < 8; i++) chk(bad, z[i].y, tag);
      more = bad && ++n < SPIN_LIMIT;
      if (more) { __nanosleep(150); }
    } while (more);
#pragma unroll
    for (int i = 0; i < 2; i++)
      fft_first(tid + 256 * i, make_float2(bf_lo(z[i].x), bf_hi(z[i].x)), make_float2(bf_lo(z[i + 2].x), bf_hi(z[i + 2].x)),
                make_float2(bf_lo(z[i + 4].x), bf_hi(z[i + 4].x)), make_float2(bf_lo(z[i + 6].x), bf_hi(z[i + 6].x)));
    if (tid == 0) TIM(7);
    fft_passes<2>(tid);
    if (tid == 0) TIM(1);
    uint32_t k8[8];
#pragma unroll
    for (int i = 0; i < 4; i++) {
      const int k = tid + 256 * i;
      const float2 v0 = SM<float2>(H_BUF1 + k * 8), v1 = SM<float2>(H_BUF1 + (k + 1024) * 8);
      const float w = v1.x * tw[2 * i + 1] - v1.y * tw[2 * i];
      const uint32_t a = __float_as_uint(v0.x + w), b = __float_as_uint(v0.x - w);
      k8[2 * i] = (((a & 0x80000000u) ? ~a : (a | 0x80000000u)) & ~2047u) | k;
      k8[2 * i + 1] = (((b & 0x80000000u) ? ~b : (b | 0x80000000u)) & ~2047u) | (k + 1024);
    }
    uint32_t lim = 0xFFFFFFFFu;
#pragma unroll 1
    for (int r = 0; r < 4; r++) {
      uint32_t mx = 0;
#pragma unroll
      for (int i = 0; i < 8; i++) mx = max(mx, k8[i] <= lim ? k8[i] : 0u);
      mx = __reduce_max_sync(0xffffffffu, mx);
      if (lane == 0) SM<uint32_t>(H_KEYS + (warp * 4 + r) * 4) = mx;
      lim = mx - 1;
    }
    hsync();
    if (tid < 32) {
      const uint32_t me = SM<uint32_t>(H_KEYS + tid * 4);
      int rank = 0;
#pragma unroll
      for (int i = 0; i < 8; i++) { const uint4 o = SM<uint4>(H_KEYS + i * 16); rank += (o.x > me) + (o.y > me) + (o.z > me) + (o.w > me); }
      if (rank < 8) SM<uint16_t>(H_KEYS + 256 + rank * 2) = me & 2047u;
    }
    hsync();
    if (tid >= 128) pkt_st64(&p.sc->cl[(hi * 32 + ((tid - 128) >> 2)) * 16 + (tid & 3)], SM<uint32_t>(H_KEYS + 256 + (tid & 3) * 4), tag);
  }
  const uint32_t cpair = SM<uint32_t>(H_KEYS + 256 + hi * 4);
  const int ca = cpair & 2047, cb = (cpair >> 16) & 2047;
  if (tid < 128) prefetch_l2(((tid & 32) ? p.Wim : p.Wre) + (size_t)((tid & 64) ? cb : ca) * 2048 + lane * 64);
  if (tid == 0) TIM(2);
}

__device__ __noinline__ void slow_path(const Params& p, int grp, int eps, uint32_t tag, uint32_t key, int win, float mb, float inv) {
  const int tid = threadIdx.x, warp = tid >> 5, lane = tid & 31;
  uint32_t best = __reduce_max_sync(0xffffffffu, poll64(&p.sc->key[tid & 127], tag, 200));
  if (lane == 0) SM<uint32_t>(H_KEYS + warp * 4) = best;
  hsync();
  { const uint4 b4 = SM<uint4>(H_KEYS); best = max(max(b4.x, b4.y), max(b4.z, b4.w)); }
  const int tw = key_row(best), col = eps * 128 + (tid & 127);
  if ((tw >> 7) != grp) return;
  poll64(&p.sc->rdone[col >> 3], tag, 100);
  const uint32_t h0 = poll64(&p.sc->hrow[(tw >> 4) * 512 + 2 * tid], tag, 100), h1 = poll64(&p.sc->hrow[(tw >> 4) * 512 + 2 * tid + 1], tag, 100);
  float h[1][4] = {{bf_lo(h0), bf_hi(h0), bf_lo(h1), bf_hi(h1)}}, hn[1][4];
  ln_rows<1>(h, hn, warp, lane);
  SM<float4>(H_ROW + tid * 16) = make_float4(hn[0][0], hn[0][1], hn[0][2], hn[0][3]);
  SM<float4>(H_ROW + 4096 + tid * 16) = make_float4(h[0][0], h[0][1], h[0][2], h[0][3]);
  hsync();
#pragma unroll 1
  for (int ph = 0; ph < 2; ph++) {
    const int part = min(tid / 56, 3), fh = tid >> 7, len = ph ? 224 : 512, ld = ph ? 1024 : 3584;
    const bf16* wp = ph ? p.wdown + (eps * 448 + fh * 224) * 1024 + (tid & 127) * 8
                        : ((part & 1) ? p.wup : p.wgate) + (part >> 1) * 512 * 3584 + eps * 448 + min(tid - part * 56, 55) * 8;
    const int xo = ph ? H_ACT + fh * 224 * 4 : H_ROW + (part >> 1) * 2048;
    float acc[8] = {0.f, 0.f, 0.f, 0.f, 0.f, 0.f, 0.f, 0.f};
#pragma unroll 16
    for (int d = 0; d < (len & ~15); d++) fma8(acc, ldg_nc128(wp + d * ld), SM<float>(xo + d * 4));
    SM<float4>(H_PART + tid * 32) = make_float4(acc[0], acc[1], acc[2], acc[3]);
    SM<float4>(H_PART + tid * 32 + 16) = make_float4(acc[4], acc[5], acc[6], acc[7]);
    hsync();
    if (ph) break;
#pragma unroll 1
    for (int f = tid; f < 448; f += 256)
      SM<float>(H_ACT + f * 4) = swiglu(SM<float>(H_PART + f * 4) + SM<float>(H_PART + (896 + f) * 4), SM<float>(H_PART + (448 + f) * 4) + SM<float>(H_PART + (1344 + f) * 4));
    hsync();
  }
#pragma unroll 1
  for (int e = tid; e < 1024; e += 256) pkt_st64(&p.sc->fpart[eps * 1024 + e], __float_as_uint(SM<float>(H_PART + e * 4) + SM<float>(H_PART + (1024 + e) * 4)), tag);
  if (tid < 128) {
    float y = 0.f;
#pragma unroll 1
    for (int q = 0; q < 8; q++) y += __uint_as_float(poll64(&p.sc->fpart[q * 1024 + col], tag, 200));
    st_bf16(p.out + tw * 1024 + col, routed_out(SM<float>(H_ROW + 4096 + col * 4), SM<float>(H_ROW + col * 4), y, sigmoid_bf(key_val(best))));
    const uint32_t a = poll64(&p.sc->ch[win * 512 + (col >> 4) * 8 + (col & 7)], tag, 100);
    const float hc = (col & 8) ? bf_hi(a) : bf_lo(a);
    st_bf16(p.out + key_row(key) * 1024 + col, hc + bf16r(bf16r(hc - mb) * inv));
  }
}

template<int MAP>
__global__ void __cluster_dims__(2, 1, 1) __launch_bounds__(NTHR, 1)
fnet_moe_kernel(const __grid_constant__ Params p) {
  const CUtensorMap* tmX0 = &p.tmX;
  asm volatile("" : "+l"(tmX0));
  const uint32_t t_entry = clk32();
  uint32_t smid;
  asm("mov.u32 %0, %%smid;" : "=r"(smid));
  const int tpc = smid >> 1, m = blockIdx.x & 1;
  if (MAP == 1 ? tpc >= 64 : (tpc >> 1) == 30) {
    if (threadIdx.x < 256) helper_cta(p, (tpc & 1) * 2 + m, t_entry);
    return;
  }
  const uint32_t sb = smem_u32(smem_raw);
  const int tid = threadIdx.x, lane = tid & 31;
  const int e7 = ((tpc - 32) * 37) >> 8;
  const int tau = MAP == 1 || tpc < 32 ? (tpc & 7) : (tpc < 60 ? tpc - 31 - 7 * e7 : 0);
  const int eps = MAP == 1 || tpc < 32 ? (tpc >> 3) : (tpc < 60 ? 4 + e7 : tpc - 58);
  const int cid = tau * 16 + eps * 2 + m;
  auto BAR = [&](int i) { return sb + OFF_BAR + 8 * i; };
  const CUtensorMap* tmD = &p.tmD0 + m;

  if ((tid >> 5) == 4) {
    if (elect_one()) {
      mbar_init(BAR(B_FULL), 1);
      asm volatile("fence.mbarrier_init.release.cluster;" ::: "memory");
      mbar_expect_tx(BAR(B_FULL), ST_BYTES);
      tma_load_2d(sb, tmX0 + 1 + m, BAR(B_FULL), 0, eps * 128);
      tma_load_2d(sb + A_BYTES, tmX0, BAR(B_FULL), 0, tau * 256);
      TIM(0);
    }
  }
  const int warp = __shfl_sync(0xffffffffu, tid >> 5, 0);
  if (warp < 6 && warp != 4) {
    const int wv = warp;
    if (elect_one()) {
      const uint32_t b0 = BAR(wv < 4 ? 8 * wv : B_GUX);
#pragma unroll
      for (int i = 0; i < 8; i++)
        if (i || wv) mbar_init(b0 + 8 * i, wv == 1 || (wv == 3 && i == B_STAT - 24) ? 4 : wv == 3 && i == B_CD - 24 ? 2 : 1);
      asm volatile("fence.mbarrier_init.release.cluster;" ::: "memory");
      if (wv == 3) { mbar_expect_tx(BAR(B_XCH), 16384); mbar_expect_tx(BAR(B_XCH + 1), 16384); }
      if (wv == 5) mbar_expect_tx(BAR(B_GUX), 256);
    }
  }
  __syncthreads();
  asm volatile("barrier.cluster.arrive.relaxed.aligned;" ::: "memory");

  if (warp >= 8) {
    auto stage = [&](int k) {
      if (warp == 11) {
        if (elect_one()) {
          while (clk32() - t_entry < ST1_CLK + (k - 1) * ST_GAP) {}
          mbar_expect_tx(BAR(B_FULL + k), ST_BYTES);
          tma_load_2d(sb + k * ST_BYTES + A_BYTES, &p.tmX, BAR(B_FULL + k), k * 64, tau * 256);
          tma_load_2d(sb + k * ST_BYTES, tmD, BAR(B_FULL + k), k * 64, eps * 128);
          TIM(k);
        }
        __syncwarp();
      }
    };
    reg_dec<72>();
    const uint32_t epoch = ld_relaxed32(&p.sc->epoch + threadIdx.y);
    const uint4 wq = ldg128(p.wr + (tid & 127) * 8);
#pragma unroll 1
    for (int k = 1; k < 4; k++) stage(k);
    cluster_wait();
    const int cid0 = cid;
    const uint32_t tag0 = __shfl_sync(0xffffffffu, epoch, 0) + 1, sb0 = sb;
    int a, lane, j, cid, tau, eps, m, grp, abrow, fc, src;
    uint32_t tag, c0, c1, sb, buf, bar0;
    bool ffn;
    auto BAR = [&](int i) { return sb + OFF_BAR + 8 * i; };
    auto fresh_ids = [&]() {
      const uint32_t z = uniform_zero_here();
      uint32_t l; asm volatile("mov.u32 %0, %%laneid;" : "=r"(l));
      a = warp - 8 + z; lane = l; j = a * 32 + l;
      cid = cid0 + z; tau = cid >> 4; eps = (cid >> 1) & 7; m = cid & 1; grp = tau * 2 + m; abrow = m * 1024 + eps * 128;
      const int ef = tau ? eps : eps ^ 5;
      ffn = ef > 0; fc = (tau * 7 + ef - 1) * 64; src = (fc >> 5) + m;
      tag = tag0 + z; c0 = code_of(tag); c1 = c0 >> 1;
      sb = sb0 + z; buf = sb + OFF_AUX + a * 8192; bar0 = BAR(B_AW + 2 * a);
    };
    fresh_ids();
    {
      const float s = warp_sum(((bf_lo(wq.x) + bf_hi(wq.x)) + (bf_lo(wq.y) + bf_hi(wq.y))) + ((bf_lo(wq.z) + bf_hi(wq.z)) + (bf_lo(wq.w) + bf_hi(wq.w))));
      if ((j >> 4) == eps) SM<uint4>(OFF_WR + (j & 15) * 16) = wq;
      if (lane == 0) { SM<float>(INFO_DS + a * 4) = s; SM<uint32_t>(INFO_ONES + a * 4) = 0x3F803F80u; }
    }
    const bf16* xrows = p.x + (cid * 16 + a * 4) * 1024;
    const bf16* drows = (cid < 64 ? p.Dre : p.Dim) + ((cid & 63) * 16 + a * 4) * 1024;
    fresh_ids();
    {
      wait_clk(t_entry, U_CLK);
      uint4 u[8]; uint32_t n = 0;
      bool more;
#pragma unroll 1
      do {
        uint32_t bad = 0;
#pragma unroll
        for (int q = 0; q < 8; q++) u[q] = pkt_ld128(&p.sc->u[a * 512 + lane * 2] + q * 64);
        if (n == 0 && lane == 0) { mbar_expect_tx(bar0, 4096); bulk_load(buf, xrows, 4096, bar0); }
#pragma unroll
        for (int q = 0; q < 8; q++) chk_code(bad, u[q], c0, c1);
        more = __any_sync(0xffffffffu, bad & 1) && ++n < SPIN_LIMIT;
        if (more) { __nanosleep(200); }
      } while (more);
      if (j == 0) TIM(96);
      if (lane == 0) { mbar_expect_tx(bar0 + 8, 4096); bulk_load(buf + 4096, xrows + 2048, 4096, bar0 + 8); }
#pragma unroll
      for (int q = 0; q < 8; q++) { u[q].x &= ~1u; u[q].y &= ~1u; u[q].z &= ~1u; u[q].w &= ~1u; }
#pragma unroll 1
      for (int r2 = 0; r2 < 2; r2++) {
        float v8[8];
        mbar_wait(bar0 + r2 * 8, 0);
        if (lane == 0) TIM(140 + r2 * 4 + a);
#pragma unroll
        for (int r = 0; r < 2; r++) {
          float s0 = 0.f, s1 = 0.f, q0 = 0.f, q1 = 0.f;
          uint32_t zr = 0, zi = 0;
#pragma unroll
          for (int q = 0; q < 4; q++) {
            const uint4 v = lds128(buf + r2 * 4096 + r * 2048 + (q * 32 + lane) * 16);
            const uint32_t ww[4] = {v.x, v.y, v.z, v.w};
#pragma unroll
            for (int z = 0; z < 4; z++) {
              const float lo = bf_lo(ww[z]), hi = bf_hi(ww[z]);
              s0 += lo; s1 += hi; q0 = fmaf(lo, lo, q0); q1 = fmaf(hi, hi, q1);
            }
            zr = bfma2(v.x, u[2 * q].x, zr); zi = bfma2(v.x, u[2 * q].y, zi); zr = bfma2(v.y, u[2 * q].z, zr); zi = bfma2(v.y, u[2 * q].w, zi);
            zr = bfma2(v.z, u[2 * q + 1].x, zr); zi = bfma2(v.z, u[2 * q + 1].y, zi); zr = bfma2(v.w, u[2 * q + 1].z, zr); zi = bfma2(v.w, u[2 * q + 1].w, zi);
          }
          v8[4 * r] = s0 + s1; v8[4 * r + 1] = q0 + q1; v8[4 * r + 2] = bf_lo(zr) + bf_hi(zr); v8[4 * r + 3] = bf_lo(zi) + bf_hi(zi);
        }
        fold<8>(v8, 16, lane);
        if (lane == 0) { mbar_expect_tx(bar0 + r2 * 8, 4096); bulk_load(buf + r2 * 4096, drows + r2 * 2048, 4096, bar0 + r2 * 8); }
        fold<4>(v8, 8, lane); fold<2>(v8, 4, lane);
        v8[0] += __shfl_xor_sync(0xffffffffu, v8[0], 2);
        v8[0] += __shfl_xor_sync(0xffffffffu, v8[0], 1);
        SM<float>(OFF_REM + a * 64 + r2 * 32 + (lane >> 2) * 4) = v8[0];
        if (lane == 0) TIM(148 + r2 * 4 + a);
      }
    }
    bar_sync(NB_AUX, 128);
    fresh_ids();
    if (a == 0 && lane < 16) {
      const float4 v = SM<float4>(OFF_REM + lane * 16);
      const float mean = v.x * (1.f / 1024.f), rs = fast_rcp(ref_sd(fmaxf(v.y * (1.f / 1024.f) - mean * mean, 0.f)));
      pkt_st128(&p.sc->xz[cid * 16 + lane], __float_as_uint(bf16r(mean)) | (tag & 0xFFFFu), __float_as_uint(rs), pack_bf16(v.z * rs, v.w * rs), tag);
    }
    if (j == 32) { const float4 v = SM<float4>(INFO_DS); SM<float2>(INFO_WSUM) = make_float2((v.x + v.y) + (v.z + v.w), __uint_as_float(tag)); }
    if (j == 0) TIM(98);
#pragma unroll 1
    for (int r2 = 0; r2 < 2; r2++) {
      mbar_wait(bar0 + r2 * 8, 1);
      const uint32_t da = buf + r2 * 4096 + (lane >> 4) * 2048 + (lane & 15) * 16;
      uint4 dv[3] = {lds128(da), lds128(da + 256), make_uint4(0, 0, 0, 0)};
      float s0 = 0.f, s1 = 0.f;
#pragma unroll
      for (int q = 0; q < 8; q++) {
        if (q < 6) dv[(q + 2) % 3] = lds128(da + (q + 2) * 256);
        s0 += __uint_as_float(zero_here());
        const uint4 v = dv[q % 3];
        s0 += bf_lo(v.x); s1 += bf_hi(v.x); s0 += bf_lo(v.y); s1 += bf_hi(v.y); s0 += bf_lo(v.z); s1 += bf_hi(v.z); s0 += bf_lo(v.w); s1 += bf_hi(v.w);
      }
      s0 += s1;
#pragma unroll
      for (int o = 8; o > 0; o >>= 1) s0 += __shfl_xor_sync(0xffffffffu, s0, o);
      SM<float>(INFO_DS2 + (a * 4 + r2 * 2 + (lane >> 4)) * 4) = s0;
    }
    bar_sync(NB_AUX, 128);
    if (a == 1 && lane < 16) pkt_st64(&p.sc->dsum[cid * 16 + lane], SM<uint32_t>(INFO_DS2 + lane * 4), tag);
    if (j == 0) TIM(99);
    {
      wait_clk(clk32(), XS_DELAY);
      uint2 v0, v1, cs; uint32_t n = 0;
      const uint32_t t16 = tag & 0xFFFFu;
      bool more;
#pragma unroll 1
      do {
        v0 = pkt_ld64(&p.sc->xz[tau * 256 + j]); v1 = pkt_ld64(&p.sc->xz[tau * 256 + j] + 128); cs = pkt_ld64(&p.sc->dsum[m * 1024 + eps * 128 + j]);
        more = !(__all_sync(0xffffffffu, (v0.x & 0xFFFFu) == t16 && (v1.x & 0xFFFFu) == t16 && cs.y == tag)) && ++n < SPIN_LIMIT;
        if (more) { __nanosleep(200); }
      } while (more);
      const int ro = OFF_RS + ((j & 7) >> 1) * 272 + (j >> 3) * 8 + (j & 1) * 4;
      SM<uint32_t>(ro) = v0.y ^ (m << 31); SM<uint32_t>(ro + 128) = v1.y ^ (m << 31);
      const uint32_t n0 = (v0.x >> 16) ^ 0x8000u, n1 = (v1.x >> 16) ^ 0x8000u;
      SM<uint4>(OFF_EXB + j * 16) = make_uint4(n0 | (n0 << 16), n0, 0, 0);
      SM<uint4>(OFF_EXB + 2048 + j * 16) = make_uint4(n1 | (n1 << 16), n1, 0, 0);
      const float c = 0.5f * __uint_as_float(cs.x), hi = bf16r(c), mid = bf16r(c - hi), lo = bf16r((c - hi) - mid);
      SM<uint4>(OFF_EXA + j * 16) = make_uint4((__float_as_uint(hi) >> 16) | __float_as_uint(mid), __float_as_uint(lo) >> 16, 0, 0);
      fence_async_smem();
      __syncwarp();
      if (lane == 0) mbar_arrive(BAR(B_STAT));
    }
    if (j == 0) TIM(100);
    auto all_published = [&](int half) {
      uint32_t n = 0;
#pragma unroll 1
      while (!__all_sync(0xffffffffu, ld_acquire32(&p.sc->abdone[(cid * 2 + half) * 32 + (lane & 7)]) == tag) && ++n < SPIN_LIMIT) {}
      if (lane == 31) {
        asm volatile("fence.proxy.async.global;" ::: "memory");
        mbar_arrive(BAR(B_ALL + half));
        TIM(80 + half);
      }
      __syncwarp();
    };
    {
      if (a == 3) {
        const uint32_t cl = poll64_warp(&p.sc->cl[cid * 16 + (lane & 3)], tag, 100);
        if (lane == 0) TIM(101);
        const bf16* wm = (m ? p.Wim : p.Wre) + tau * 256 + lane * 8;
        uint4 v[8];
#pragma unroll
        for (int i = 0; i < 8; i++) v[i] = ldg128(wm + ((__shfl_sync(0xffffffffu, cl, i >> 1) >> ((i & 1) * 16)) & 2047) * 2048);
        const int pos = cid * 4 + (lane & 3);
        const bf16* xc = p.x + ((__shfl_sync(0xffffffffu, cl, lane >> 3) >> ((lane & 4) * 4)) & 2047) * 1024 + (pos >> 3) * 16 + (pos & 7);
        const float x0 = ldbf(xc), x1 = ldbf(xc + 8), w0 = ldbf(p.wr + (pos >> 3) * 16 + (pos & 7)), w1 = ldbf(p.wr + (pos >> 3) * 16 + (pos & 7) + 8);
        if (lane < 4) SM<uint32_t>(INFO_CAND + lane * 4) = cl;
#pragma unroll
        for (int i = 0; i < 8; i++) SM<uint4>(OFF_WC + (lane >> 3) * 1024 + i * 128 + (((lane & 7) ^ i) << 4)) = v[i];
        fence_async_smem();
        __syncwarp();
        if (lane == 0) { mbar_arrive(BAR(B_WC)); TIM(102); }
        mbar_wait(BAR(B_CD), 0);
        wait_clk(clk32(), CP_DELAY);
        uint32_t n = 0;
        bool more;
#pragma unroll 1
        do {
          uint32_t bad = 0;
#pragma unroll
          for (int i = 0; i < 8; i++) v[i] = pkt_ld128(&p.sc->cpart[((lane >> 3) * 16 + ((lane >> 2) & 1)) * 512 + pos] + i * 1024);
#pragma unroll
          for (int i = 0; i < 8; i++) chk_code(bad, v[i], c0, c1);
          more = __any_sync(0xffffffffu, bad & 1) && ++n < SPIN_LIMIT;
          if (more) { __nanosleep(200); }
        } while (more);
        float y[4] = {0.f, 0.f, 0.f, 0.f};
#pragma unroll
        for (int i = 0; i < 8; i++) { y[0] += no_bit(v[i].x); y[2] += no_bit(v[i].y); y[1] += no_bit(v[i].z); y[3] += no_bit(v[i].w); }
#pragma unroll
        for (int i = 0; i < 4; i++) y[i] = bf16r(y[i]);
        __syncwarp();
        fold<4>(y, 4, lane);
        const uint32_t hp = pack_bf16(x0 + bf16r(y[0]), x1 + bf16r(y[1]));
        pkt_st64(&p.sc->ch[(lane >> 2) * 512 + pos], hp, tag);
        float st[3] = {bf_lo(hp) + bf_hi(hp), bf_lo(hp) * bf_lo(hp) + bf_hi(hp) * bf_hi(hp), bf_lo(hp) * w0 + bf_hi(hp) * w1};
#pragma unroll
        for (int o = 1; o < 4; o <<= 1) {
#pragma unroll
          for (int i = 0; i < 3; i++) st[i] += __shfl_xor_sync(0xffffffffu, st[i], o);
        }
        if ((lane & 3) == 0) pkt_st128(&p.sc->cs[cid * 8 + (lane >> 2)], with_bit(st[0], c0), with_bit(st[1], c1), __float_as_uint(st[2]), tag);
        if (lane == 0) TIM(119);
      }
      if (a < 2) {
        uint32_t* fl = lane < 2 ? &p.sc->abflag[(cid * 4 + 2 * a + lane) * 32] : &p.sc->abdone[(((cid & 15) + (lane & 7) * 16) * 2 + a) * 32 + tau];
        if (lane == 0) {
          if (a == 1) mbar_wait(BAR(B_SD), 0);
          const uint32_t t1 = clk32();
#pragma unroll 1
          for (int i = 2 * a; i < 2 + 6 * a; i++) {
            const int w = i & 1, c = (4 - (i >> 1)) & 3;
            if (a == 1) wait_clk(t1, (i - 2) * PUB_PACE);
            mbar_wait(BAR(B_EP + w * 4 + c), 0);
            TIM(64 + i);
            fence_async_smem();
            tma_store_2d(&p.tmAbS, sb + off_stage(c) + w * 8192, tau * 256 + c * 64, abrow + w * 64);
            if (w) { bulk_commit(); bulk_wait_all(); mbar_arrive(BAR(B_SD + c)); }
          }
          TIM(72 + a * 2);
          asm volatile("fence.proxy.async.global;" ::: "memory");
          asm volatile("st.release.gpu.global.b32 [%0], %1;" :: "l"(fl), "r"(tag) : "memory");
          TIM(73 + a * 2);
        }
        __syncwarp();
        if ((lane == 1 && a == 0) || (lane >> 3) == 1) st_relaxed32(fl, tag);
        if (a == 0) { __nanosleep(ALL_NS); all_published(0); }
        else {
          uint32_t n = 0;
#pragma unroll 1
          while (__any_sync(0xffffffffu, ld_acquire32(&p.sc->abflag[(((cid + 16) & 127) * 4 + 2) * 32]) != tag) && ++n < SPIN_LIMIT) {}
#pragma unroll 1
          for (int i = 0; i < 3; i++) {
            if (elect_one()) {
              if (i == 0) asm volatile("fence.proxy.async.global;" ::: "memory");
              mbar_wait(BAR(B_E23 + i), 0);
              tma_load_2d(sb + ((i + 3) & 3) * ST_BYTES, &p.tmAbL, BAR(B_FULL + ((i + 3) & 3)), (tau * 256 + 320 + i * 64) & 2047, abrow);
              TIM(82 + i);
            }
            __syncwarp();
            if (i == 1) all_published(1);
          }
        }
      } else if (a == 2) {
        const uint32_t* fl = &p.sc->abflag[(((cid + 16 + 16 * (lane & 1)) & 127) * 4 + (lane & 1)) * 32];
        mbar_wait(BAR(B_SD), 0);
        __nanosleep(LO_NS);
        uint32_t n = 0, seen = 0;
#pragma unroll 1
        for (int c = 0; c < 4; c++) {
#pragma unroll 1
          while (c < 2 && !((seen >> c) & 1) && ++n < SPIN_LIMIT) seen = __ballot_sync(0xffffffffu, ld_acquire32(fl) == tag);
          if (lane == c) {
            if (c != 1) mbar_wait(BAR(B_SD + c), 0);
            mbar_wait(BAR(c < 3 ? B_FULL + c : B_EMPTY), 0);
            if (c == 2) mbar_wait(BAR(B_ALL), 0);
            if (c < 2) asm volatile("fence.proxy.async.global;" ::: "memory");
            tma_load_2d(sb + c * ST_BYTES, &p.tmAbL, BAR(B_FULL + c), k_col(tau, 4 + c), abrow);
            TIM(130 + c);
          }
          __syncwarp();
        }
      }
      __syncwarp();
    }
    mbar_wait(BAR(B_CD), 0);
    mbar_wait(BAR(B_SD + 1), 0);
    const uint64_t pol_ef = policy_evict_first();
    auto load_unit = [&](int v) {
      if (elect_one()) {
        const uint32_t dst = buf + (v & 1) * 4096, bar = bar0 + (v & 1) * 8;
        mbar_expect_tx(bar, 4096);
        if (v < 8) {
          tma_load_2d_hint(dst, &p.tmG, bar, fc, m * 512 + (a * 8 + v) * 16, pol_ef);
          tma_load_2d_hint(dst + 2048, &p.tmU, bar, fc, m * 512 + (a * 8 + v) * 16, pol_ef);
        } else tma_load_2d_hint(dst, &p.tmDn, bar, a * 256, src * 32 + (v - 8) * 8, pol_ef);
      }
    };
    if (ffn) load_unit(0);
    if (a != 1) {
      bar_sync(NB_SEL, 96);
      wait_clk(clk32(), CS_DELAY);
      fresh_ids();
      if (a == 0 && lane < 8) {
        if (lane == 0) mbar_expect_tx(BAR(B_CH), 16384);
        bulk_load(sb + OFF_AUX + 4096 + (lane >> 1) * 8192 + (lane & 1) * 2048, &p.sc->ch[lane * 512 + m * 256], 2048, BAR(B_CH));
      }
      const int j3 = a ? j - 32 : j;
      uint4 v[11]; uint32_t n = 0;
      bool more;
#pragma unroll 1
      do {
#pragma unroll
        for (int i = 0; i < 11; i++) v[i] = pkt_ld128(&p.sc->cs[j3] + (i < 10 || a < 3 ? i * 96 : 0));
        uint32_t bad = 0;
#pragma unroll
        for (int i = 0; i < 11; i++) { chk(bad, v[i].x, c0); chk(bad, v[i].y, c1); }
        bad &= 1;
#pragma unroll
        for (int i = 0; i < 11; i++) chk(bad, v[i].w, tag);
        more = __any_sync(0xffffffffu, bad) && ++n < SPIN_LIMIT;
        if (more) __nanosleep(200);
      } while (more);
      if (j == 0) TIM(97);
      float st[3] = {0.f, 0.f, 0.f};
      if (a < 3) { st[0] = no_bit(v[10].x); st[1] = no_bit(v[10].y); st[2] = __uint_as_float(v[10].z); }
#pragma unroll
      for (int i = 0; i < 10; i++) { st[0] += no_bit(v[i].x); st[1] += no_bit(v[i].y); st[2] += __uint_as_float(v[i].z); }
#pragma unroll
      for (int o = 8; o < 32; o <<= 1) {
#pragma unroll
        for (int i = 0; i < 3; i++) st[i] += __shfl_xor_sync(0xffffffffu, st[i], o);
      }
      if (lane < 8) SM<float4>(OFF_XS + ((j3 >> 5) * 8 + lane) * 16) = make_float4(st[0], st[1], st[2], 0.f);
      bar_sync(NB_SEL, 96);
      const float4 f0 = SM<float4>(OFF_XS + (lane & 7) * 16), f1 = SM<float4>(OFF_XS + 128 + (lane & 7) * 16), f2 = SM<float4>(OFF_XS + 256 + (lane & 7) * 16);
      const float mu = ((f0.x + f1.x) + f2.x) * (1.f / 1024.f);
      float mb = bf16r(mu), inv = fast_rcp(ref_sd(fmaxf(((f0.y + f1.y) + f2.y) * (1.f / 1024.f) - mu * mu, 0.f)));
      const uint32_t kk = make_key(bf16r((((f0.z + f1.z) + f2.z) - mb * SM<float>(INFO_WSUM)) * inv), SM<uint16_t>(INFO_CAND + (lane & 7) * 2));
      const uint32_t key = __reduce_max_sync(0xffffffffu, kk);
      const int win = __ffs(__ballot_sync(0xffffffffu, kk == key)) - 1;
      mb = __shfl_sync(0xffffffffu, mb, win); inv = __shfl_sync(0xffffffffu, inv, win);
      if (j == 0) { SM<uint2>(INFO_KEY) = make_uint2(key, win); SM<float2>(INFO_LN) = make_float2(mb, inv); }
      mbar_wait(BAR(B_CH), 0);
      bar_sync(NB_SEL, 96);
#pragma unroll 1
      for (int i = j3; i < 128; i += 96) {
        uint4 r = lds128(sb + OFF_AUX + 4096 + (win >> 1) * 8192 + (win & 1) * 2048 + i * 16);
#pragma unroll 1
        while ((r.y != tag || r.w != tag) && ++n < SPIN_LIMIT) r = pkt_ld128(&p.sc->ch[win * 512 + m * 256 + 2 * i]);
        auto ln = [&](float h) { return bf16r(bf16r(h - mb) * inv); };
        const int d = (i >> 2) * 16 + (i & 3) * 2;
        SM<float2>(OFF_XS + d * 4) = make_float2(ln(bf_lo(r.x)), ln(bf_lo(r.z)));
        SM<float2>(OFF_XS + (d + 8) * 4) = make_float2(ln(bf_hi(r.x)), ln(bf_hi(r.z)));
      }
      __syncwarp();
    }
    bar_sync(NB_AUX, 128);
    if (j == 0) {
      mbar_arrive(BAR(B_INFO)); TIM(103);
      if (cid == 0) st_relaxed32(&p.sc->epoch, tag);
    }
    const uint32_t t2 = clk32();
    fresh_ids();
    uint2 hp2 = make_uint2(0, 0);
    const uint2* hpp = &p.sc->ch[SM<uint32_t>(INFO_KEY + 4) * 512 + (cid >> 1) * 8 + (lane & 7)];
    if (a == 3) { hp2 = pkt_ld64(hpp); if (lane == 0) asm volatile("prefetch.tensormap [%0];" :: "l"(&p.tmY) : "memory"); }
    if (ffn) {
      load_unit(1);
      const int r = lane >> 3;
      float acc[8] = {0.f, 0.f, 0.f, 0.f, 0.f, 0.f, 0.f, 0.f};
#pragma unroll 1
      for (int v = 0; v < 8; v++) {
        const uint4 x0 = lds128(sb + OFF_XS + ((a * 8 + v) * 16 + (r & 1) * 8) * 4), x1 = lds128(sb + OFF_XS + ((a * 8 + v) * 16 + (r & 1) * 8 + 4) * 4);
        const float xv[8] = {__uint_as_float(x0.x), __uint_as_float(x0.y), __uint_as_float(x0.z), __uint_as_float(x0.w), __uint_as_float(x1.x), __uint_as_float(x1.y), __uint_as_float(x1.z), __uint_as_float(x1.w)};
        mbar_wait(bar0 + (v & 1) * 8, (v >> 1) & 1);
        gemv8x8<128>(acc, buf + (v & 1) * 4096 + r * 1024 + (lane & 7) * 16, xv);
        fence_regs(acc);
        __syncwarp();
        wait_clk(t2, v * UNIT_PACE);
        load_unit(v + 2);
        if (j == 0) TIM(104 + v);
      }
      fold<8>(acc, 8, lane);
      bar_sync(NB_AUX, 128);
      SM<float4>(OFF_XS + (a * 128 + (r >> 1) * 64 + (lane & 7) * 8 + (r & 1) * 4) * 4) = make_float4(acc[0], acc[1], acc[2], acc[3]);
      bar_sync(NB_AUX, 128);
      auto psum = [&](int i) { return (SM<float>(OFF_XS + i * 4) + SM<float>(OFF_XS + (128 + i) * 4)) + (SM<float>(OFF_XS + (256 + i) * 4) + SM<float>(OFF_XS + (384 + i) * 4)); };
      if (a < 2) st_async_b32(mapa(sb + OFF_REM + j * 4, m ^ 1), mapa(BAR(B_GUX), m ^ 1), __float_as_uint(psum(a * 64 + (m ^ 1) * 32 + lane)));
      const float og = psum(m * 32 + lane), ou = psum(64 + m * 32 + lane);
      mbar_wait(BAR(B_GUX), 0);
      const float rg = SM<float>(OFF_REM + lane * 4), ru = SM<float>(OFF_REM + 128 + lane * 4);
      const float act = swiglu(m ? rg + og : og + rg, m ? ru + ou : ou + ru);
      if (j == 0) TIM(112);
      float y[8] = {0.f, 0.f, 0.f, 0.f, 0.f, 0.f, 0.f, 0.f};
#pragma unroll 1
      for (int v = 8; v < 12; v++) {
        float av[8];
#pragma unroll
        for (int i = 0; i < 8; i++) av[i] = __shfl_sync(0xffffffffu, act, (v - 8) * 8 + i);
        mbar_wait(bar0 + (v & 1) * 8, (v >> 1) & 1);
        gemv8x8<512>(y, buf + (v & 1) * 4096 + lane * 16, av);
        fence_regs(y);
        __syncwarp();
        if (v < 10) load_unit(v + 2);
        if (j == 0) TIM(105 + v);
      }
      fresh_ids();
      uint4* ypart = &p.sc->ypart[(a * NSRC + src) * 64 + lane];
      pkt_st128(ypart, with_bit(y[0], c0), with_bit(y[1], c1), with_bit(y[2], c0), with_bit(y[3], c1));
      pkt_st128(ypart + 32, with_bit(y[4], c0), with_bit(y[5], c1), with_bit(y[6], c0), with_bit(y[7], c1));
      if (lane == 0) TIM(160 + a);
    }
    if (a == 3) {
      const uint32_t hh = __all_sync(0xffffffffu, hp2.y == tag) ? hp2.x : poll64_warp(&p.sc->ch[SM<uint32_t>(INFO_KEY + 4) * 512 + (cid >> 1) * 8 + (lane & 7)], tag, 100);
      const uint32_t key = SM<uint32_t>(INFO_KEY);
      const float h = m ? bf_hi(hh) : bf_lo(hh), hn = bf16r(bf16r(h - SM<float>(INFO_LN)) * SM<float>(INFO_LN + 4));
      float sig = sigmoid_bf(key_val(key));
      bf16* op = p.out + (key_row(key) * 1024 + cid * 8 + (lane & 7));
      asm volatile("" : "+f"(sig), "+l"(op));
      wait_clk(t2, ROW_CLK);
      uint4 v[7]; uint32_t n = 0;
      bool more;
#pragma unroll 1
      do {
        if (elect_one()) { mbar_expect_tx(bar0, NSRC * 32); tma_load_2d(buf, &p.tmY, bar0, (cid & 31) * 8, (cid >> 5) * (2 * NSRC)); }
        mbar_wait(bar0, n & 1);
        uint32_t bad = 0;
#pragma unroll
        for (int i = 0; i < 7; i++) { v[i] = lds128(buf + i * 512 + lane * 16); chk_code(bad, v[i], c0, c1); }
        more = __any_sync(0xffffffffu, bad & 1) && ++n < SPIN_LIMIT;
        if (more) __nanosleep(200);
      } while (more);
      if (lane == 0) TIM(164);
      float y[4] = {0.f, 0.f, 0.f, 0.f};
#pragma unroll
      for (int i = 0; i < 7; i++) { y[0] += no_bit(v[i].x); y[1] += no_bit(v[i].y); y[2] += no_bit(v[i].z); y[3] += no_bit(v[i].w); }
      fold<4>(y, 16, lane); fold<2>(y, 8, lane);
      y[0] += __shfl_xor_sync(0xffffffffu, y[0], 4);
      y[0] += __shfl_xor_sync(0xffffffffu, y[0], 2);
      const float ys = __shfl_sync(0xffffffffu, y[0], (lane & 3) * 8 + ((lane >> 2) & 1));
      if (lane < 8) st_bf16(op, routed_out(h, hn, ys, sig));
      if (lane == 0) { TIM(118); pkt_st64(&p.sc->rdone[cid], 0, tag); }
    }
  } else {
    reg_inc<216>();
    const uint32_t sb = __shfl_sync(0xffffffffu, smem_u32(smem_raw), 0);
    auto BAR = [&](int i) { return sb + OFF_BAR + 8 * i; };
    const int w = warp >> 2, wi = warp & 3, t = tid & 127;
    const int turn_me = NB_TURN0 + w, turn_other = NB_TURN1 - w;
    const uint64_t dA0 = make_desc(sb + w * 8192);
    uint64_t dA, dB;
    int tau, eps, m, grp, abrow, fc, src;
    bool ffn;
    const CUtensorMap* tmD; const CUtensorMap* tmW;
    auto new_desc = [&](int salt) {
      const uint32_t z = salt < 0 ? uniform_zero_here() : salt & blockIdx.y;
      dA = dA0 + z; dB = dA0 + (z + ((A_BYTES - w * 8192) >> 4));
      const int c = cid + z;
      tau = c >> 4; eps = (c >> 1) & 7; m = c & 1; grp = tau * 2 + m; abrow = m * 1024 + eps * 128;
      const int ef = tau ? eps : eps ^ 5;
      ffn = ef > 0; fc = (tau * 7 + ef - 1) * 64; src = (fc >> 5) + m;
      tmD = &p.tmD0 + m; tmW = &p.tmW0 + m;
    };
    constexpr int SL = ST_BYTES >> 4;
    float acc[128];
#pragma unroll
    for (int i = 0; i < 128; i++) acc[i] = 0.f;
    if (w == 1) bar_arrive(NB_TURN0, 256);
    auto full = [&](int k) { mbar_wait(BAR(B_FULL + (k & 3)), (k >> 2) & 1); CT(64 + k); };
    auto refill_w = [&](int k) {
      if (warp == 4) {
        if (elect_one()) {
          const int s = k & 3, s0 = k_col(tau, k - 12);
          TIM(k + 4);
          mbar_expect_tx(BAR(B_FULL + s), k < 16 ? B_BYTES : ST_BYTES);
          if (k == 19) mbar_arrive(BAR(B_EMPTY));
          tma_load_2d(sb + s * ST_BYTES + A_BYTES, tmW, BAR(B_FULL + s), s0, grp * 128);
          tma_load_2d(sb + s * ST_BYTES + A_BYTES + 16384, tmW, BAR(B_FULL + s), s0, (grp ^ 1) * 128);
        }
        __syncwarp();
      }
    };
    auto mma_ss = [&](int k) {
#pragma unroll
      for (int kk = 0; kk < 4; kk++) wgmma_n256(acc, dA + (k & 3) * SL + kk * 2, dB + (k & 3) * SL + kk * 2);
    };
    const CUtensorMap* rf_tm; uint32_t rf_dst; int rf_row, rf_c; bool rf_on;
    auto rf_set = [&](const CUtensorMap* tm, uint32_t dst, int row) {
      rf_tm = (const CUtensorMap*)__shfl_sync(0xffffffffu, (unsigned long long)tm, 0);
      rf_dst = __shfl_sync(0xffffffffu, dst, 0); rf_row = __shfl_sync(0xffffffffu, row, 0);
    };
    auto refill = [&](int s) {
      if (rf_on) {
        if (elect_one()) tma_load_2d(rf_dst + s * ST_BYTES, rf_tm, BAR(B_FULL + s), rf_c, rf_row);
        __syncwarp();
      }
      if (tid == 224) mbar_expect_tx(BAR(B_FULL + s), ST_BYTES);
    };
    const bf16* pf; int pf_step; bool pf_on;
    auto pf_ffn = [&](int v) {
      pf_on = ffn && v >= 0 && v < 12;
      pf = v < 8 ? ((lane & 16) ? p.wup : p.wgate) + (m * 512 + (wi * 8 + v) * 16 + (lane & 15)) * 3584 + fc : p.wdown + (src * 32 + (v - 8) * 8) * 1024 + t * 64;
      pf_step = v < 8 ? 16 * 3584 : 8192;
    };
    auto prefetch = [&](int s) { if (pf_on && (wi >> 1) == (s & 1)) prefetch_l2(pf + (s >> 1) * pf_step); };
    auto kstep = [&](int k) {
      full(k);
      bar_sync(turn_me, 256);
      wgmma_fence();
      mma_ss(k);
      wgmma_commit();
      bar_arrive(turn_other, 256);
    };

    uint32_t R[64];
    auto load_rs = [&](auto gi) {
      const uint32_t rsa = sb + OFF_RS + (lane & 3) * 272;
#pragma unroll
      for (int i = 4 * decltype(gi)::value; i < 4 * decltype(gi)::value + 4; i++) { const uint4 v = lds128(rsa + i * 16); R[4 * i] = v.x; R[4 * i + 1] = v.y; R[4 * i + 2] = v.z; R[4 * i + 3] = v.w; }
    };
    new_desc(64);
    rf_on = (warp >> 1) == 2;
    rf_set(wi ? tmD : &p.tmX, wi ? sb : sb + A_BYTES, wi ? eps * 128 : tau * 256);
#pragma unroll 1
    for (int k4 = 0; k4 < 12; k4 += 4) {
#pragma unroll
      for (int s = 0; s < 4; s++) {
        kstep(k4 | s);
        if (s == 0) {
          if (w == 0) pf_ffn((k4 >> 1) - 2);
          else {
            pf_on = k4 == 8 || (k4 == 4 && (lane & 7) < 3);
            pf = (m ? p.Wim : p.Wre) + (tau * 256 + eps * 32 + wi * 4 + (lane >> 3)) * 2048 + k_col(tau, (lane & 7) + (k4 == 8 ? 3 : 0));
            pf_step = 16 * 2048;
          }
        }
        rf_c = (k4 + s + 4) * 64;
        prefetch(s);
        if (s == 3) new_desc(k4);
        if (s == 0 || s == 3) pf += zero_here();
        wgmma_wait<0>();
        refill(s);
      }
    }
    kstep(12);
    mbar_wait(BAR(B_STAT), 0);
    load_rs(std::integral_constant<int, 0>());
    CT(1);
    load_rs(std::integral_constant<int, 1>());
    wgmma_wait<0>(); refill_w(12);
    auto mma_h = [&](float (&d)[64], int s, int half) {
#pragma unroll
      for (int kk = 0; kk < 4; kk++) wgmma_n128(d, dA + s * SL + kk * 2, dB + s * SL + half * 1024 + kk * 2);
    };
    const int rho = 16 * wi + (lane & 15);
    const uint32_t arow = sb + w * 8192 + rho * 128;
    auto convert = [&](auto cc, const float* d) {
      const float z = __uint_as_float(zero_here());
#pragma unroll
      for (int jj = 8 * decltype(cc)::value; jj < 8 * decltype(cc)::value + 8; jj++) {
        const float r0 = __uint_as_float(R[2 * jj]), r1 = __uint_as_float(R[2 * jj + 1]);
        const float* ac = &d[4 * (jj & 7)];
        R[2 * jj] = pack_bf16(fmaf(ac[0], r0, z), fmaf(ac[1], r1, z));
        R[2 * jj + 1] = pack_bf16(fmaf(ac[2], r0, z), fmaf(ac[3], r1, z));
      }
    };
    auto put = [&](auto cc) {
      constexpr int c = decltype(cc)::value;
#pragma unroll
      for (int jj = 8 * c; jj < 8 * c + 8; jj += 2)
        stsm_x4(arow + off_stage(c) + ((((jj & 7) + (lane >> 4)) ^ (rho & 7)) << 4), R[2 * jj], R[2 * jj + 1], R[2 * jj + 2], R[2 * jj + 3]);
      __syncwarp();
      if (lane == 0) mbar_arrive(BAR(B_EP + w * 4 + c));
    };
    {
      float lo[32], hi[96];
      fence_regs(acc);
#pragma unroll
      for (int i = 0; i < 32; i++) asm volatile("mov.b32 %0, %1;" : "=f"(lo[i]) : "f"(acc[i]));
#pragma unroll
      for (int i = 0; i < 96; i++) asm volatile("mov.b32 %0, %1;" : "=f"(hi[i]) : "f"(acc[32 + i]));
      auto mma_p = [&](auto& d, int s, int boff) {
#pragma unroll
        for (int kk = 0; kk < 4; kk++) wgmma_part(d, dA + s * SL + kk * 2, dB + s * SL + boff + kk * 2);
      };
      const uint64_t dEA = make_desc_noswz(sb + OFF_EXA + w * 1024), dEB = make_desc_noswz(sb + OFF_EXB);
      full(13); full(14);
      bar_sync(turn_me, 256);
      wgmma_fence();
      mma_p(lo, 1, 0); mma_p(lo, 2, 0);
      wgmma_commit();
      bar_arrive(turn_other, 256);
      new_desc(66);
      full(15);
      bar_sync(turn_me, 256);
      wgmma_fence();
      mma_p(lo, 3, 0);
      wgmma_part(lo, dEA, dEB);
      wgmma_commit();
      mma_p(hi, 1, 512);
      wgmma_commit();
      bar_arrive(turn_other, 256);
      new_desc(67);
      wgmma_wait<1>();
      fence_regs(lo);
      CT(15);
      convert(std::integral_constant<int, 0>(), lo); put(std::integral_constant<int, 0>());
      load_rs(std::integral_constant<int, 3>());
      wgmma_wait<0>(); refill_w(13);
      bar_sync(turn_me, 256);
      wgmma_fence();
      mma_p(hi, 2, 512);
      wgmma_commit();
      mma_p(hi, 3, 512);
      wgmma_part(hi, dEA, dEB + 64);
      wgmma_commit();
      bar_arrive(turn_other, 256);
      load_rs(std::integral_constant<int, 2>());
      wgmma_wait<1>(); refill_w(14);
      wgmma_wait<0>(); refill_w(15);
      fence_regs(hi);
      CT(2);
      convert(std::integral_constant<int, 3>(), hi + 64);
      put(std::integral_constant<int, 3>());
      convert(std::integral_constant<int, 1>(), hi);
      convert(std::integral_constant<int, 2>(), hi + 32);
    }
    CT(3);
    new_desc(-1);
    full(16);
    bar_sync(turn_me, 256);
    wgmma_fence();
    wgmma_n256_rs_init(acc, R, dB);
#pragma unroll
    for (int kk = 1; kk < 4; kk++) wgmma_n256_rs(acc, R + 4 * kk, dB + kk * 2);
    wgmma_commit();
    full(17);
    wgmma_fence();
#pragma unroll
    for (int kk = 0; kk < 4; kk++) wgmma_n256_rs(acc, R + 16 + 4 * kk, dB + SL + kk * 2);
    wgmma_commit();
    bar_arrive(turn_other, 256);
    put(std::integral_constant<int, 2>());
    wgmma_wait<1>(); refill_w(16);
    wgmma_wait<0>(); refill_w(17);
    {
      fence_async_smem();
      mbar_wait(BAR(B_WC), 0);
      CT(4);
      full(18);
      bar_sync(turn_me, 256);
      wgmma_fence();
      float cc[4];
      const uint64_t dC = make_desc(sb + OFF_WC);
      wgmma_n8_rs<0>(cc, R, dC);
#pragma unroll
      for (int i = 1; i < 12; i++) wgmma_n8_rs<1>(cc, R + 4 * i, dC + (i >> 2) * 64 + (i & 3) * 2);
#pragma unroll
      for (int kk = 0; kk < 4; kk++) wgmma_n8(cc, dA + 3 * SL + kk * 2, dC + 192 + kk * 2);
      wgmma_commit();
#pragma unroll
      for (int kk = 0; kk < 4; kk++) wgmma_n256_rs(acc, R + 32 + 4 * kk, dB + 2 * SL + kk * 2);
      wgmma_commit();
      bar_arrive(turn_other, 256);
      wgmma_wait<1>();
      fence_regs(cc);
      const uint32_t cd = code_of(SM<uint32_t>(INFO_TAG));
      if (t == 0) mbar_arrive(BAR(B_CD));
      pkt_st128(&p.sc->cpart[((lane & 3) * 16 + grp) * 512 + eps * 64 + warp * 8 + (lane >> 2)], with_bit(cc[0], cd), with_bit(cc[1], cd >> 1), with_bit(cc[2], cd), with_bit(cc[3], cd >> 1));
      CT(5);
    }
    put(std::integral_constant<int, 1>());
    wgmma_wait<0>(); refill_w(18);
    kstep(19);
    cluster_wait();
    new_desc(68);
    rf_set(wi == 2 ? &p.tmAbL : tmW, wi == 2 ? sb : sb + A_BYTES + wi * 16384, wi == 2 ? abrow : (grp ^ wi) * 128);
    wgmma_wait<0>(); refill_w(19);
    const int g = lane >> 2, q = lane & 3;
    uint4 ha[4], hb[4], wv[4], info = make_uint4(0, 0, 0, 0);
#pragma unroll
    for (int i = 0; i < 4; i++) ha[i] = hb[i] = wv[i] = make_uint4(0, 0, 0, 0);
    auto load_x = [&](auto ii) {
      constexpr int i = decltype(ii)::value;
      const bf16* xp = p.x + ((grp * 128 + warp * 16 + g) * 1024 + eps * 128 + q * 8);
      ha[i] = ldg128(xp + i * 32); hb[i] = ldg128(xp + 8192 + i * 32);
    };
    auto load_w = [&]() {
      mbar_wait(BAR(B_INFO), 0);
#pragma unroll
      for (int i = 0; i < 4; i++) wv[i] = lds128(sb + ((g & 1) ? OFF_WR + (i * 4 + q) * 16 : INFO_ONES));
      info = lds128(sb + OFF_INFO);
    };

    rf_on = w == 1 && wi < 3;
    rf_c = k_col(tau, 7);
#pragma unroll 1
    for (int k4 = 20; k4 < 44; k4 += 4) {
#pragma unroll
      for (int s = 0; s < 4; s++) {
        kstep(k4 | s);
        if (s == 0) {
          if (w == 0) { pf_ffn((k4 >> 1) - 8); pf_on = pf_on && k4 >= 24; }
          else {
            pf_on = k4 == 32;
            pf = p.x + (grp * 128 + (t >> 1)) * 1024 + eps * 128 + (t & 1) * 64;
            pf_step = 64 * 1024;
          }
        }
        rf_c = k_next(rf_c, k4 + s - 12);
        if (s == 0 && k4 == 20 && warp == 6) mbar_wait(BAR(B_ALL), 0);
        if (s == 2 && k4 == 24 && warp == 6) mbar_wait(BAR(B_ALL + 1), 0);
        prefetch(s);
        if (k4 == 40) {
          if (s == 1) load_w();
          if (s == 2) load_x(std::integral_constant<int, 0>());
          if (s == 3) load_x(std::integral_constant<int, 1>());
        }
        if (s == 3) new_desc(k4);
        if (s == 0 || s == 3) pf += zero_here();
        wgmma_wait<0>();
        if (((s == 3 && k4 == 20) || (s < 2 && k4 == 24)) && warp == 6) { if (lane == 0) mbar_arrive(BAR(B_E23 + ((s + 1) & 3))); }
        else refill(s);
      }
    }
    const int row0 = grp * 128 + warp * 16 + g;
    kstep(44);
    load_x(std::integral_constant<int, 2>());
    wgmma_wait<0>();
    if (tid == 128) mbar_arrive_remote(mapa(BAR(B_PEER), m ^ 1));
    uint32_t hp[32];
    bf16* op; uint4* hpub; uint4* hst;
    uint32_t cd, ast, ald, zr;
    auto swz = [](int row) { return ((row & 1) << 2) | ((row >> 1) & 3); };
    {
      float as[64], ak[64];
      fence_regs(acc);
#pragma unroll
      for (int i = 0; i < 64; i++) asm volatile("mov.b32 %0, %1;" : "=f"(as[i]) : "f"(acc[64 + i]));
#pragma unroll
      for (int i = 0; i < 64; i++) asm volatile("mov.b32 %0, %1;" : "=f"(ak[i]) : "f"(acc[i]));
      full(45); full(46);
      bar_sync(turn_me, 256);
      wgmma_fence();
      mma_h(as, 1, 1); mma_h(as, 2, 1);
      wgmma_commit();
      bar_arrive(turn_other, 256);
      load_x(std::integral_constant<int, 3>());
      full(47);
      bar_sync(turn_me, 256);
      wgmma_fence();
      mma_h(as, 3, 1);
      wgmma_commit();
      const uint32_t rx = mapa(sb + OFF_RECV + w * 16384 + t * 16, m ^ 1), rb = mapa(BAR(B_XCH + w), m ^ 1);
      mma_h(ak, 1, 0);
      wgmma_commit();
      bar_arrive(turn_other, 256);
      mbar_wait(BAR(B_PEER), 0);
      wgmma_wait<1>();
      fence_regs(as);
      CT(6);
#pragma unroll
      for (int i = 0; i < 8; i++) {
        const float* ac = &as[8 * i];
        st_async_v4(rx + i * 2048, rb, pack_bf16(ac[0], ac[1]), pack_bf16(ac[2], ac[3]), pack_bf16(ac[4], ac[5]), pack_bf16(ac[6], ac[7]));
      }
      CT(7);
      bar_sync(turn_me, 256);
      wgmma_fence();
      mma_h(ak, 2, 0); mma_h(ak, 3, 0);
      wgmma_commit();
      if (w == 0) bar_arrive(turn_other, 256);
      op = p.out + row0 * 1024 + eps * 128 + q * 8;
      hst = &p.sc->hstat[grp * 1024 + warp * 16 + g];
      hpub = hst + eps * 128; hst += q * 256;
      cd = code_of(info.y);
      ast = sb + w * ST_BYTES + (8 * (lane >> 4) + (lane & 7)) * 128 + (((2 * wi + ((lane >> 3) & 1)) ^ swz(lane & 7)) << 4);
      ald = sb + (warp * 16 + g) * 128 + ((q ^ swz(g)) << 4);
      asm volatile("" : "+l"(op), "+l"(hpub), "+l"(hst), "+r"(cd), "+r"(ast), "+r"(ald));
      zr = zero_here();
#pragma unroll
      for (int i = 0; i < 4; i++) { ha[i].x += zr; hb[i].x += zr; asm volatile("" : "+r"(ha[i].x), "+r"(hb[i].x)); }
      ast += (uint32_t)(clock64() >> 32) & zr;
      mbar_wait(BAR(B_XCH + w), 0);
      CT(9);
#pragma unroll
      for (int i = 0; i < 8; i++) { const uint4 v = lds128(sb + OFF_RECV + w * 16384 + t * 16 + i * 2048); hp[4 * i] = v.x; hp[4 * i + 1] = v.y; hp[4 * i + 2] = v.z; hp[4 * i + 3] = v.w; }
      wgmma_wait<0>();
      fence_regs(ak);
      CT(10);
#pragma unroll
      for (int i = 0; i < 32; i++) hp[i] = badd2(pack_bf16(ak[2 * i], ak[2 * i + 1]), hp[i]);
    }
#pragma unroll
    for (int jj = 0; jj < 16; jj += 2) stsm_x4_t(ast + jj * 1024, hp[2 * jj], hp[2 * jj + 1], hp[2 * jj + 2], hp[2 * jj + 3]);
    const uint32_t tag = info.y;
    uint4 v[4];
    auto fetch = [&]() { v[0] = pkt_ld128(hst); v[1] = pkt_ld128(hst + 128); v[2] = pkt_ld128(hst + 8); v[3] = pkt_ld128(hst + 136); };
    float st[6], hf[64];
    {
      float sw[2][4], qa[2][4], qb[2][4];
#pragma unroll
      for (int i = 0; i < 8; i++) { sw[i >> 2][i & 3] = 0.f; qa[i >> 2][i & 3] = 0.f; qb[i >> 2][i & 3] = 0.f; }
      bar_sync(NB_BOTH, 256);
      CT(11);
      uint4 ya[4], yb[4];
#pragma unroll
      for (int i = 0; i < 4; i++) {
        const uint32_t ad = (ald ^ ((i & 1) << 6)) + (i >> 1) * ST_BYTES;
        ya[i] = lds128(ad); yb[i] = lds128(ad + 1024);
      }
      fetch();
      sw[0][0] = __uint_as_float((uint32_t)(clock64() >> 32) & zr);
#pragma unroll
      for (int i = 0; i < 4; i++) {
        ha[i] = make_uint4(badd2(ha[i].x, ya[i].x), badd2(ha[i].y, ya[i].y), badd2(ha[i].z, ya[i].z), badd2(ha[i].w, ya[i].w));
        hb[i] = make_uint4(badd2(hb[i].x, yb[i].x), badd2(hb[i].y, yb[i].y), badd2(hb[i].z, yb[i].z), badd2(hb[i].w, yb[i].w));
        mma16816(sw[0], ha[i].x, hb[i].x, ha[i].y, hb[i].y, wv[i].x, wv[i].y);
        mma16816(qa[0], ha[i].x, hb[i].x, ha[i].y, hb[i].y, ha[i].x, ha[i].y);
        mma16816(qb[0], ha[i].x, hb[i].x, ha[i].y, hb[i].y, hb[i].x, hb[i].y);
        mma16816(sw[1], ha[i].z, hb[i].z, ha[i].w, hb[i].w, wv[i].z, wv[i].w);
        mma16816(qa[1], ha[i].z, hb[i].z, ha[i].w, hb[i].w, ha[i].z, ha[i].w);
        mma16816(qb[1], ha[i].z, hb[i].z, ha[i].w, hb[i].w, hb[i].z, hb[i].w);
      }
      const uint32_t s0 = with_bit(sw[0][0] + sw[1][0], cd), s1 = with_bit((g & 1) ? qa[0][1] + qa[1][1] : qa[0][0] + qa[1][0], cd >> 1), s2 = __float_as_uint(sw[0][1] + sw[1][1]);
      const uint32_t s3 = with_bit(sw[0][2] + sw[1][2], cd), s4 = with_bit((g & 1) ? qb[0][3] + qb[1][3] : qb[0][2] + qb[1][2], cd >> 1), s5 = __float_as_uint(sw[0][3] + sw[1][3]);
      if (q == (g >> 1)) { pkt_st128(hpub, s0, s1, s2, tag); pkt_st128(hpub + 8, s3, s4, s5, tag); }
      CT(12);
      {
#pragma unroll
        for (int i = 0; i < 8; i++) {
          const uint4 h = i < 4 ? ha[i] : hb[i - 4];
          hf[8 * i] = bf_lo(h.x); hf[8 * i + 1] = bf_hi(h.x); hf[8 * i + 2] = bf_lo(h.y); hf[8 * i + 3] = bf_hi(h.y);
          hf[8 * i + 4] = bf_lo(h.z); hf[8 * i + 5] = bf_hi(h.z); hf[8 * i + 6] = bf_lo(h.w); hf[8 * i + 7] = bf_hi(h.w);
        }
        fence_regs(hf);
        op += (uint32_t)(clock64() >> 32) & zr;
      }
      const uint32_t o1 = __shfl_sync(0xffffffffu, s1, (lane & 28) | (g >> 1)), o4 = __shfl_sync(0xffffffffu, s4, (lane & 28) | (g >> 1));
      uint32_t n = 0;
      bool more;
#pragma unroll 1
      do {
        if (2 * q == eps) { v[0] = make_uint4(s0, o1, s2, tag); v[2] = make_uint4(s3, o4, s5, tag); }
        if (2 * q + 1 == eps) { v[1] = make_uint4(s0, o1, s2, tag); v[3] = make_uint4(s3, o4, s5, tag); }
        uint32_t bad = 0;
#pragma unroll
        for (int i = 0; i < 4; i++) { chk(bad, v[i].x, cd); chk(bad, v[i].y, cd >> 1); }
        bad &= 1;
#pragma unroll
        for (int i = 0; i < 4; i++) chk(bad, v[i].w, tag);
        more = __any_sync(0xffffffffu, bad) && ++n < SPIN_LIMIT;
        if (more && bad) fetch();
      } while (more);
      st[0] = no_bit(v[0].x) + no_bit(v[1].x); st[1] = no_bit(v[0].y) + no_bit(v[1].y); st[2] = __uint_as_float(v[0].z) + __uint_as_float(v[1].z);
      st[3] = no_bit(v[2].x) + no_bit(v[3].x); st[4] = no_bit(v[2].y) + no_bit(v[3].y); st[5] = __uint_as_float(v[2].z) + __uint_as_float(v[3].z);
    }
    CT(13);
#pragma unroll
    for (int o = 1; o < 4; o <<= 1) {
#pragma unroll
      for (int i = 0; i < 6; i++) st[i] += __shfl_xor_sync(0xffffffffu, st[i], o);
    }
    float mb[2], inv[2];
#pragma unroll
    for (int i = 0; i < 2; i++) {
      const float mu = st[3 * i] * (1.f / 1024.f);
      mb[i] = bf16r(mu);
      inv[i] = fast_rcp(ref_sd(fmaxf(st[3 * i + 1] * (1.f / 1024.f) - mu * mu, 0.f)));
    }
    {
      const int srow = key_row(info.z);
      auto put_out = [&](bf16* dst, const float* f, float sc, float of, bool on) {
        auto cvt = [&](int i) { return pack_bf16(fmaf(f[i], sc, of), fmaf(f[i + 1], sc, of)); };
        asm volatile("{\n.reg .pred p;\nsetp.ne.b32 p, %5, 0;\n@p st.global.v4.b32 [%0], {%1, %2, %3, %4};\n}\n"
                     :: "l"(dst), "r"(cvt(0)), "r"(cvt(2)), "r"(cvt(4)), "r"(cvt(6)), "r"((int)on) : "memory");
      };
#pragma unroll
      for (int i = 0; i < 4; i++) {
        put_out(op + i * 32, hf + 8 * i, 1.f + inv[0], -mb[0] * inv[0], row0 != srow);
        put_out(op + 8192 + i * 32, hf + 32 + 8 * i, 1.f + inv[1], -mb[1] * inv[1], row0 + 8 != srow);
      }
    }
    CT(14);
    const uint4 cand = lds128(sb + INFO_CAND);
    uint32_t wkey = zero_here();
#pragma unroll
    for (int i = 0; i < 2; i++) {
      const uint32_t row = row0 + 8 * i, rr = row | (row << 16);
      const bool is_cand = __vcmpeq2(cand.x, rr) | __vcmpeq2(cand.y, rr) | __vcmpeq2(cand.z, rr) | __vcmpeq2(cand.w, rr);
      if (!is_cand) wkey = max(wkey, make_key(bf16r((st[3 * i + 2] - mb[i] * __uint_as_float(info.x)) * inv[i]), row));
    }
    wkey = __reduce_max_sync(0xffffffffu, wkey);
    if (eps == 0 && lane == 0) pkt_st64(&p.sc->key[grp * 8 + warp], wkey, tag);
    const bool beaten = (wkey >> 16) > (info.z >> 16);
    if (__builtin_expect(beaten, 0)) {
      const int br = key_row(wkey);
      if (br == row0 || br == row0 + 8) {
#pragma unroll
        for (int i = 0; i < 4; i++) {
          const uint4 h = br == row0 ? ha[i] : hb[i];
          uint2* dst = &p.sc->hrow[(grp * 8 + warp) * 512 + eps * 64 + i * 16 + q * 4];
          pkt_st128(dst, h.x, tag, h.y, tag); pkt_st128(dst + 2, h.z, tag, h.w, tag);
        }
      }
      __syncwarp();
    }
    uint32_t any;
    asm volatile("{\n.reg .pred p, q;\nsetp.ne.b32 p, %1, 0;\nbarrier.cta.red.or.aligned.pred q, %2, 256, p;\nselp.u32 %0, 1, 0, q;\n}\n" : "=r"(any) : "r"((int)beaten), "n"((int)NB_END) : "memory");
    if (__builtin_expect(any, 0)) slow_path(p, grp, eps, tag, info.z, info.w, SM<float>(INFO_LN), SM<float>(INFO_LN + 4));
  }
}

__global__ void __launch_bounds__(NTHR, 1) occupancy_probe_kernel() {}

typedef CUresult (*EncodeFn)(CUtensorMap*, CUtensorMapDataType, cuuint32_t, void*, const cuuint64_t*, const cuuint64_t*, const cuuint32_t*, const cuuint32_t*,
                             CUtensorMapInterleave, CUtensorMapSwizzle, CUtensorMapL2promotion, CUtensorMapFloatOOBfill);

static void make_tm(EncodeFn enc, CUtensorMap* tm, const void* ptr, uint64_t rows, uint64_t cols, uint32_t brows, uint32_t bcols, bool swz) {
  cuuint64_t dims[2] = {cols, rows};
  cuuint64_t strides[1] = {cols * 2};
  cuuint32_t box[2] = {bcols, brows};
  cuuint32_t es[2] = {1, 1};
  enc(tm, CU_TENSOR_MAP_DATA_TYPE_BFLOAT16, 2, const_cast<void*>(ptr), dims, strides, box, es, CU_TENSOR_MAP_INTERLEAVE_NONE,
      swz ? CU_TENSOR_MAP_SWIZZLE_128B : CU_TENSOR_MAP_SWIZZLE_NONE, CU_TENSOR_MAP_L2_PROMOTION_L2_128B, CU_TENSOR_MAP_FLOAT_OOB_FILL_NONE);
}

extern "C" void kernel_launch(void* const* d_in, const int* in_sizes, int n_in, void* d_out, int out_size) {
  (void)in_sizes; (void)n_in; (void)out_size;
  static EncodeFn enc = nullptr;
  static void* abT = nullptr;
  static void* sc = nullptr;
  static int map = 0;
  if (!enc) {
    void* fn = nullptr; cudaDriverEntryPointQueryResult st;
    cudaGetDriverEntryPoint("cuTensorMapEncodeTiled", &fn, cudaEnableDefault, &st);
    enc = (EncodeFn)fn;
    cudaGetSymbolAddress(&abT, g_abT);
    cudaGetSymbolAddress(&sc, g_sc);
    cudaFuncSetAttribute(fnet_moe_kernel<0>, cudaFuncAttributeMaxDynamicSharedMemorySize, SMEM_TOTAL);
    cudaFuncSetAttribute(fnet_moe_kernel<1>, cudaFuncAttributeMaxDynamicSharedMemorySize, SMEM_TOTAL);
    cudaFuncSetAttribute(occupancy_probe_kernel, cudaFuncAttributeMaxDynamicSharedMemorySize, SMEM_TOTAL);
    cudaFuncSetAttribute(occupancy_probe_kernel, cudaFuncAttributeNonPortableClusterSizeAllowed, 1);
    cudaLaunchConfig_t cfg = {};
    cfg.gridDim = dim3(128); cfg.blockDim = dim3(NTHR); cfg.dynamicSmemBytes = SMEM_TOTAL;
    cudaLaunchAttribute at[1];
    at[0].id = cudaLaunchAttributeClusterDimension; at[0].val.clusterDim.x = 16; at[0].val.clusterDim.y = 1; at[0].val.clusterDim.z = 1;
    cfg.attrs = at; cfg.numAttrs = 1;
    int ncl = 0;
    if (cudaOccupancyMaxActiveClusters(&ncl, occupancy_probe_kernel, &cfg) == cudaSuccess && ncl >= 8) map = 1;
    (void)cudaGetLastError();
  }
  Params p;
  const bf16* x = (const bf16*)d_in[0];
  make_tm(enc, &p.tmD0, d_in[3], 1024, 1024, 128, 64, true);
  make_tm(enc, &p.tmD1, d_in[4], 1024, 1024, 128, 64, true);
  make_tm(enc, &p.tmX, x, 2048, 1024, 256, 64, true);
  make_tm(enc, &p.tmAbS, abT, 2048, 2048, 64, 64, true);
  make_tm(enc, &p.tmAbL, abT, 2048, 2048, 128, 64, true);
  make_tm(enc, &p.tmW0, d_in[1], 2048, 2048, 128, 64, true);
  make_tm(enc, &p.tmW1, d_in[2], 2048, 2048, 128, 64, true);
  make_tm(enc, &p.tmG, d_in[7], 1024, 3584, 16, 64, false);
  make_tm(enc, &p.tmU, d_in[8], 1024, 3584, 16, 64, false);
  make_tm(enc, &p.tmDn, d_in[9], 3584, 1024, 8, 256, false);
  make_tm(enc, &p.tmY, (char*)sc + offsetof(Scratch, ypart), 8 * NSRC, 256, 2 * NSRC, 8, false);
  p.x = x; p.Dre = (const bf16*)d_in[3]; p.Dim = (const bf16*)d_in[4];
  p.wr = (const bf16*)d_in[6]; p.wdown = (const bf16*)d_in[9]; p.wgate = (const bf16*)d_in[7]; p.wup = (const bf16*)d_in[8]; p.Wre = (const bf16*)d_in[1]; p.Wim = (const bf16*)d_in[2];
  p.out = (bf16*)d_out; p.sc = (Scratch*)sc;
  if (map == 1) fnet_moe_kernel<1><<<NGRID, NTHR, SMEM_TOTAL>>>(p);
  else fnet_moe_kernel<0><<<NGRID, NTHR, SMEM_TOTAL>>>(p);
}
```

```cpp
#include <cuda.h>
#include <cuda_runtime.h>
#include <cuda_bf16.h>
#include <stdint.h>
#include <stddef.h>
#include <type_traits>

typedef __nv_bfloat16 bf16;

constexpr int NGRID = 132, NTHR = 384;
__device__ __forceinline__ int k_col(int tau, int j) { return (tau * 256 + (j < 4 ? j * 64 : (j - 3) * 256)) & 2047; }
__device__ __forceinline__ int k_next(int c, int j) { return (c + (j < 11 ? 256 : j == 11 ? 576 : (c & 192) == 192 ? 128 : 64)) & 2047; }
constexpr int A_BYTES = 128 * 64 * 2;
constexpr int B_BYTES = 256 * 64 * 2;
constexpr int ST_BYTES = A_BYTES + B_BYTES;
constexpr int OFF_AUX = 4 * ST_BYTES;
constexpr int OFF_BAR = OFF_AUX + 32768;
constexpr int OFF_XS = OFF_BAR + 256;
constexpr int OFF_WR = OFF_XS + 2048;
constexpr int OFF_REM = OFF_WR + 256;
constexpr int OFF_INFO = OFF_REM + 256;
constexpr int SMEM_TOTAL = OFF_INFO + 256;
constexpr int INFO_WSUM = OFF_INFO, INFO_TAG = OFF_INFO + 4, INFO_KEY = OFF_INFO + 8, INFO_CAND = OFF_INFO + 16, INFO_LN = OFF_INFO + 32, INFO_ONES = OFF_INFO + 48, INFO_DS = OFF_INFO + 64, INFO_DS2 = OFF_INFO + 192;
constexpr int OFF_RS = OFF_XS;
constexpr int OFF_WC = OFF_AUX;
constexpr int OFF_EXA = OFF_AUX + 4096;
constexpr int OFF_EXB = OFF_AUX + 6144;
__host__ __device__ constexpr int off_stage(int c) { return c == 1 ? OFF_AUX + 16384 : c * ST_BYTES; }
constexpr int OFF_RECV = A_BYTES;
constexpr int NSRC = 112;
enum { B_FULL = 0,
       B_EMPTY = 4,
       B_ALL = 6,
       B_EP = 8,
       B_AW = 16,
       B_STAT = 24, B_WC = 25, B_CD = 26, B_CH = 27, B_INFO = 28, B_PEER = 29,
       B_XCH = 30,
       B_GUX = (OFF_INFO + 128 - OFF_BAR) / 8,
       B_SD = B_GUX + 1,
       B_E23 = B_GUX + 5 };
enum { NB_TURN0 = 1, NB_TURN1 = 2, NB_BOTH = 3, NB_AUX = 4, NB_H = 5, NB_SEL = 6, NB_END = 7 };

struct Scratch;
struct Params {
  Scratch* sc; const bf16* wr; const bf16* x; const bf16* Dre; const bf16* Dim; const bf16* Wre; const bf16* Wim;
  const bf16* wgate; const bf16* wup; const bf16* wdown; bf16* out;
  CUtensorMap tmX, tmD0, tmD1, tmW0, tmW1, tmAbS, tmAbL, tmG, tmU, tmDn, tmY;
};

__device__ __align__(1024) bf16 g_abT[2048 * 2048];
struct Scratch {
  alignas(128) uint4 xz[2048];
  alignas(128) uint2 dsum[2048];
  alignas(128) uint32_t abflag[128 * 4 * 32];
  alignas(128) uint32_t abdone[128 * 2 * 32];
  alignas(128) uint2 u[4 * 512];
  alignas(128) uint2 cl[128 * 16];
  alignas(128) uint4 cpart[4 * 16 * 512];
  alignas(128) uint2 ch[8 * 512];
  alignas(128) uint4 cs[128 * 8];
  alignas(128) uint4 ypart[4 * NSRC * 64];
  alignas(128) uint4 hstat[16 * 8 * 128];
  alignas(128) uint2 rdone[128];
  alignas(128) uint2 key[128];
  alignas(128) uint2 hrow[128 * 512];
  alignas(128) uint2 fpart[8 * 1024];
  alignas(128) uint32_t epoch;
};
__device__ Scratch g_sc;

#define SPIN_LIMIT (1u << 17)
constexpr uint32_t ST1_CLK = 1200, ST_GAP = 600, U_CLK = 3700, Z_CLK = 9000;
constexpr uint32_t XS_DELAY = 300, CP_DELAY = 1500, CS_DELAY = 800;
constexpr uint32_t PUB_PACE = 1000, UNIT_PACE = 1800, ROW_CLK = 22000;
constexpr int LO_NS = 250, ALL_NS = 400;
__device__ __forceinline__ uint32_t smem_u32(const void* p) { return (uint32_t)__cvta_generic_to_shared(p); }
__device__ __forceinline__ uint32_t clk32() { uint32_t c; asm volatile("mov.u32 %0, %%clock;" : "=r"(c)); return c; }
__device__ __forceinline__ uint32_t zero_here() { uint64_t c; asm volatile("mov.u64 %0, %%clock64;" : "=l"(c) :: "memory"); return (uint32_t)(c >> 32) & blockIdx.y; }
__device__ __forceinline__ uint32_t uniform_zero_here() { uint32_t c; asm volatile("mov.u32 %0, %%clock;" : "=r"(c) :: "memory"); return c & blockIdx.y; }
__device__ __forceinline__ void wait_clk(uint32_t t0, uint32_t dt) {
  asm volatile("{\n.reg .pred p;\n.reg .u32 c;\nLOOP:\nmov.u32 c, %%clock;\nsub.u32 c, c, %0;\nsetp.lt.u32 p, c, %1;\n@p nanosleep.u32 100;\n@p bra LOOP;\n}\n" :: "r"(t0), "r"(dt) : "memory");
}
__device__ __forceinline__ void mbar_init(uint32_t bar, uint32_t cnt) { asm volatile("mbarrier.init.shared::cta.b64 [%0], %1;" :: "r"(bar), "r"(cnt) : "memory"); }
__device__ __forceinline__ void mbar_expect_tx(uint32_t bar, uint32_t bytes) { asm volatile("mbarrier.arrive.expect_tx.shared::cta.b64 _, [%0], %1;" :: "r"(bar), "r"(bytes) : "memory"); }
__device__ __forceinline__ void mbar_arrive(uint32_t bar) { asm volatile("mbarrier.arrive.shared::cta.b64 _, [%0];" :: "r"(bar) : "memory"); }
__device__ __forceinline__ void mbar_arrive_remote(uint32_t cluster_addr) { asm volatile("mbarrier.arrive.shared::cluster.b64 _, [%0];" :: "r"(cluster_addr) : "memory"); }
__device__ __forceinline__ void mbar_wait_bounded(uint32_t bar, uint32_t parity) {
  asm volatile("{\n.reg .pred p;\n.reg .u32 n;\nmov.u32 n, 0;\n"
               "LOOP:\nmbarrier.try_wait.parity.shared::cta.b64 p, [%0], %1;\nadd.u32 n, n, 1;\nsetp.ge.or.u32 p, n, 0x20000, p;\n@!p bra LOOP;\n}\n" :: "r"(bar), "r"(parity) : "memory");
}
__device__ __forceinline__ void mbar_wait(uint32_t bar, uint32_t parity) {
  asm volatile("{\n.reg .pred p;\nLOOP:\nmbarrier.try_wait.parity.shared::cta.b64 p, [%0], %1;\n@!p bra LOOP;\n}\n" :: "r"(bar), "r"(parity) : "memory");
}
__device__ __forceinline__ void tma_load_2d(uint32_t dst, const CUtensorMap* tm, uint32_t bar, int c0, int c1) {
  asm volatile("cp.async.bulk.tensor.2d.shared::cluster.global.mbarrier::complete_tx::bytes [%0], [%1, {%3, %4}], [%2];"
    :: "r"(dst), "l"(tm), "r"(bar), "r"(c0), "r"(c1) : "memory");
}
__device__ __forceinline__ void tma_load_2d_hint(uint32_t dst, const CUtensorMap* tm, uint32_t bar, int c0, int c1, uint64_t pol) {
  asm volatile("cp.async.bulk.tensor.2d.shared::cluster.global.mbarrier::complete_tx::bytes.L2::cache_hint [%0], [%1, {%3, %4}], [%2], %5;"
    :: "r"(dst), "l"(tm), "r"(bar), "r"(c0), "r"(c1), "l"(pol) : "memory");
}
__device__ __forceinline__ uint64_t policy_evict_first() { uint64_t p; asm volatile("createpolicy.fractional.L2::evict_first.b64 %0, 1.0;" : "=l"(p)); return p; }
__device__ __forceinline__ void tma_store_2d(const CUtensorMap* tm, uint32_t src, int c0, int c1) {
  asm volatile("cp.async.bulk.tensor.2d.global.shared::cta.bulk_group [%0, {%2, %3}], [%1];" :: "l"(tm), "r"(src), "r"(c0), "r"(c1) : "memory");
}
__device__ __forceinline__ void bulk_load(uint32_t dst, const void* src, uint32_t bytes, uint32_t bar) {
  asm volatile("cp.async.bulk.shared::cluster.global.mbarrier::complete_tx::bytes [%0], [%1], %2, [%3];" :: "r"(dst), "l"(src), "r"(bytes), "r"(bar) : "memory");
}
__device__ __forceinline__ void prefetch_l2(const void* p) { asm volatile("prefetch.global.L2 [%0];" :: "l"(p)); }
__device__ __forceinline__ void bulk_commit() { asm volatile("cp.async.bulk.commit_group;" ::: "memory"); }
__device__ __forceinline__ void bulk_wait_all() { asm volatile("cp.async.bulk.wait_group 0;" ::: "memory"); }
__device__ __forceinline__ void fence_async_smem() { asm volatile("fence.proxy.async.shared::cta;" ::: "memory"); }
__device__ __forceinline__ void wgmma_fence() { asm volatile("wgmma.fence.sync.aligned;" ::: "memory"); }
__device__ __forceinline__ void wgmma_commit() { asm volatile("wgmma.commit_group.sync.aligned;" ::: "memory"); }
template<int N> __device__ __forceinline__ void wgmma_wait() { asm volatile("wgmma.wait_group.sync.aligned %0;" :: "n"(N) : "memory"); }
__device__ __forceinline__ void bar_sync(int id, int n) { asm volatile("bar.sync %0, %1;" :: "r"(id), "r"(n) : "memory"); }
__device__ __forceinline__ void bar_arrive(int id, int n) { asm volatile("bar.arrive %0, %1;" :: "r"(id), "r"(n) : "memory"); }
__device__ __forceinline__ void cluster_wait() { asm volatile("barrier.cluster.wait.aligned;" ::: "memory"); }
template<int R> __device__ __forceinline__ void reg_inc() { asm volatile("setmaxnreg.inc.sync.aligned.u32 %0;" :: "n"(R)); }
template<int R> __device__ __forceinline__ void reg_dec() { asm volatile("setmaxnreg.dec.sync.aligned.u32 %0;" :: "n"(R)); }
__device__ __forceinline__ bool elect_one() {
  uint32_t p;
  asm volatile("{\n.reg .pred q;\nelect.sync _|q, 0xffffffff;\nselp.u32 %0, 1, 0, q;\n}\n" : "=r"(p));
  return p != 0;
}
__device__ __forceinline__ uint32_t mapa(uint32_t addr, uint32_t cta) { uint32_t r; asm volatile("mapa.shared::cluster.u32 %0, %1, %2;" : "=r"(r) : "r"(addr), "r"(cta)); return r; }
__device__ __forceinline__ void st_async_v4(uint32_t addr, uint32_t bar, uint32_t a, uint32_t b, uint32_t c, uint32_t d) {
  asm volatile("st.async.weak.shared::cluster.mbarrier::complete_tx::bytes.v4.b32 [%0], {%2, %3, %4, %5}, [%1];" :: "r"(addr), "r"(bar), "r"(a), "r"(b), "r"(c), "r"(d) : "memory");
}
__device__ __forceinline__ void st_async_b32(uint32_t addr, uint32_t bar, uint32_t a) {
  asm volatile("st.async.weak.shared::cluster.mbarrier::complete_tx::bytes.b32 [%0], %2, [%1];" :: "r"(addr), "r"(bar), "r"(a) : "memory");
}
__device__ __forceinline__ void stsm_x4(uint32_t addr, uint32_t a, uint32_t b, uint32_t c, uint32_t d) {
  asm volatile("stmatrix.sync.aligned.m8n8.x4.shared.b16 [%0], {%1, %2, %3, %4};" :: "r"(addr), "r"(a), "r"(b), "r"(c), "r"(d) : "memory");
}
__device__ __forceinline__ void stsm_x4_t(uint32_t addr, uint32_t a, uint32_t b, uint32_t c, uint32_t d) {
  asm volatile("stmatrix.sync.aligned.m8n8.x4.trans.shared.b16 [%0], {%1, %2, %3, %4};" :: "r"(addr), "r"(a), "r"(b), "r"(c), "r"(d) : "memory");
}
__device__ __forceinline__ uint4 lds128(uint32_t addr) { uint4 v; asm volatile("ld.shared.v4.b32 {%0, %1, %2, %3}, [%4];" : "=r"(v.x), "=r"(v.y), "=r"(v.z), "=r"(v.w) : "r"(addr) : "memory"); return v; }
extern __shared__ __align__(1024) uint8_t smem_raw[];
template<class T> __device__ __forceinline__ T& SM(int off) { return *reinterpret_cast<T*>(smem_raw + off); }
__device__ __forceinline__ uint4 ldg128(const void* p) { uint4 v; asm volatile("ld.global.L1::no_allocate.v4.b32 {%0, %1, %2, %3}, [%4];" : "=r"(v.x), "=r"(v.y), "=r"(v.z), "=r"(v.w) : "l"(p) : "memory"); return v; }
__device__ __forceinline__ void pkt_st128(void* p, uint32_t a, uint32_t b, uint32_t c, uint32_t d) {
  asm volatile("{\n.reg .b128 v;\n.reg .b64 lo, hi;\nmov.b64 lo, {%1, %2};\nmov.b64 hi, {%3, %4};\nmov.b128 v, {lo, hi};\nst.relaxed.gpu.global.b128 [%0], v;\n}\n"
    :: "l"(p), "r"(a), "r"(b), "r"(c), "r"(d) : "memory");
}
__device__ __forceinline__ uint4 pkt_ld128(const void* p) {
  uint4 r;
  asm volatile("{\n.reg .b128 v;\n.reg .b64 lo, hi;\nld.relaxed.gpu.global.b128 v, [%4];\nmov.b128 {lo, hi}, v;\nmov.b64 {%0, %1}, lo;\nmov.b64 {%2, %3}, hi;\n}\n"
    : "=r"(r.x), "=r"(r.y), "=r"(r.z), "=r"(r.w) : "l"(p) : "memory");
  return r;
}
__device__ __forceinline__ void pkt_st64(void* p, uint32_t a, uint32_t b) {
  asm volatile("{\n.reg .b64 v;\nmov.b64 v, {%1, %2};\nst.relaxed.gpu.global.b64 [%0], v;\n}\n" :: "l"(p), "r"(a), "r"(b) : "memory");
}
__device__ __forceinline__ uint2 pkt_ld64(const void* p) {
  uint2 r;
  asm volatile("{\n.reg .b64 v;\nld.relaxed.gpu.global.b64 v, [%2];\nmov.b64 {%0, %1}, v;\n}\n" : "=r"(r.x), "=r"(r.y) : "l"(p) : "memory");
  return r;
}
__device__ __forceinline__ uint32_t ld_relaxed32(const void* p) { uint32_t v; asm volatile("ld.relaxed.gpu.global.b32 %0, [%1];" : "=r"(v) : "l"(p) : "memory"); return v; }
__device__ __forceinline__ uint32_t ld_acquire32(const void* p) { uint32_t v; asm volatile("ld.acquire.gpu.global.b32 %0, [%1];" : "=r"(v) : "l"(p) : "memory"); return v; }
__device__ __forceinline__ void st_relaxed32(void* p, uint32_t v) { asm volatile("st.relaxed.gpu.global.b32 [%0], %1;" :: "l"(p), "r"(v) : "memory"); }
__device__ __forceinline__ uint32_t poll64(const void* p, uint32_t tag, int ns) {
  uint2 v; uint32_t n = 0;
  bool more;
#pragma unroll 1
  do {
    v = pkt_ld64(p);
    more = v.y != tag && ++n < SPIN_LIMIT;
    if (more) { __nanosleep(ns); }
  } while (more);
  return v.x;
}
__device__ __forceinline__ uint32_t poll64_warp(const void* p, uint32_t tag, int ns) {
  uint2 v; uint32_t n = 0;
  bool more;
#pragma unroll 1
  do {
    v = pkt_ld64(p);
    more = !(__all_sync(0xffffffffu, v.y == tag)) && ++n < SPIN_LIMIT;
    if (more) { __nanosleep(ns); }
  } while (more);
  return v.x;
}
__device__ __forceinline__ uint32_t code_of(uint32_t tag) { return tag % 3u + 1u; }
__device__ __forceinline__ uint32_t with_bit(uint32_t v, uint32_t bit) { return (v & ~1u) | (bit & 1u); }
__device__ __forceinline__ uint32_t with_bit(float v, uint32_t bit) { return with_bit(__float_as_uint(v), bit); }
__device__ __forceinline__ float no_bit(uint32_t v) { return __uint_as_float(v & ~1u); }
__device__ __forceinline__ void chk(uint32_t& bad, uint32_t a, uint32_t want) { bad |= a ^ want; asm("" : "+r"(bad)); }
__device__ __forceinline__ void chk_code(uint32_t& bad, const uint4& v, uint32_t c0, uint32_t c1) { chk(bad, v.x, c0); chk(bad, v.y, c1); chk(bad, v.z, c0); chk(bad, v.w, c1); }
__device__ __forceinline__ uint32_t pack_bf16(float lo, float hi) { uint32_t r; asm("cvt.rn.bf16x2.f32 %0, %1, %2;" : "=r"(r) : "f"(hi), "f"(lo)); return r; }
__device__ __forceinline__ float bf_lo(uint32_t v) { return __uint_as_float(v << 16); }
__device__ __forceinline__ float bf_hi(uint32_t v) { return __uint_as_float(v & 0xFFFF0000u); }
__device__ __forceinline__ float bf16r(float x) { return __uint_as_float(pack_bf16(0.f, x)); }
__device__ __forceinline__ void st_bf16(bf16* p, float x) { *reinterpret_cast<uint16_t*>(p) = (uint16_t)pack_bf16(x, 0.f); }
__device__ __forceinline__ float fast_rcp(float x) { float r; asm("rcp.approx.ftz.f32 %0, %1;" : "=f"(r) : "f"(x)); return r; }
__device__ __forceinline__ float ldbf(const bf16* p) { return __bfloat162float(*p); }
__device__ __forceinline__ uint32_t badd2(uint32_t a, uint32_t b) { uint32_t r; asm("add.rn.bf16x2 %0, %1, %2;" : "=r"(r) : "r"(a), "r"(b)); return r; }
__device__ __forceinline__ uint32_t bfma2(uint32_t a, uint32_t b, uint32_t c) { uint32_t r; asm("fma.rn.bf16x2 %0, %1, %2, %3;" : "=r"(r) : "r"(a), "r"(b), "r"(c)); return r; }
__device__ __forceinline__ float warp_sum(float v) {
#pragma unroll
  for (int o = 16; o > 0; o >>= 1) v += __shfl_xor_sync(0xffffffffu, v, o);
  return v;
}
template<int N> __device__ __forceinline__ void fold(float* v, int o, int lane) {
  const bool up = lane & o;
#pragma unroll
  for (int i = 0; i < N / 2; i++) {
    const float keep = up ? v[N / 2 + i] : v[i], send = up ? v[i] : v[N / 2 + i];
    v[i] = keep + __shfl_xor_sync(0xffffffffu, send, o);
  }
}
__device__ __forceinline__ uint32_t make_key(float r_bf, int row) {
  const uint32_t u = __float_as_uint(r_bf);
  return (((u & 0x80000000u) ? ~u : (u | 0x80000000u)) & 0xFFFF0000u) | (0xFFFFu - (uint32_t)row);
}
__device__ __forceinline__ int key_row(uint32_t key) { return (0xFFFF - (int)(key & 0xFFFFu)) & 2047; }
__device__ __forceinline__ float key_val(uint32_t key) { const uint32_t o = key & 0xFFFF0000u; return __uint_as_float((o & 0x80000000u) ? (o & 0x7FFFFFFFu) : (~o & 0xFFFF0000u)); }
__device__ __forceinline__ float ref_sd(float var) { float r; asm("sqrt.approx.ftz.f32 %0, %1;" : "=f"(r) : "f"(bf16r(bf16r(var) + 1e-5f))); return bf16r(r); }
__device__ __forceinline__ uint64_t make_desc(uint32_t addr) { return (uint64_t)((addr & 0x3FFFF) >> 4) | ((uint64_t)64 << 32) | ((uint64_t)1 << 62); }
__device__ __forceinline__ uint64_t make_desc_noswz(uint32_t addr) { return (uint64_t)((addr & 0x3FFFF) >> 4) | ((uint64_t)8 << 32); }
#define ACC8(d, o) "+f"(d[o]), "+f"(d[o + 1]), "+f"(d[o + 2]), "+f"(d[o + 3]), "+f"(d[o + 4]), "+f"(d[o + 5]), "+f"(d[o + 6]), "+f"(d[o + 7])
#define ACC64(d, o) ACC8(d, o), ACC8(d, o + 8), ACC8(d, o + 16), ACC8(d, o + 24), ACC8(d, o + 32), ACC8(d, o + 40), ACC8(d, o + 48), ACC8(d, o + 56)
#define REGS64 "%0, %1, %2, %3, %4, %5, %6, %7, %8, %9, %10, %11, %12, %13, %14, %15, %16, %17, %18, %19, %20, %21, %22, %23, %24, %25, %26, %27, %28, %29, %30, %31, " \
    "%32, %33, %34, %35, %36, %37, %38, %39, %40, %41, %42, %43, %44, %45, %46, %47, %48, %49, %50, %51, %52, %53, %54, %55, %56, %57, %58, %59, %60, %61, %62, %63"
#define REGS128 REGS64 ", %64, %65, %66, %67, %68, %69, %70, %71, %72, %73, %74, %75, %76, %77, %78, %79, %80, %81, %82, %83, %84, %85, %86, %87, %88, %89, %90, %91, %92, %93, %94, %95, " \
    "%96, %97, %98, %99, %100, %101, %102, %103, %104, %105, %106, %107, %108, %109, %110, %111, %112, %113, %114, %115, %116, %117, %118, %119, %120, %121, %122, %123, %124, %125, %126, %127"
__device__ __forceinline__ void wgmma_n256(float (&d)[128], uint64_t da, uint64_t db) {
  asm volatile("wgmma.mma_async.sync.aligned.m64n256k16.f32.bf16.bf16 {" REGS128 "}, %128, %129, 1, 1, 1, 0, 0;\n"
    : ACC64(d, 0), ACC64(d, 64) : "l"(da), "l"(db));
}
#define OUT8(d, o) "=f"(d[o]), "=f"(d[o + 1]), "=f"(d[o + 2]), "=f"(d[o + 3]), "=f"(d[o + 4]), "=f"(d[o + 5]), "=f"(d[o + 6]), "=f"(d[o + 7])
#define OUT64(d, o) OUT8(d, o), OUT8(d, o + 8), OUT8(d, o + 16), OUT8(d, o + 24), OUT8(d, o + 32), OUT8(d, o + 40), OUT8(d, o + 48), OUT8(d, o + 56)
__device__ __forceinline__ void wgmma_n256_rs_init(float (&d)[128], const uint32_t* a, uint64_t db) {
  asm volatile("wgmma.mma_async.sync.aligned.m64n256k16.f32.bf16.bf16 {" REGS128 "}, {%128, %129, %130, %131}, %132, 0, 1, 1, 0;\n"
    : OUT64(d, 0), OUT64(d, 64) : "r"(a[0]), "r"(a[1]), "r"(a[2]), "r"(a[3]), "l"(db));
}
__device__ __forceinline__ void wgmma_n256_rs(float (&d)[128], const uint32_t* a, uint64_t db) {
  asm volatile("wgmma.mma_async.sync.aligned.m64n256k16.f32.bf16.bf16 {" REGS128 "}, {%128, %129, %130, %131}, %132, 1, 1, 1, 0;\n"
    : ACC64(d, 0), ACC64(d, 64) : "r"(a[0]), "r"(a[1]), "r"(a[2]), "r"(a[3]), "l"(db));
}
template<int ACCUM> __device__ __forceinline__ void wgmma_n8_rs(float (&d)[4], const uint32_t* a, uint64_t db) {
  asm volatile("wgmma.mma_async.sync.aligned.m64n8k16.f32.bf16.bf16 {%0, %1, %2, %3}, {%4, %5, %6, %7}, %8, %9, 1, 1, 0;\n"
    : "+f"(d[0]), "+f"(d[1]), "+f"(d[2]), "+f"(d[3]) : "r"(a[0]), "r"(a[1]), "r"(a[2]), "r"(a[3]), "l"(db), "n"(ACCUM));
}
__device__ __forceinline__ void wgmma_n8(float (&d)[4], uint64_t da, uint64_t db) {
  asm volatile("wgmma.mma_async.sync.aligned.m64n8k16.f32.bf16.bf16 {%0, %1, %2, %3}, %4, %5, 1, 1, 1, 0, 0;\n"
    : "+f"(d[0]), "+f"(d[1]), "+f"(d[2]), "+f"(d[3]) : "l"(da), "l"(db));
}
__device__ __forceinline__ void wgmma_n128(float (&d)[64], uint64_t da, uint64_t db) {
  asm volatile("wgmma.mma_async.sync.aligned.m64n128k16.f32.bf16.bf16 {" REGS64 "}, %64, %65, 1, 1, 1, 0, 0;\n" : ACC64(d, 0) : "l"(da), "l"(db));
}
#define ACC32(d, o) ACC8(d, o), ACC8(d, o + 8), ACC8(d, o + 16), ACC8(d, o + 24)
#define REGS32 "%0, %1, %2, %3, %4, %5, %6, %7, %8, %9, %10, %11, %12, %13, %14, %15, %16, %17, %18, %19, %20, %21, %22, %23, %24, %25, %26, %27, %28, %29, %30, %31"
#define REGS96 REGS64 ", %64, %65, %66, %67, %68, %69, %70, %71, %72, %73, %74, %75, %76, %77, %78, %79, %80, %81, %82, %83, %84, %85, %86, %87, %88, %89, %90, %91, %92, %93, %94, %95"
__device__ __forceinline__ void wgmma_part(float (&d)[32], uint64_t da, uint64_t db) {
  asm volatile("wgmma.mma_async.sync.aligned.m64n64k16.f32.bf16.bf16 {" REGS32 "}, %32, %33, 1, 1, 1, 0, 0;\n" : ACC32(d, 0) : "l"(da), "l"(db));
}
__device__ __forceinline__ void wgmma_part(float (&d)[96], uint64_t da, uint64_t db) {
  asm volatile("wgmma.mma_async.sync.aligned.m64n192k16.f32.bf16.bf16 {" REGS96 "}, %96, %97, 1, 1, 1, 0, 0;\n" : ACC64(d, 0), ACC32(d, 64) : "l"(da), "l"(db));
}
template<int N> __device__ __forceinline__ void fence_regs(float (&d)[N]) {
#pragma unroll
  for (int i = 0; i < N; i++) asm volatile("" : "+f"(d[i]) :: "memory");
}
__device__ __forceinline__ void mma16816(float (&c)[4], uint32_t a0, uint32_t a1, uint32_t a2, uint32_t a3, uint32_t b0, uint32_t b1) {
  asm volatile("mma.sync.aligned.m16n8k16.row.col.f32.bf16.bf16.f32 {%0, %1, %2, %3}, {%4, %5, %6, %7}, {%8, %9}, {%0, %1, %2, %3};"
               : "+f"(c[0]), "+f"(c[1]), "+f"(c[2]), "+f"(c[3]) : "r"(a0), "r"(a1), "r"(a2), "r"(a3), "r"(b0), "r"(b1));
}
__device__ __forceinline__ void fma8(float* acc, const uint4& v, float x) {
  acc[0] = fmaf(bf_lo(v.x), x, acc[0]); acc[1] = fmaf(bf_hi(v.x), x, acc[1]); acc[2] = fmaf(bf_lo(v.y), x, acc[2]); acc[3] = fmaf(bf_hi(v.y), x, acc[3]);
  acc[4] = fmaf(bf_lo(v.z), x, acc[4]); acc[5] = fmaf(bf_hi(v.z), x, acc[5]); acc[6] = fmaf(bf_lo(v.w), x, acc[6]); acc[7] = fmaf(bf_hi(v.w), x, acc[7]);
}
template<int PITCH> __device__ __forceinline__ void gemv8x8(float (&acc)[8], uint32_t addr, const float (&x)[8]) {
  uint4 v[2][2];
  v[0][0] = lds128(addr); v[0][1] = lds128(addr + PITCH);
#pragma unroll
  for (int b = 0; b < 4; b++) {
    if (b < 3) { v[(b + 1) & 1][0] = lds128(addr + (2 * b + 2) * PITCH); v[(b + 1) & 1][1] = lds128(addr + (2 * b + 3) * PITCH); }
    acc[0] += __uint_as_float(zero_here());
#pragma unroll
    for (int c = 0; c < 4; c++) {
      if (c == 2) acc[4] += __uint_as_float(zero_here());
#pragma unroll
      for (int r = 0; r < 2; r++) {
        const uint4& q = v[b & 1][r];
        const uint32_t u = c == 0 ? q.x : c == 1 ? q.y : c == 2 ? q.z : q.w;
        acc[2 * c] = fmaf(bf_lo(u), x[2 * b + r], acc[2 * c]); acc[2 * c + 1] = fmaf(bf_hi(u), x[2 * b + r], acc[2 * c + 1]);
      }
    }
  }
}
__device__ __forceinline__ float swiglu(float g, float u) {
  g = bf16r(g); u = bf16r(u);
  return bf16r(bf16r(g * fast_rcp(1.f + __expf(-g))) * u);
}

#define CT(slot) do {} while (0)
#define TIM(slot) do {} while (0)

constexpr int H_BUF0 = 0, H_BUF1 = 16384, H_RED = 32768, H_KEYS = H_RED + 1024, H_ROW = H_KEYS + 1024, H_ACT = H_ROW + 8192, H_PART = H_ACT + 4096;
__device__ __forceinline__ void hsync() { bar_sync(NB_H, 256); }
template<int N> __device__ __forceinline__ void block_sum(float (&v)[N], int warp, int lane) {
#pragma unroll
  for (int i = 0; i < N; i++) v[i] = warp_sum(v[i]);
  hsync();
  if (lane == 0) {
#pragma unroll
    for (int i = 0; i < N; i++) SM<float>(H_RED + (i * 8 + warp) * 4) = v[i];
  }
  hsync();
#pragma unroll
  for (int i = 0; i < N; i++) {
    const float4 a = SM<float4>(H_RED + i * 32), b = SM<float4>(H_RED + i * 32 + 16);
    v[i] = ((a.x + a.y) + (a.z + a.w)) + ((b.x + b.y) + (b.z + b.w));
  }
}
__device__ __forceinline__ void fft_first(int j, float2 v0, float2 v1, float2 v2, float2 v3) {
  const float2 a = make_float2(v0.x + v2.x, v0.y + v2.y), b = make_float2(v0.x - v2.x, v0.y - v2.y);
  const float2 c = make_float2(v1.x + v3.x, v1.y + v3.y), d = make_float2(v1.y - v3.y, v3.x - v1.x);
  SM<float4>(H_BUF1 + j * 32) = make_float4(a.x + c.x, a.y + c.y, b.x + d.x, b.y + d.y);
  SM<float4>(H_BUF1 + j * 32 + 16) = make_float4(a.x - c.x, a.y - c.y, b.x - d.x, b.y - d.y);
}
template<int NB> __device__ __forceinline__ void fft_passes(int tid) {
  constexpr int q = 256 * NB;
#pragma unroll 1
  for (int ps = 1; ps < 5; ps++) {
    const int ns = 1 << (2 * ps), k = tid & (ns - 1);
    float s1, c1;
    __sincosf(-1.57079632679f * __fdividef((float)k, (float)ns), &s1, &c1);
    const float c2 = c1 * c1 - s1 * s1, s2 = 2.f * c1 * s1, c3 = c1 * c2 - s1 * s2, s3 = c1 * s2 + s1 * c2;
    hsync();
#pragma unroll
    for (int i = 0; i < NB; i++) {
      const int j = tid + 256 * i;
      const float2* in = &SM<float2>((ps & 1) ? H_BUF1 : H_BUF0);
      float2* o = &SM<float2>((ps & 1) ? H_BUF0 : H_BUF1) + (j - k) * 4 + k;
      const float2 v0 = in[j], x1 = in[j + q], x2 = in[j + 2 * q], x3 = in[j + 3 * q];
      const float2 v1 = make_float2(x1.x * c1 - x1.y * s1, x1.x * s1 + x1.y * c1);
      const float2 v2 = make_float2(x2.x * c2 - x2.y * s2, x2.x * s2 + x2.y * c2);
      const float2 v3 = make_float2(x3.x * c3 - x3.y * s3, x3.x * s3 + x3.y * c3);
      const float2 a = make_float2(v0.x + v2.x, v0.y + v2.y), b = make_float2(v0.x - v2.x, v0.y - v2.y);
      const float2 c = make_float2(v1.x + v3.x, v1.y + v3.y), d = make_float2(v1.y - v3.y, v3.x - v1.x);
      o[0] = make_float2(a.x + c.x, a.y + c.y); o[ns] = make_float2(b.x + d.x, b.y + d.y);
      o[2 * ns] = make_float2(a.x - c.x, a.y - c.y); o[3 * ns] = make_float2(b.x - d.x, b.y - d.y);
    }
  }
  hsync();
}
template<int NR> __device__ __forceinline__ void ln_rows(const float (&h)[NR][4], float (&hn)[NR][4], int warp, int lane) {
  float s[NR], q[NR];
#pragma unroll
  for (int i = 0; i < NR; i++) s[i] = (h[i][0] + h[i][1]) + (h[i][2] + h[i][3]);
  block_sum(s, warp, lane);
#pragma unroll
  for (int i = 0; i < NR; i++) {
    s[i] *= 1.f / 1024.f; q[i] = 0.f;
#pragma unroll
    for (int z = 0; z < 4; z++) q[i] = fmaf(h[i][z] - s[i], h[i][z] - s[i], q[i]);
  }
  block_sum(q, warp, lane);
#pragma unroll
  for (int i = 0; i < NR; i++) {
    const float mb = bf16r(s[i]), inv = fast_rcp(ref_sd(q[i] * (1.f / 1024.f)));
#pragma unroll
    for (int z = 0; z < 4; z++) hn[i][z] = bf16r(bf16r(h[i][z] - mb) * inv);
  }
}
__device__ __forceinline__ float sigmoid_bf(float r) { return bf16r(fast_rcp(1.f + __expf(-r))); }
__device__ __forceinline__ float routed_out(float h, float hn, float y, float sig) { return h + bf16r(hn + bf16r(bf16r(y) * sig)); }

__device__ __forceinline__ void helper_cta(const Params& p, const int hi, const uint32_t t_entry) {
  const int tid = threadIdx.x, warp = tid >> 5, lane = tid & 31;
  const float w0 = ldbf(p.wr + tid), w1 = ldbf(p.wr + tid + 256), w2 = ldbf(p.wr + tid + 512), w3 = ldbf(p.wr + tid + 768), wf = ldbf(p.wr);
  const uint32_t tag = ld_relaxed32(&p.sc->epoch) + 1;
  fft_first(tid, make_float2(w0, 0.f), make_float2(w1, 0.f), make_float2(w2, 0.f), make_float2(w3, 0.f));
  fft_passes<1>(tid);
  const uint32_t c0 = code_of(tag), c1 = c0 >> 1;
  {
    const float off = wf - SM<float>(H_BUF1) * (1.f / 1024.f);
    const float4 v = SM<float4>(H_BUF1 + tid * 32), u = SM<float4>(H_BUF1 + tid * 32 + 16);
    pkt_st128(&p.sc->u[hi * 512 + ((tid & 192) + (tid & 1) * 32 + ((tid >> 1) & 31)) * 2], with_bit(pack_bf16((tid ? v.x : 0.f) - off, v.z - off), c0), with_bit(pack_bf16(v.y, v.w), c1),
              with_bit(pack_bf16(u.x - off, u.z - off), c0), with_bit(pack_bf16(u.y, u.w), c1));
    hsync();
  }
  if (tid == 0) TIM(0);
  {
    float tw[8];
#pragma unroll
    for (int i = 0; i < 4; i++) __sincosf((float)(tid + 256 * i) * (-6.28318530718f / 2048.f), &tw[2 * i], &tw[2 * i + 1]);
    wait_clk(t_entry, Z_CLK);
    uint2 z[8]; uint32_t n = 0;
    bool more;
#pragma unroll 1
    do {
      uint32_t bad = 0;
#pragma unroll
      for (int i = 0; i < 8; i++) z[i] = pkt_ld64(reinterpret_cast<const uint2*>(&p.sc->xz[tid]) + 512 * i + 1);
#pragma unroll
      for (int i = 0; i < 8; i++) chk(bad, z[i].y, tag);
      more = bad && ++n < SPIN_LIMIT;
      if (more) { __nanosleep(150); }
    } while (more);
#pragma unroll
    for (int i = 0; i < 2; i++)
      fft_first(tid + 256 * i, make_float2(bf_lo(z[i].x), bf_hi(z[i].x)), make_float2(bf_lo(z[i + 2].x), bf_hi(z[i + 2].x)),
                make_float2(bf_lo(z[i + 4].x), bf_hi(z[i + 4].x)), make_float2(bf_lo(z[i + 6].x), bf_hi(z[i + 6].x)));
    if (tid == 0) TIM(7);
    fft_passes<2>(tid);
    if (tid == 0) TIM(1);
    uint32_t k8[8];
#pragma unroll
    for (int i = 0; i < 4; i++) {
      const int k = tid + 256 * i;
      const float2 v0 = SM<float2>(H_BUF1 + k * 8), v1 = SM<float2>(H_BUF1 + (k + 1024) * 8);
      const float w = v1.x * tw[2 * i + 1] - v1.y * tw[2 * i];
      const uint32_t a = __float_as_uint(v0.x + w), b = __float_as_uint(v0.x - w);
      k8[2 * i] = (((a & 0x80000000u) ? ~a : (a | 0x80000000u)) & ~2047u) | k;
      k8[2 * i + 1] = (((b & 0x80000000u) ? ~b : (b | 0x80000000u)) & ~2047u) | (k + 1024);
    }
    uint32_t lim = 0xFFFFFFFFu;
#pragma unroll 1
    for (int r = 0; r < 4; r++) {
      uint32_t mx = 0;
#pragma unroll
      for (int i = 0; i < 8; i++) mx = max(mx, k8[i] <= lim ? k8[i] : 0u);
      mx = __reduce_max_sync(0xffffffffu, mx);
      if (lane == 0) SM<uint32_t>(H_KEYS + (warp * 4 + r) * 4) = mx;
      lim = mx - 1;
    }
    hsync();
    if (tid < 32) {
      const uint32_t me = SM<uint32_t>(H_KEYS + tid * 4);
      int rank = 0;
#pragma unroll
      for (int i = 0; i < 8; i++) { const uint4 o = SM<uint4>(H_KEYS + i * 16); rank += (o.x > me) + (o.y > me) + (o.z > me) + (o.w > me); }
      if (rank < 8) SM<uint16_t>(H_KEYS + 256 + rank * 2) = me & 2047u;
    }
    hsync();
    if (tid >= 128) pkt_st64(&p.sc->cl[(hi * 32 + ((tid - 128) >> 2)) * 16 + (tid & 3)], SM<uint32_t>(H_KEYS + 256 + (tid & 3) * 4), tag);
  }
  const uint32_t cpair = SM<uint32_t>(H_KEYS + 256 + hi * 4);
  const int ca = cpair & 2047, cb = (cpair >> 16) & 2047;
  if (tid < 128) prefetch_l2(((tid & 32) ? p.Wim : p.Wre) + (size_t)((tid & 64) ? cb : ca) * 2048 + lane * 64);
  if (tid == 0) TIM(2);
}

__device__ __noinline__ void slow_path(const Params& p, int grp, int eps, uint32_t tag, uint32_t key, int win, float mb, float inv) {
  const int tid = threadIdx.x, warp = tid >> 5, lane = tid & 31;
  uint32_t best = __reduce_max_sync(0xffffffffu, poll64(&p.sc->key[tid & 127], tag, 200));
  if (lane == 0) SM<uint32_t>(H_KEYS + warp * 4) = best;
  hsync();
  { const uint4 b4 = SM<uint4>(H_KEYS); best = max(max(b4.x, b4.y), max(b4.z, b4.w)); }
  const int tw = key_row(best), col = eps * 128 + (tid & 127);
  if ((tw >> 7) != grp) return;
  poll64(&p.sc->rdone[col >> 3], tag, 100);
  const uint32_t h0 = poll64(&p.sc->hrow[(tw >> 4) * 512 + 2 * tid], tag, 100), h1 = poll64(&p.sc->hrow[(tw >> 4) * 512 + 2 * tid + 1], tag, 100);
  float h[1][4] = {{bf_lo(h0), bf_hi(h0), bf_lo(h1), bf_hi(h1)}}, hn[1][4];
  ln_rows<1>(h, hn, warp, lane);
  SM<float4>(H_ROW + tid * 16) = make_float4(hn[0][0], hn[0][1], hn[0][2], hn[0][3]);
  SM<float4>(H_ROW + 4096 + tid * 16) = make_float4(h[0][0], h[0][1], h[0][2], h[0][3]);
  hsync();
#pragma unroll 1
  for (int ph = 0; ph < 2; ph++) {
    const int part = min(tid / 56, 3), fh = tid >> 7, len = ph ? 224 : 512, ld = ph ? 1024 : 3584;
    const bf16* wp = ph ? p.wdown + (eps * 448 + fh * 224) * 1024 + (tid & 127) * 8
                        : ((part & 1) ? p.wup : p.wgate) + (part >> 1) * 512 * 3584 + eps * 448 + min(tid - part * 56, 55) * 8;
    const int xo = ph ? H_ACT + fh * 224 * 4 : H_ROW + (part >> 1) * 2048;
    float acc[8] = {0.f, 0.f, 0.f, 0.f, 0.f, 0.f, 0.f, 0.f};
#pragma unroll 1
    for (int d = 0; d < len; d += 16) {
      uint4 v[16];
#pragma unroll
      for (int i = 0; i < 16; i++) v[i] = ldg128(wp + (d + i) * ld);
      acc[0] += __uint_as_float(zero_here());
#pragma unroll
      for (int i = 0; i < 16; i++) fma8(acc, v[i], SM<float>(xo + (d + i) * 4));
    }
    SM<float4>(H_PART + tid * 32) = make_float4(acc[0], acc[1], acc[2], acc[3]);
    SM<float4>(H_PART + tid * 32 + 16) = make_float4(acc[4], acc[5], acc[6], acc[7]);
    hsync();
    if (ph) break;
#pragma unroll 1
    for (int f = tid; f < 448; f += 256)
      SM<float>(H_ACT + f * 4) = swiglu(SM<float>(H_PART + f * 4) + SM<float>(H_PART + (896 + f) * 4), SM<float>(H_PART + (448 + f) * 4) + SM<float>(H_PART + (1344 + f) * 4));
    hsync();
  }
#pragma unroll 1
  for (int e = tid; e < 1024; e += 256) pkt_st64(&p.sc->fpart[eps * 1024 + e], __float_as_uint(SM<float>(H_PART + e * 4) + SM<float>(H_PART + (1024 + e) * 4)), tag);
  if (tid < 128) {
    float y = 0.f;
#pragma unroll 1
    for (int q = 0; q < 8; q++) y += __uint_as_float(poll64(&p.sc->fpart[q * 1024 + col], tag, 200));
    st_bf16(p.out + tw * 1024 + col, routed_out(SM<float>(H_ROW + 4096 + col * 4), SM<float>(H_ROW + col * 4), y, sigmoid_bf(key_val(best))));
    const uint32_t a = poll64(&p.sc->ch[win * 512 + (col >> 4) * 8 + (col & 7)], tag, 100);
    const float hc = (col & 8) ? bf_hi(a) : bf_lo(a);
    st_bf16(p.out + key_row(key) * 1024 + col, hc + bf16r(bf16r(hc - mb) * inv));
  }
}

template<int MAP>
__global__ void __cluster_dims__(2, 1, 1) __launch_bounds__(NTHR, 1)
fnet_moe_kernel(const __grid_constant__ Params p) {
  const CUtensorMap* tmX0 = &p.tmX;
  asm volatile("" : "+l"(tmX0));
  const uint32_t t_entry = clk32();
  uint32_t smid;
  asm("mov.u32 %0, %%smid;" : "=r"(smid));
  const int tpc = smid >> 1, m = blockIdx.x & 1;
  if (MAP == 1 ? tpc >= 64 : (tpc >> 1) == 30) {
    if (threadIdx.x < 256) helper_cta(p, (tpc & 1) * 2 + m, t_entry);
    return;
  }
  const uint32_t sb = smem_u32(smem_raw);
  const int tid = threadIdx.x, lane = tid & 31;
  const int e7 = ((tpc - 32) * 37) >> 8;
  const int tau = MAP == 1 || tpc < 32 ? (tpc & 7) : (tpc < 60 ? tpc - 31 - 7 * e7 : 0);
  const int eps = MAP == 1 || tpc < 32 ? (tpc >> 3) : (tpc < 60 ? 4 + e7 : tpc - 58);
  const int cid = tau * 16 + eps * 2 + m;
  auto BAR = [&](int i) { return sb + OFF_BAR + 8 * i; };
  const CUtensorMap* tmD = &p.tmD0 + m;

  if ((tid >> 5) == 4) {
    if (elect_one()) {
      mbar_init(BAR(B_FULL), 1);
      asm volatile("fence.mbarrier_init.release.cluster;" ::: "memory");
      mbar_expect_tx(BAR(B_FULL), ST_BYTES);
      tma_load_2d(sb, tmX0 + 1 + m, BAR(B_FULL), 0, eps * 128);
      tma_load_2d(sb + A_BYTES, tmX0, BAR(B_FULL), 0, tau * 256);
      TIM(0);
    }
  }
  const int warp = __shfl_sync(0xffffffffu, tid >> 5, 0);
  if (warp < 6 && warp != 4) {
    const int wv = warp;
    if (elect_one()) {
      const uint32_t b0 = BAR(wv < 4 ? 8 * wv : B_GUX);
#pragma unroll
      for (int i = 0; i < 8; i++)
        if (i || wv) mbar_init(b0 + 8 * i, wv == 1 || (wv == 3 && i == B_STAT - 24) ? 4 : wv == 3 && i == B_CD - 24 ? 2 : 1);
      asm volatile("fence.mbarrier_init.release.cluster;" ::: "memory");
      if (wv == 3) { mbar_expect_tx(BAR(B_XCH), 16384); mbar_expect_tx(BAR(B_XCH + 1), 16384); }
      if (wv == 5) mbar_expect_tx(BAR(B_GUX), 256);
    }
  }
  __syncthreads();
  asm volatile("barrier.cluster.arrive.relaxed.aligned;" ::: "memory");

  if (warp >= 8) {
    auto stage = [&](int k) {
      if (warp == 11) {
        if (elect_one()) {
          while (clk32() - t_entry < ST1_CLK + (k - 1) * ST_GAP) {}
          mbar_expect_tx(BAR(B_FULL + k), ST_BYTES);
          tma_load_2d(sb + k * ST_BYTES + A_BYTES, &p.tmX, BAR(B_FULL + k), k * 64, tau * 256);
          tma_load_2d(sb + k * ST_BYTES, tmD, BAR(B_FULL + k), k * 64, eps * 128);
          TIM(k);
        }
        __syncwarp();
      }
    };
    reg_dec<72>();
    const uint32_t epoch = ld_relaxed32(&p.sc->epoch + threadIdx.y);
    const uint4 wq = ldg128(p.wr + (tid & 127) * 8);
#pragma unroll 1
    for (int k = 1; k < 4; k++) stage(k);
    cluster_wait();
    const int cid0 = cid;
    const uint32_t tag0 = __shfl_sync(0xffffffffu, epoch, 0) + 1, sb0 = sb;
    int a, lane, j, cid, tau, eps, m, grp, abrow, fc, src;
    uint32_t tag, c0, c1, sb, buf, bar0;
    bool ffn;
    auto BAR = [&](int i) { return sb + OFF_BAR + 8 * i; };
    auto fresh_ids = [&]() {
      const uint32_t z = uniform_zero_here();
      uint32_t l; asm volatile("mov.u32 %0, %%laneid;" : "=r"(l));
      a = warp - 8 + z; lane = l; j = a * 32 + l;
      cid = cid0 + z; tau = cid >> 4; eps = (cid >> 1) & 7; m = cid & 1; grp = tau * 2 + m; abrow = m * 1024 + eps * 128;
      const int ef = tau ? eps : eps ^ 5;
      ffn = ef > 0; fc = (tau * 7 + ef - 1) * 64; src = (fc >> 5) + m;
      tag = tag0 + z; c0 = code_of(tag); c1 = c0 >> 1;
      sb = sb0 + z; buf = sb + OFF_AUX + a * 8192; bar0 = BAR(B_AW + 2 * a);
    };
    fresh_ids();
    {
      const float s = warp_sum(((bf_lo(wq.x) + bf_hi(wq.x)) + (bf_lo(wq.y) + bf_hi(wq.y))) + ((bf_lo(wq.z) + bf_hi(wq.z)) + (bf_lo(wq.w) + bf_hi(wq.w))));
      if ((j >> 4) == eps) SM<uint4>(OFF_WR + (j & 15) * 16) = wq;
      if (lane == 0) { SM<float>(INFO_DS + a * 4) = s; SM<uint32_t>(INFO_ONES + a * 4) = 0x3F803F80u; }
    }
    const bf16* xrows = p.x + (cid * 16 + a * 4) * 1024;
    const bf16* drows = (cid < 64 ? p.Dre : p.Dim) + ((cid & 63) * 16 + a * 4) * 1024;
    fresh_ids();
    {
      wait_clk(t_entry, U_CLK);
      uint4 u[8]; uint32_t n = 0;
      bool more;
#pragma unroll 1
      do {
        uint32_t bad = 0;
#pragma unroll
        for (int q = 0; q < 8; q++) u[q] = pkt_ld128(&p.sc->u[a * 512 + lane * 2] + q * 64);
        if (n == 0 && lane == 0) { mbar_expect_tx(bar0, 4096); bulk_load(buf, xrows, 4096, bar0); }
#pragma unroll
        for (int q = 0; q < 8; q++) chk_code(bad, u[q], c0, c1);
        more = __any_sync(0xffffffffu, bad & 1) && ++n < SPIN_LIMIT;
        if (more) { __nanosleep(200); }
      } while (more);
      if (j == 0) TIM(96);
      if (lane == 0) { mbar_expect_tx(bar0 + 8, 4096); bulk_load(buf + 4096, xrows + 2048, 4096, bar0 + 8); }
#pragma unroll
      for (int q = 0; q < 8; q++) { u[q].x &= ~1u; u[q].y &= ~1u; u[q].z &= ~1u; u[q].w &= ~1u; }
#pragma unroll 1
      for (int r2 = 0; r2 < 2; r2++) {
        float v8[8];
        mbar_wait(bar0 + r2 * 8, 0);
        if (lane == 0) TIM(140 + r2 * 4 + a);
#pragma unroll
        for (int r = 0; r < 2; r++) {
          float s0 = 0.f, s1 = 0.f, q0 = 0.f, q1 = 0.f;
          uint32_t zr = 0, zi = 0;
#pragma unroll
          for (int q = 0; q < 4; q++) {
            const uint4 v = lds128(buf + r2 * 4096 + r * 2048 + (q * 32 + lane) * 16);
            const uint32_t ww[4] = {v.x, v.y, v.z, v.w};
#pragma unroll
            for (int z = 0; z < 4; z++) {
              const float lo = bf_lo(ww[z]), hi = bf_hi(ww[z]);
              s0 += lo; s1 += hi; q0 = fmaf(lo, lo, q0); q1 = fmaf(hi, hi, q1);
            }
            zr = bfma2(v.x, u[2 * q].x, zr); zi = bfma2(v.x, u[2 * q].y, zi); zr = bfma2(v.y, u[2 * q].z, zr); zi = bfma2(v.y, u[2 * q].w, zi);
            zr = bfma2(v.z, u[2 * q + 1].x, zr); zi = bfma2(v.z, u[2 * q + 1].y, zi); zr = bfma2(v.w, u[2 * q + 1].z, zr); zi = bfma2(v.w, u[2 * q + 1].w, zi);
          }
          v8[4 * r] = s0 + s1; v8[4 * r + 1] = q0 + q1; v8[4 * r + 2] = bf_lo(zr) + bf_hi(zr); v8[4 * r + 3] = bf_lo(zi) + bf_hi(zi);
        }
        fold<8>(v8, 16, lane);
        if (lane == 0) { mbar_expect_tx(bar0 + r2 * 8, 4096); bulk_load(buf + r2 * 4096, drows + r2 * 2048, 4096, bar0 + r2 * 8); }
        fold<4>(v8, 8, lane); fold<2>(v8, 4, lane);
        v8[0] += __shfl_xor_sync(0xffffffffu, v8[0], 2);
        v8[0] += __shfl_xor_sync(0xffffffffu, v8[0], 1);
        SM<float>(OFF_REM + a * 64 + r2 * 32 + (lane >> 2) * 4) = v8[0];
        if (lane == 0) TIM(148 + r2 * 4 + a);
      }
    }
    bar_sync(NB_AUX, 128);
    fresh_ids();
    if (a == 0 && lane < 16) {
      const float4 v = SM<float4>(OFF_REM + lane * 16);
      const float mean = v.x * (1.f / 1024.f), rs = fast_rcp(ref_sd(fmaxf(v.y * (1.f / 1024.f) - mean * mean, 0.f)));
      pkt_st128(&p.sc->xz[cid * 16 + lane], __float_as_uint(bf16r(mean)) | (tag & 0xFFFFu), __float_as_uint(rs), pack_bf16(v.z * rs, v.w * rs), tag);
    }
    if (j == 32) { const float4 v = SM<float4>(INFO_DS); SM<float2>(INFO_WSUM) = make_float2((v.x + v.y) + (v.z + v.w), __uint_as_float(tag)); }
    if (j == 0) TIM(98);
#pragma unroll 1
    for (int r2 = 0; r2 < 2; r2++) {
      mbar_wait(bar0 + r2 * 8, 1);
      const uint32_t da = buf + r2 * 4096 + (lane >> 4) * 2048 + (lane & 15) * 16;
      uint4 dv[3] = {lds128(da), lds128(da + 256), make_uint4(0, 0, 0, 0)};
      float s0 = 0.f, s1 = 0.f;
#pragma unroll
      for (int q = 0; q < 8; q++) {
        if (q < 6) dv[(q + 2) % 3] = lds128(da + (q + 2) * 256);
        s0 += __uint_as_float(zero_here());
        const uint4 v = dv[q % 3];
        s0 += bf_lo(v.x); s1 += bf_hi(v.x); s0 += bf_lo(v.y); s1 += bf_hi(v.y); s0 += bf_lo(v.z); s1 += bf_hi(v.z); s0 += bf_lo(v.w); s1 += bf_hi(v.w);
      }
      s0 += s1;
#pragma unroll
      for (int o = 8; o > 0; o >>= 1) s0 += __shfl_xor_sync(0xffffffffu, s0, o);
      SM<float>(INFO_DS2 + (a * 4 + r2 * 2 + (lane >> 4)) * 4) = s0;
    }
    bar_sync(NB_AUX, 128);
    if (a == 1 && lane < 16) pkt_st64(&p.sc->dsum[cid * 16 + lane], SM<uint32_t>(INFO_DS2 + lane * 4), tag);
    if (j == 0) TIM(99);
    {
      wait_clk(clk32(), XS_DELAY);
      uint2 v0, v1, cs; uint32_t n = 0;
      const uint32_t t16 = tag & 0xFFFFu;
      bool more;
#pragma unroll 1
      do {
        v0 = pkt_ld64(&p.sc->xz[tau * 256 + j]); v1 = pkt_ld64(&p.sc->xz[tau * 256 + j] + 128); cs = pkt_ld64(&p.sc->dsum[m * 1024 + eps * 128 + j]);
        more = !(__all_sync(0xffffffffu, (v0.x & 0xFFFFu) == t16 && (v1.x & 0xFFFFu) == t16 && cs.y == tag)) && ++n < SPIN_LIMIT;
        if (more) { __nanosleep(200); }
      } while (more);
      const int ro = OFF_RS + ((j & 7) >> 1) * 272 + (j >> 3) * 8 + (j & 1) * 4;
      SM<uint32_t>(ro) = v0.y ^ (m << 31); SM<uint32_t>(ro + 128) = v1.y ^ (m << 31);
      const uint32_t n0 = (v0.x >> 16) ^ 0x8000u, n1 = (v1.x >> 16) ^ 0x8000u;
      SM<uint4>(OFF_EXB + j * 16) = make_uint4(n0 | (n0 << 16), n0, 0, 0);
      SM<uint4>(OFF_EXB + 2048 + j * 16) = make_uint4(n1 | (n1 << 16), n1, 0, 0);
      const float c = 0.5f * __uint_as_float(cs.x), hi = bf16r(c), mid = bf16r(c - hi), lo = bf16r((c - hi) - mid);
      SM<uint4>(OFF_EXA + j * 16) = make_uint4((__float_as_uint(hi) >> 16) | __float_as_uint(mid), __float_as_uint(lo) >> 16, 0, 0);
      fence_async_smem();
      __syncwarp();
      if (lane == 0) mbar_arrive(BAR(B_STAT));
    }
    if (j == 0) TIM(100);
    auto all_published = [&](int half) {
      uint32_t n = 0;
#pragma unroll 1
      while (!__all_sync(0xffffffffu, ld_acquire32(&p.sc->abdone[(cid * 2 + half) * 32 + (lane & 7)]) == tag) && ++n < SPIN_LIMIT) {}
      if (lane == 31) {
        asm volatile("fence.proxy.async.global;" ::: "memory");
        mbar_arrive(BAR(B_ALL + half));
        TIM(80 + half);
      }
      __syncwarp();
    };
    {
      if (a == 3) {
        const uint32_t cl = poll64_warp(&p.sc->cl[cid * 16 + (lane & 3)], tag, 100);
        if (lane == 0) TIM(101);
        const bf16* wm = (m ? p.Wim : p.Wre) + tau * 256 + lane * 8;
        uint4 v[8];
#pragma unroll
        for (int i = 0; i < 8; i++) v[i] = ldg128(wm + ((__shfl_sync(0xffffffffu, cl, i >> 1) >> ((i & 1) * 16)) & 2047) * 2048);
        const int pos = cid * 4 + (lane & 3);
        const bf16* xc = p.x + ((__shfl_sync(0xffffffffu, cl, lane >> 3) >> ((lane & 4) * 4)) & 2047) * 1024 + (pos >> 3) * 16 + (pos & 7);
        const float x0 = ldbf(xc), x1 = ldbf(xc + 8), w0 = ldbf(p.wr + (pos >> 3) * 16 + (pos & 7)), w1 = ldbf(p.wr + (pos >> 3) * 16 + (pos & 7) + 8);
        if (lane < 4) SM<uint32_t>(INFO_CAND + lane * 4) = cl;
#pragma unroll
        for (int i = 0; i < 8; i++) SM<uint4>(OFF_WC + (lane >> 3) * 1024 + i * 128 + (((lane & 7) ^ i) << 4)) = v[i];
        fence_async_smem();
        __syncwarp();
        if (lane == 0) { mbar_arrive(BAR(B_WC)); TIM(102); }
        mbar_wait(BAR(B_CD), 0);
        wait_clk(clk32(), CP_DELAY);
        uint32_t n = 0;
        bool more;
#pragma unroll 1
        do {
          uint32_t bad = 0;
#pragma unroll
          for (int i = 0; i < 8; i++) v[i] = pkt_ld128(&p.sc->cpart[((lane >> 3) * 16 + ((lane >> 2) & 1)) * 512 + pos] + i * 1024);
#pragma unroll
          for (int i = 0; i < 8; i++) chk_code(bad, v[i], c0, c1);
          more = __any_sync(0xffffffffu, bad & 1) && ++n < SPIN_LIMIT;
          if (more) { __nanosleep(200); }
        } while (more);
        float y[4] = {0.f, 0.f, 0.f, 0.f};
#pragma unroll
        for (int i = 0; i < 8; i++) { y[0] += no_bit(v[i].x); y[2] += no_bit(v[i].y); y[1] += no_bit(v[i].z); y[3] += no_bit(v[i].w); }
#pragma unroll
        for (int i = 0; i < 4; i++) y[i] = bf16r(y[i]);
        __syncwarp();
        fold<4>(y, 4, lane);
        const uint32_t hp = pack_bf16(x0 + bf16r(y[0]), x1 + bf16r(y[1]));
        pkt_st64(&p.sc->ch[(lane >> 2) * 512 + pos], hp, tag);
        float st[3] = {bf_lo(hp) + bf_hi(hp), bf_lo(hp) * bf_lo(hp) + bf_hi(hp) * bf_hi(hp), bf_lo(hp) * w0 + bf_hi(hp) * w1};
#pragma unroll
        for (int o = 1; o < 4; o <<= 1) {
#pragma unroll
          for (int i = 0; i < 3; i++) st[i] += __shfl_xor_sync(0xffffffffu, st[i], o);
        }
        if ((lane & 3) == 0) pkt_st128(&p.sc->cs[cid * 8 + (lane >> 2)], with_bit(st[0], c0), with_bit(st[1], c1), __float_as_uint(st[2]), tag);
        if (lane == 0) TIM(119);
      }
      if (a < 2) {
        uint32_t* fl = lane < 2 ? &p.sc->abflag[(cid * 4 + 2 * a + lane) * 32] : &p.sc->abdone[(((cid & 15) + (lane & 7) * 16) * 2 + a) * 32 + tau];
        if (lane == 0) {
          if (a == 1) mbar_wait(BAR(B_SD), 0);
          const uint32_t t1 = clk32();
#pragma unroll 1
          for (int i = 2 * a; i < 2 + 6 * a; i++) {
            const int w = i & 1, c = (4 - (i >> 1)) & 3;
            if (a == 1) wait_clk(t1, (i - 2) * PUB_PACE);
            mbar_wait(BAR(B_EP + w * 4 + c), 0);
            TIM(64 + i);
            fence_async_smem();
            tma_store_2d(&p.tmAbS, sb + off_stage(c) + w * 8192, tau * 256 + c * 64, abrow + w * 64);
            if (w) { bulk_commit(); bulk_wait_all(); mbar_arrive(BAR(B_SD + c)); }
          }
          TIM(72 + a * 2);
          asm volatile("fence.proxy.async.global;" ::: "memory");
          asm volatile("st.release.gpu.global.b32 [%0], %1;" :: "l"(fl), "r"(tag) : "memory");
          TIM(73 + a * 2);
        }
        __syncwarp();
        if ((lane == 1 && a == 0) || (lane >> 3) == 1) st_relaxed32(fl, tag);
        if (a == 0) { __nanosleep(ALL_NS); all_published(0); }
        else {
          uint32_t n = 0;
#pragma unroll 1
          while (__any_sync(0xffffffffu, ld_acquire32(&p.sc->abflag[(((cid + 16) & 127) * 4 + 2) * 32]) != tag) && ++n < SPIN_LIMIT) {}
#pragma unroll 1
          for (int i = 0; i < 3; i++) {
            if (elect_one()) {
              if (i == 0) asm volatile("fence.proxy.async.global;" ::: "memory");
              mbar_wait(BAR(B_E23 + i), 0);
              tma_load_2d(sb + ((i + 3) & 3) * ST_BYTES, &p.tmAbL, BAR(B_FULL + ((i + 3) & 3)), (tau * 256 + 320 + i * 64) & 2047, abrow);
              TIM(82 + i);
            }
            __syncwarp();
            if (i == 1) all_published(1);
          }
        }
      } else if (a == 2) {
        const uint32_t* fl = &p.sc->abflag[(((cid + 16 + 16 * (lane & 1)) & 127) * 4 + (lane & 1)) * 32];
        mbar_wait(BAR(B_SD), 0);
        __nanosleep(LO_NS);
        uint32_t n = 0, seen = 0;
#pragma unroll 1
        for (int c = 0; c < 4; c++) {
#pragma unroll 1
          while (c < 2 && !((seen >> c) & 1) && ++n < SPIN_LIMIT) seen = __ballot_sync(0xffffffffu, ld_acquire32(fl) == tag);
          if (lane == c) {
            if (c != 1) mbar_wait(BAR(B_SD + c), 0);
            mbar_wait(BAR(c < 3 ? B_FULL + c : B_EMPTY), 0);
            if (c == 2) mbar_wait(BAR(B_ALL), 0);
            if (c < 2) asm volatile("fence.proxy.async.global;" ::: "memory");
            tma_load_2d(sb + c * ST_BYTES, &p.tmAbL, BAR(B_FULL + c), k_col(tau, 4 + c), abrow);
            TIM(130 + c);
          }
          __syncwarp();
        }
      }
      __syncwarp();
    }
    mbar_wait(BAR(B_CD), 0);
    mbar_wait(BAR(B_SD + 1), 0);
    const uint64_t pol_ef = policy_evict_first();
    auto load_unit = [&](int v) {
      if (elect_one()) {
        const uint32_t dst = buf + (v & 1) * 4096, bar = bar0 + (v & 1) * 8;
        mbar_expect_tx(bar, 4096);
        if (v < 8) {
          tma_load_2d_hint(dst, &p.tmG, bar, fc, m * 512 + (a * 8 + v) * 16, pol_ef);
          tma_load_2d_hint(dst + 2048, &p.tmU, bar, fc, m * 512 + (a * 8 + v) * 16, pol_ef);
        } else tma_load_2d_hint(dst, &p.tmDn, bar, a * 256, src * 32 + (v - 8) * 8, pol_ef);
      }
    };
    if (ffn) load_unit(0);
    if (a != 1) {
      bar_sync(NB_SEL, 96);
      wait_clk(clk32(), CS_DELAY);
      fresh_ids();
      if (a == 0 && lane < 8) {
        if (lane == 0) mbar_expect_tx(BAR(B_CH), 16384);
        bulk_load(sb + OFF_AUX + 4096 + (lane >> 1) * 8192 + (lane & 1) * 2048, &p.sc->ch[lane * 512 + m * 256], 2048, BAR(B_CH));
      }
      const int j3 = a ? j - 32 : j;
      uint4 v[11]; uint32_t n = 0;
      bool more;
#pragma unroll 1
      do {
#pragma unroll
        for (int i = 0; i < 11; i++) v[i] = pkt_ld128(&p.sc->cs[j3] + (i < 10 || a < 3 ? i * 96 : 0));
        uint32_t bad = 0;
#pragma unroll
        for (int i = 0; i < 11; i++) { chk(bad, v[i].x, c0); chk(bad, v[i].y, c1); }
        bad &= 1;
#pragma unroll
        for (int i = 0; i < 11; i++) chk(bad, v[i].w, tag);
        more = __any_sync(0xffffffffu, bad) && ++n < SPIN_LIMIT;
        if (more) __nanosleep(200);
      } while (more);
      if (j == 0) TIM(97);
      float st[3] = {0.f, 0.f, 0.f};
      if (a < 3) { st[0] = no_bit(v[10].x); st[1] = no_bit(v[10].y); st[2] = __uint_as_float(v[10].z); }
#pragma unroll
      for (int i = 0; i < 10; i++) { st[0] += no_bit(v[i].x); st[1] += no_bit(v[i].y); st[2] += __uint_as_float(v[i].z); }
#pragma unroll
      for (int o = 8; o < 32; o <<= 1) {
#pragma unroll
        for (int i = 0; i < 3; i++) st[i] += __shfl_xor_sync(0xffffffffu, st[i], o);
      }
      if (lane < 8) SM<float4>(OFF_XS + ((j3 >> 5) * 8 + lane) * 16) = make_float4(st[0], st[1], st[2], 0.f);
      bar_sync(NB_SEL, 96);
      const float4 f0 = SM<float4>(OFF_XS + (lane & 7) * 16), f1 = SM<float4>(OFF_XS + 128 + (lane & 7) * 16), f2 = SM<float4>(OFF_XS + 256 + (lane & 7) * 16);
      const float mu = ((f0.x + f1.x) + f2.x) * (1.f / 1024.f);
      float mb = bf16r(mu), inv = fast_rcp(ref_sd(fmaxf(((f0.y + f1.y) + f2.y) * (1.f / 1024.f) - mu * mu, 0.f)));
      const uint32_t kk = make_key(bf16r((((f0.z + f1.z) + f2.z) - mb * SM<float>(INFO_WSUM)) * inv), SM<uint16_t>(INFO_CAND + (lane & 7) * 2));
      const uint32_t key = __reduce_max_sync(0xffffffffu, kk);
      const int win = __ffs(__ballot_sync(0xffffffffu, kk == key)) - 1;
      mb = __shfl_sync(0xffffffffu, mb, win); inv = __shfl_sync(0xffffffffu, inv, win);
      if (j == 0) { SM<uint2>(INFO_KEY) = make_uint2(key, win); SM<float2>(INFO_LN) = make_float2(mb, inv); }
      mbar_wait(BAR(B_CH), 0);
      bar_sync(NB_SEL, 96);
#pragma unroll 1
      for (int i = j3; i < 128; i += 96) {
        uint4 r = lds128(sb + OFF_AUX + 4096 + (win >> 1) * 8192 + (win & 1) * 2048 + i * 16);
#pragma unroll 1
        while ((r.y != tag || r.w != tag) && ++n < SPIN_LIMIT) r = pkt_ld128(&p.sc->ch[win * 512 + m * 256 + 2 * i]);
        auto ln = [&](float h) { return bf16r(bf16r(h - mb) * inv); };
        const int d = (i >> 2) * 16 + (i & 3) * 2;
        SM<float2>(OFF_XS + d * 4) = make_float2(ln(bf_lo(r.x)), ln(bf_lo(r.z)));
        SM<float2>(OFF_XS + (d + 8) * 4) = make_float2(ln(bf_hi(r.x)), ln(bf_hi(r.z)));
      }
      __syncwarp();
    }
    bar_sync(NB_AUX, 128);
    if (j == 0) {
      mbar_arrive(BAR(B_INFO)); TIM(103);
      if (cid == 0) st_relaxed32(&p.sc->epoch, tag);
    }
    const uint32_t t2 = clk32();
    fresh_ids();
    uint2 hp2 = make_uint2(0, 0);
    const uint2* hpp = &p.sc->ch[SM<uint32_t>(INFO_KEY + 4) * 512 + (cid >> 1) * 8 + (lane & 7)];
    if (a == 3) { hp2 = pkt_ld64(hpp); if (lane == 0) asm volatile("prefetch.tensormap [%0];" :: "l"(&p.tmY) : "memory"); }
    if (ffn) {
      load_unit(1);
      const int r = lane >> 3;
      float acc[8] = {0.f, 0.f, 0.f, 0.f, 0.f, 0.f, 0.f, 0.f};
#pragma unroll 1
      for (int v = 0; v < 8; v++) {
        const uint4 x0 = lds128(sb + OFF_XS + ((a * 8 + v) * 16 + (r & 1) * 8) * 4), x1 = lds128(sb + OFF_XS + ((a * 8 + v) * 16 + (r & 1) * 8 + 4) * 4);
        const float xv[8] = {__uint_as_float(x0.x), __uint_as_float(x0.y), __uint_as_float(x0.z), __uint_as_float(x0.w), __uint_as_float(x1.x), __uint_as_float(x1.y), __uint_as_float(x1.z), __uint_as_float(x1.w)};
        mbar_wait(bar0 + (v & 1) * 8, (v >> 1) & 1);
        gemv8x8<128>(acc, buf + (v & 1) * 4096 + r * 1024 + (lane & 7) * 16, xv);
        fence_regs(acc);
        __syncwarp();
        wait_clk(t2, v * UNIT_PACE);
        load_unit(v + 2);
        if (j == 0) TIM(104 + v);
      }
      fold<8>(acc, 8, lane);
      bar_sync(NB_AUX, 128);
      SM<float4>(OFF_XS + (a * 128 + (r >> 1) * 64 + (lane & 7) * 8 + (r & 1) * 4) * 4) = make_float4(acc[0], acc[1], acc[2], acc[3]);
      bar_sync(NB_AUX, 128);
      auto psum = [&](int i) { return (SM<float>(OFF_XS + i * 4) + SM<float>(OFF_XS + (128 + i) * 4)) + (SM<float>(OFF_XS + (256 + i) * 4) + SM<float>(OFF_XS + (384 + i) * 4)); };
      if (a < 2) st_async_b32(mapa(sb + OFF_REM + j * 4, m ^ 1), mapa(BAR(B_GUX), m ^ 1), __float_as_uint(psum(a * 64 + (m ^ 1) * 32 + lane)));
      const float og = psum(m * 32 + lane), ou = psum(64 + m * 32 + lane);
      mbar_wait_bounded(BAR(B_GUX), 0);
      const float rg = SM<float>(OFF_REM + lane * 4), ru = SM<float>(OFF_REM + 128 + lane * 4);
      const float act = swiglu(m ? rg + og : og + rg, m ? ru + ou : ou + ru);
      if (j == 0) TIM(112);
      float y[8] = {0.f, 0.f, 0.f, 0.f, 0.f, 0.f, 0.f, 0.f};
#pragma unroll 1
      for (int v = 8; v < 12; v++) {
        float av[8];
#pragma unroll
        for (int i = 0; i < 8; i++) av[i] = __shfl_sync(0xffffffffu, act, (v - 8) * 8 + i);
        mbar_wait(bar0 + (v & 1) * 8, (v >> 1) & 1);
        gemv8x8<512>(y, buf + (v & 1) * 4096 + lane * 16, av);
        fence_regs(y);
        __syncwarp();
        if (v < 10) load_unit(v + 2);
        if (j == 0) TIM(105 + v);
      }
      fresh_ids();
      uint4* ypart = &p.sc->ypart[(a * NSRC + src) * 64 + lane];
      pkt_st128(ypart, with_bit(y[0], c0), with_bit(y[1], c1), with_bit(y[2], c0), with_bit(y[3], c1));
      pkt_st128(ypart + 32, with_bit(y[4], c0), with_bit(y[5], c1), with_bit(y[6], c0), with_bit(y[7], c1));
      if (lane == 0) TIM(160 + a);
    }
    if (a == 3) {
      const uint32_t hh = __all_sync(0xffffffffu, hp2.y == tag) ? hp2.x : poll64_warp(&p.sc->ch[SM<uint32_t>(INFO_KEY + 4) * 512 + (cid >> 1) * 8 + (lane & 7)], tag, 100);
      const uint32_t key = SM<uint32_t>(INFO_KEY);
      const float h = m ? bf_hi(hh) : bf_lo(hh), hn = bf16r(bf16r(h - SM<float>(INFO_LN)) * SM<float>(INFO_LN + 4));
      float sig = sigmoid_bf(key_val(key));
      bf16* op = p.out + (key_row(key) * 1024 + cid * 8 + (lane & 7));
      asm volatile("" : "+f"(sig), "+l"(op));
      wait_clk(t2, ROW_CLK);
      uint4 v[7]; uint32_t n = 0;
      bool more;
#pragma unroll 1
      do {
        if (elect_one()) { mbar_expect_tx(bar0, NSRC * 32); tma_load_2d(buf, &p.tmY, bar0, (cid & 31) * 8, (cid >> 5) * (2 * NSRC)); }
        mbar_wait(bar0, n & 1);
        uint32_t bad = 0;
#pragma unroll
        for (int i = 0; i < 7; i++) { v[i] = lds128(buf + i * 512 + lane * 16); chk_code(bad, v[i], c0, c1); }
        more = __any_sync(0xffffffffu, bad & 1) && ++n < SPIN_LIMIT;
        if (more) __nanosleep(200);
      } while (more);
      if (lane == 0) TIM(164);
      float y[4] = {0.f, 0.f, 0.f, 0.f};
#pragma unroll
      for (int i = 0; i < 7; i++) { y[0] += no_bit(v[i].x); y[1] += no_bit(v[i].y); y[2] += no_bit(v[i].z); y[3] += no_bit(v[i].w); }
      fold<4>(y, 16, lane); fold<2>(y, 8, lane);
      y[0] += __shfl_xor_sync(0xffffffffu, y[0], 4);
      y[0] += __shfl_xor_sync(0xffffffffu, y[0], 2);
      const float ys = __shfl_sync(0xffffffffu, y[0], (lane & 3) * 8 + ((lane >> 2) & 1));
      if (lane < 8) st_bf16(op, routed_out(h, hn, ys, sig));
      if (lane == 0) { TIM(118); pkt_st64(&p.sc->rdone[cid], 0, tag); }
    }
  } else {
    reg_inc<216>();
    const uint32_t sb = __shfl_sync(0xffffffffu, smem_u32(smem_raw), 0);
    auto BAR = [&](int i) { return sb + OFF_BAR + 8 * i; };
    const int w = warp >> 2, wi = warp & 3, t = tid & 127;
    const int turn_me = NB_TURN0 + w, turn_other = NB_TURN1 - w;
    const uint64_t dA0 = make_desc(sb + w * 8192);
    uint64_t dA, dB;
    int tau, eps, m, grp, abrow, fc, src;
    bool ffn;
    const CUtensorMap* tmD; const CUtensorMap* tmW;
    auto new_desc = [&](int salt) {
      const uint32_t z = salt < 0 ? uniform_zero_here() : salt & blockIdx.y;
      dA = dA0 + z; dB = dA0 + (z + ((A_BYTES - w * 8192) >> 4));
      const int c = cid + z;
      tau = c >> 4; eps = (c >> 1) & 7; m = c & 1; grp = tau * 2 + m; abrow = m * 1024 + eps * 128;
      const int ef = tau ? eps : eps ^ 5;
      ffn = ef > 0; fc = (tau * 7 + ef - 1) * 64; src = (fc >> 5) + m;
      tmD = &p.tmD0 + m; tmW = &p.tmW0 + m;
    };
    constexpr int SL = ST_BYTES >> 4;
    float acc[128];
#pragma unroll
    for (int i = 0; i < 128; i++) acc[i] = 0.f;
    if (w == 1) bar_arrive(NB_TURN0, 256);
    auto full = [&](int k) { mbar_wait(BAR(B_FULL + (k & 3)), (k >> 2) & 1); CT(64 + k); };
    auto refill_w = [&](int k) {
      if (warp == 4) {
        if (elect_one()) {
          const int s = k & 3, s0 = k_col(tau, k - 12);
          TIM(k + 4);
          mbar_expect_tx(BAR(B_FULL + s), k < 16 ? B_BYTES : ST_BYTES);
          if (k == 19) mbar_arrive(BAR(B_EMPTY));
          tma_load_2d(sb + s * ST_BYTES + A_BYTES, tmW, BAR(B_FULL + s), s0, grp * 128);
          tma_load_2d(sb + s * ST_BYTES + A_BYTES + 16384, tmW, BAR(B_FULL + s), s0, (grp ^ 1) * 128);
        }
        __syncwarp();
      }
    };
    auto mma_ss = [&](int k) {
#pragma unroll
      for (int kk = 0; kk < 4; kk++) wgmma_n256(acc, dA + (k & 3) * SL + kk * 2, dB + (k & 3) * SL + kk * 2);
    };
    const CUtensorMap* rf_tm; uint32_t rf_dst; int rf_row, rf_c; bool rf_on;
    auto rf_set = [&](const CUtensorMap* tm, uint32_t dst, int row) {
      rf_tm = (const CUtensorMap*)__shfl_sync(0xffffffffu, (unsigned long long)tm, 0);
      rf_dst = __shfl_sync(0xffffffffu, dst, 0); rf_row = __shfl_sync(0xffffffffu, row, 0);
    };
    auto refill = [&](int s) {
      if (rf_on) {
        if (elect_one()) tma_load_2d(rf_dst + s * ST_BYTES, rf_tm, BAR(B_FULL + s), rf_c, rf_row);
        __syncwarp();
      }
      if (tid == 224) mbar_expect_tx(BAR(B_FULL + s), ST_BYTES);
    };
    const bf16* pf; int pf_step; bool pf_on;
    auto pf_ffn = [&](int v) {
      pf_on = ffn && v >= 0 && v < 12;
      pf = v < 8 ? ((lane & 16) ? p.wup : p.wgate) + (m * 512 + (wi * 8 + v) * 16 + (lane & 15)) * 3584 + fc : p.wdown + (src * 32 + (v - 8) * 8) * 1024 + t * 64;
      pf_step = v < 8 ? 16 * 3584 : 8192;
    };
    auto prefetch = [&](int s) { if (pf_on && (wi >> 1) == (s & 1)) prefetch_l2(pf + (s >> 1) * pf_step); };
    auto kstep = [&](int k) {
      full(k);
      bar_sync(turn_me, 256);
      wgmma_fence();
      mma_ss(k);
      wgmma_commit();
      bar_arrive(turn_other, 256);
    };

    uint32_t R[64];
    auto load_rs = [&](auto gi) {
      const uint32_t rsa = sb + OFF_RS + (lane & 3) * 272;
#pragma unroll
      for (int i = 4 * decltype(gi)::value; i < 4 * decltype(gi)::value + 4; i++) { const uint4 v = lds128(rsa + i * 16); R[4 * i] = v.x; R[4 * i + 1] = v.y; R[4 * i + 2] = v.z; R[4 * i + 3] = v.w; }
    };
    new_desc(64);
    rf_on = (warp >> 1) == 2;
    rf_set(wi ? tmD : &p.tmX, wi ? sb : sb + A_BYTES, wi ? eps * 128 : tau * 256);
#pragma unroll 1
    for (int k4 = 0; k4 < 12; k4 += 4) {
#pragma unroll
      for (int s = 0; s < 4; s++) {
        kstep(k4 | s);
        if (s == 0) {
          if (w == 0) pf_ffn((k4 >> 1) - 2);
          else {
            pf_on = k4 == 8 || (k4 == 4 && (lane & 7) < 3);
            pf = (m ? p.Wim : p.Wre) + (tau * 256 + eps * 32 + wi * 4 + (lane >> 3)) * 2048 + k_col(tau, (lane & 7) + (k4 == 8 ? 3 : 0));
            pf_step = 16 * 2048;
          }
        }
        rf_c = (k4 + s + 4) * 64;
        prefetch(s);
        if (s == 3) new_desc(k4);
        if (s == 0 || s == 3) pf += zero_here();
        wgmma_wait<0>();
        refill(s);
      }
    }
    kstep(12);
    mbar_wait(BAR(B_STAT), 0);
    load_rs(std::integral_constant<int, 0>());
    CT(1);
    load_rs(std::integral_constant<int, 1>());
    wgmma_wait<0>(); refill_w(12);
    auto mma_h = [&](float (&d)[64], int s, int half) {
#pragma unroll
      for (int kk = 0; kk < 4; kk++) wgmma_n128(d, dA + s * SL + kk * 2, dB + s * SL + half * 1024 + kk * 2);
    };
    const int rho = 16 * wi + (lane & 15);
    const uint32_t arow = sb + w * 8192 + rho * 128 + (((lane >> 4) ^ (rho & 7)) << 4);
    auto convert = [&](auto cc, const float* d) {
      const float z = __uint_as_float(zero_here());
#pragma unroll
      for (int jj = 8 * decltype(cc)::value; jj < 8 * decltype(cc)::value + 8; jj++) {
        const float r0 = __uint_as_float(R[2 * jj]), r1 = __uint_as_float(R[2 * jj + 1]);
        const float* ac = &d[4 * (jj & 7)];
        R[2 * jj] = pack_bf16(fmaf(ac[0], r0, z), fmaf(ac[1], r1, z));
        R[2 * jj + 1] = pack_bf16(fmaf(ac[2], r0, z), fmaf(ac[3], r1, z));
      }
    };
    auto put = [&](auto cc) {
      constexpr int c = decltype(cc)::value;
      const uint32_t a0 = c == 1 || c == 2 ? arow + zero_here() : arow;
#pragma unroll
      for (int jj = 8 * c; jj < 8 * c + 8; jj += 2)
        stsm_x4((a0 ^ ((jj & 7) << 4)) + off_stage(c), R[2 * jj], R[2 * jj + 1], R[2 * jj + 2], R[2 * jj + 3]);
      __syncwarp();
      if (lane == 0) mbar_arrive(BAR(B_EP + w * 4 + c));
    };
    {
      float lo[32], hi[96];
      fence_regs(acc);
#pragma unroll
      for (int i = 0; i < 32; i++) asm volatile("mov.b32 %0, %1;" : "=f"(lo[i]) : "f"(acc[i]));
#pragma unroll
      for (int i = 0; i < 96; i++) asm volatile("mov.b32 %0, %1;" : "=f"(hi[i]) : "f"(acc[32 + i]));
      auto mma_p = [&](auto& d, int s, int boff) {
#pragma unroll
        for (int kk = 0; kk < 4; kk++) wgmma_part(d, dA + s * SL + kk * 2, dB + s * SL + boff + kk * 2);
      };
      const uint64_t dEA = make_desc_noswz(sb + OFF_EXA + w * 1024), dEB = make_desc_noswz(sb + OFF_EXB);
      full(13); full(14);
      bar_sync(turn_me, 256);
      wgmma_fence();
      mma_p(lo, 1, 0); mma_p(lo, 2, 0);
      wgmma_commit();
      bar_arrive(turn_other, 256);
      new_desc(66);
      full(15);
      bar_sync(turn_me, 256);
      wgmma_fence();
      mma_p(lo, 3, 0);
      wgmma_part(lo, dEA, dEB);
      wgmma_commit();
      mma_p(hi, 1, 512);
      wgmma_commit();
      bar_arrive(turn_other, 256);
      new_desc(67);
      wgmma_wait<1>();
      fence_regs(lo);
      CT(15);
      convert(std::integral_constant<int, 0>(), lo); put(std::integral_constant<int, 0>());
      load_rs(std::integral_constant<int, 3>());
      wgmma_wait<0>(); refill_w(13);
      bar_sync(turn_me, 256);
      wgmma_fence();
      mma_p(hi, 2, 512);
      wgmma_commit();
      mma_p(hi, 3, 512);
      wgmma_part(hi, dEA, dEB + 64);
      wgmma_commit();
      bar_arrive(turn_other, 256);
      load_rs(std::integral_constant<int, 2>());
      wgmma_wait<1>(); refill_w(14);
      wgmma_wait<0>(); refill_w(15);
      fence_regs(hi);
      CT(2);
      convert(std::integral_constant<int, 3>(), hi + 64);
      put(std::integral_constant<int, 3>());
      convert(std::integral_constant<int, 1>(), hi);
      convert(std::integral_constant<int, 2>(), hi + 32);
    }
    CT(3);
    new_desc(-1);
    full(16);
    bar_sync(turn_me, 256);
    wgmma_fence();
    wgmma_n256_rs_init(acc, R, dB);
#pragma unroll
    for (int kk = 1; kk < 4; kk++) wgmma_n256_rs(acc, R + 4 * kk, dB + kk * 2);
    wgmma_commit();
    full(17);
    wgmma_fence();
#pragma unroll
    for (int kk = 0; kk < 4; kk++) wgmma_n256_rs(acc, R + 16 + 4 * kk, dB + SL + kk * 2);
    wgmma_commit();
    bar_arrive(turn_other, 256);
    put(std::integral_constant<int, 2>());
    wgmma_wait<1>(); refill_w(16);
    wgmma_wait<0>(); refill_w(17);
    {
      fence_async_smem();
      mbar_wait(BAR(B_WC), 0);
      CT(4);
      full(18);
      bar_sync(turn_me, 256);
      wgmma_fence();
      float cc[4];
      const uint64_t dC = make_desc(sb + OFF_WC);
      wgmma_n8_rs<0>(cc, R, dC);
#pragma unroll
      for (int i = 1; i < 12; i++) wgmma_n8_rs<1>(cc, R + 4 * i, dC + (i >> 2) * 64 + (i & 3) * 2);
#pragma unroll
      for (int kk = 0; kk < 4; kk++) wgmma_n8(cc, dA + 3 * SL + kk * 2, dC + 192 + kk * 2);
      wgmma_commit();
#pragma unroll
      for (int kk = 0; kk < 4; kk++) wgmma_n256_rs(acc, R + 32 + 4 * kk, dB + 2 * SL + kk * 2);
      wgmma_commit();
      bar_arrive(turn_other, 256);
      wgmma_wait<1>();
      fence_regs(cc);
      const uint32_t cd = code_of(SM<uint32_t>(INFO_TAG));
      if (t == 0) mbar_arrive(BAR(B_CD));
      pkt_st128(&p.sc->cpart[((lane & 3) * 16 + grp) * 512 + eps * 64 + warp * 8 + (lane >> 2)], with_bit(cc[0], cd), with_bit(cc[1], cd >> 1), with_bit(cc[2], cd), with_bit(cc[3], cd >> 1));
      CT(5);
    }
    put(std::integral_constant<int, 1>());
    wgmma_wait<0>(); refill_w(18);
    kstep(19);
    cluster_wait();
    new_desc(68);
    rf_set(wi == 2 ? &p.tmAbL : tmW, wi == 2 ? sb : sb + A_BYTES + wi * 16384, wi == 2 ? abrow : (grp ^ wi) * 128);
    wgmma_wait<0>(); refill_w(19);
    const int g = lane >> 2, q = lane & 3;
    uint4 ha[4], hb[4], wv[4], info = make_uint4(0, 0, 0, 0);
#pragma unroll
    for (int i = 0; i < 4; i++) ha[i] = hb[i] = wv[i] = make_uint4(0, 0, 0, 0);
    auto load_x = [&](auto ii) {
      constexpr int i = decltype(ii)::value;
      const bf16* xp = p.x + ((grp * 128 + warp * 16 + g) * 1024 + eps * 128 + q * 8);
      ha[i] = ldg128(xp + i * 32); hb[i] = ldg128(xp + 8192 + i * 32);
    };
    auto load_w = [&]() {
      mbar_wait(BAR(B_INFO), 0);
#pragma unroll
      for (int i = 0; i < 4; i++) wv[i] = lds128(sb + ((g & 1) ? OFF_WR + (i * 4 + q) * 16 : INFO_ONES));
      info = lds128(sb + OFF_INFO);
    };

    rf_on = w == 1 && wi < 3;
    rf_c = k_col(tau, 7);
#pragma unroll 1
    for (int k4 = 20; k4 < 44; k4 += 4) {
#pragma unroll
      for (int s = 0; s < 4; s++) {
        kstep(k4 | s);
        if (s == 0) {
          if (w == 0) { pf_ffn((k4 >> 1) - 8); pf_on = pf_on && k4 >= 24; }
          else {
            pf_on = k4 == 32;
            pf = p.x + (grp * 128 + (t >> 1)) * 1024 + eps * 128 + (t & 1) * 64;
            pf_step = 64 * 1024;
          }
        }
        rf_c = k_next(rf_c, k4 + s - 12);
        if (s == 0 && k4 == 20 && warp == 6) mbar_wait(BAR(B_ALL), 0);
        if (s == 2 && k4 == 24 && warp == 6) mbar_wait(BAR(B_ALL + 1), 0);
        prefetch(s);
        if (k4 == 40) {
          if (s == 1) load_w();
          if (s == 2) load_x(std::integral_constant<int, 0>());
          if (s == 3) load_x(std::integral_constant<int, 1>());
        }
        if (s == 3) new_desc(k4);
        if (s == 0 || s == 3) pf += zero_here();
        wgmma_wait<0>();
        if (((s == 3 && k4 == 20) || (s < 2 && k4 == 24)) && warp == 6) { if (lane == 0) mbar_arrive(BAR(B_E23 + ((s + 1) & 3))); }
        else refill(s);
      }
    }
    const int row0 = grp * 128 + warp * 16 + g;
    kstep(44);
    load_x(std::integral_constant<int, 2>());
    wgmma_wait<0>();
    if (tid == 128) mbar_arrive_remote(mapa(BAR(B_PEER), m ^ 1));
    uint32_t hp[32];
    bf16* op; uint4* hpub; uint4* hst;
    uint32_t cd, ast, ald, zr;
    auto swz = [](int row) { return ((row & 1) << 2) | ((row >> 1) & 3); };
    {
      float as[64], ak[64];
      fence_regs(acc);
#pragma unroll
      for (int i = 0; i < 64; i++) asm volatile("mov.b32 %0, %1;" : "=f"(as[i]) : "f"(acc[64 + i]));
#pragma unroll
      for (int i = 0; i < 64; i++) asm volatile("mov.b32 %0, %1;" : "=f"(ak[i]) : "f"(acc[i]));
      full(45); full(46);
      bar_sync(turn_me, 256);
      wgmma_fence();
      mma_h(as, 1, 1); mma_h(as, 2, 1);
      wgmma_commit();
      bar_arrive(turn_other, 256);
      load_x(std::integral_constant<int, 3>());
      full(47);
      bar_sync(turn_me, 256);
      wgmma_fence();
      mma_h(as, 3, 1);
      wgmma_commit();
      const uint32_t rx = mapa(sb + OFF_RECV + w * 16384 + t * 16, m ^ 1), rb = mapa(BAR(B_XCH + w), m ^ 1);
      mma_h(ak, 1, 0);
      wgmma_commit();
      bar_arrive(turn_other, 256);
      mbar_wait_bounded(BAR(B_PEER), 0);
      wgmma_wait<1>();
      fence_regs(as);
      CT(6);
#pragma unroll
      for (int i = 0; i < 8; i++) {
        const float* ac = &as[8 * i];
        st_async_v4(rx + i * 2048, rb, pack_bf16(ac[0], ac[1]), pack_bf16(ac[2], ac[3]), pack_bf16(ac[4], ac[5]), pack_bf16(ac[6], ac[7]));
      }
      CT(7);
      bar_sync(turn_me, 256);
      wgmma_fence();
      mma_h(ak, 2, 0); mma_h(ak, 3, 0);
      wgmma_commit();
      if (w == 0) bar_arrive(turn_other, 256);
      op = p.out + row0 * 1024 + eps * 128 + q * 8;
      hst = &p.sc->hstat[grp * 1024 + warp * 16 + g];
      hpub = hst + eps * 128; hst += q * 256;
      cd = code_of(info.y);
      ast = sb + w * ST_BYTES + (8 * (lane >> 4) + (lane & 7)) * 128 + (((2 * wi + ((lane >> 3) & 1)) ^ swz(lane & 7)) << 4);
      ald = sb + (warp * 16 + g) * 128 + ((q ^ swz(g)) << 4);
      asm volatile("" : "+l"(op), "+l"(hpub), "+l"(hst), "+r"(cd), "+r"(ast), "+r"(ald));
      zr = zero_here();
#pragma unroll
      for (int i = 0; i < 4; i++) { ha[i].x += zr; hb[i].x += zr; asm volatile("" : "+r"(ha[i].x), "+r"(hb[i].x)); }
      ast += (uint32_t)(clock64() >> 32) & zr;
      mbar_wait_bounded(BAR(B_XCH + w), 0);
      CT(9);
#pragma unroll
      for (int i = 0; i < 8; i++) { const uint4 v = lds128(sb + OFF_RECV + w * 16384 + t * 16 + i * 2048); hp[4 * i] = v.x; hp[4 * i + 1] = v.y; hp[4 * i + 2] = v.z; hp[4 * i + 3] = v.w; }
      wgmma_wait<0>();
      fence_regs(ak);
      CT(10);
#pragma unroll
      for (int i = 0; i < 32; i++) hp[i] = badd2(pack_bf16(ak[2 * i], ak[2 * i + 1]), hp[i]);
    }
#pragma unroll
    for (int jj = 0; jj < 16; jj += 2) stsm_x4_t(ast + jj * 1024, hp[2 * jj], hp[2 * jj + 1], hp[2 * jj + 2], hp[2 * jj + 3]);
    const uint32_t tag = info.y;
    uint4 v[4];
    auto fetch = [&]() { v[0] = pkt_ld128(hst); v[1] = pkt_ld128(hst + 128); v[2] = pkt_ld128(hst + 8); v[3] = pkt_ld128(hst + 136); };
    float st[6], hf[64];
    {
      float sw[2][4], qa[2][4], qb[2][4];
#pragma unroll
      for (int i = 0; i < 8; i++) { sw[i >> 2][i & 3] = 0.f; qa[i >> 2][i & 3] = 0.f; qb[i >> 2][i & 3] = 0.f; }
      bar_sync(NB_BOTH, 256);
      CT(11);
      uint4 ya[4], yb[4];
#pragma unroll
      for (int i = 0; i < 4; i++) {
        const uint32_t ad = (ald ^ ((i & 1) << 6)) + (i >> 1) * ST_BYTES;
        ya[i] = lds128(ad); yb[i] = lds128(ad + 1024);
      }
      fetch();
      sw[0][0] = __uint_as_float((uint32_t)(clock64() >> 32) & zr);
#pragma unroll
      for (int i = 0; i < 4; i++) {
        ha[i] = make_uint4(badd2(ha[i].x, ya[i].x), badd2(ha[i].y, ya[i].y), badd2(ha[i].z, ya[i].z), badd2(ha[i].w, ya[i].w));
        hb[i] = make_uint4(badd2(hb[i].x, yb[i].x), badd2(hb[i].y, yb[i].y), badd2(hb[i].z, yb[i].z), badd2(hb[i].w, yb[i].w));
        mma16816(sw[0], ha[i].x, hb[i].x, ha[i].y, hb[i].y, wv[i].x, wv[i].y);
        mma16816(qa[0], ha[i].x, hb[i].x, ha[i].y, hb[i].y, ha[i].x, ha[i].y);
        mma16816(qb[0], ha[i].x, hb[i].x, ha[i].y, hb[i].y, hb[i].x, hb[i].y);
        mma16816(sw[1], ha[i].z, hb[i].z, ha[i].w, hb[i].w, wv[i].z, wv[i].w);
        mma16816(qa[1], ha[i].z, hb[i].z, ha[i].w, hb[i].w, ha[i].z, ha[i].w);
        mma16816(qb[1], ha[i].z, hb[i].z, ha[i].w, hb[i].w, hb[i].z, hb[i].w);
      }
      const uint32_t s0 = with_bit(sw[0][0] + sw[1][0], cd), s1 = with_bit((g & 1) ? qa[0][1] + qa[1][1] : qa[0][0] + qa[1][0], cd >> 1), s2 = __float_as_uint(sw[0][1] + sw[1][1]);
      const uint32_t s3 = with_bit(sw[0][2] + sw[1][2], cd), s4 = with_bit((g & 1) ? qb[0][3] + qb[1][3] : qb[0][2] + qb[1][2], cd >> 1), s5 = __float_as_uint(sw[0][3] + sw[1][3]);
      if (q == (g >> 1)) { pkt_st128(hpub, s0, s1, s2, tag); pkt_st128(hpub + 8, s3, s4, s5, tag); }
      CT(12);
      {
#pragma unroll
        for (int i = 0; i < 8; i++) {
          const uint4 h = i < 4 ? ha[i] : hb[i - 4];
          hf[8 * i] = bf_lo(h.x); hf[8 * i + 1] = bf_hi(h.x); hf[8 * i + 2] = bf_lo(h.y); hf[8 * i + 3] = bf_hi(h.y);
          hf[8 * i + 4] = bf_lo(h.z); hf[8 * i + 5] = bf_hi(h.z); hf[8 * i + 6] = bf_lo(h.w); hf[8 * i + 7] = bf_hi(h.w);
        }
        fence_regs(hf);
        op += (uint32_t)(clock64() >> 32) & zr;
      }
      const uint32_t o1 = __shfl_sync(0xffffffffu, s1, (lane & 28) | (g >> 1)), o4 = __shfl_sync(0xffffffffu, s4, (lane & 28) | (g >> 1));
      uint32_t n = 0;
      bool more;
#pragma unroll 1
      do {
        if (2 * q == eps) { v[0] = make_uint4(s0, o1, s2, tag); v[2] = make_uint4(s3, o4, s5, tag); }
        if (2 * q + 1 == eps) { v[1] = make_uint4(s0, o1, s2, tag); v[3] = make_uint4(s3, o4, s5, tag); }
        uint32_t bad = 0;
#pragma unroll
        for (int i = 0; i < 4; i++) { chk(bad, v[i].x, cd); chk(bad, v[i].y, cd >> 1); }
        bad &= 1;
#pragma unroll
        for (int i = 0; i < 4; i++) chk(bad, v[i].w, tag);
        more = __any_sync(0xffffffffu, bad) && ++n < SPIN_LIMIT;
        if (more && bad) fetch();
      } while (more);
      st[0] = no_bit(v[0].x) + no_bit(v[1].x); st[1] = no_bit(v[0].y) + no_bit(v[1].y); st[2] = __uint_as_float(v[0].z) + __uint_as_float(v[1].z);
      st[3] = no_bit(v[2].x) + no_bit(v[3].x); st[4] = no_bit(v[2].y) + no_bit(v[3].y); st[5] = __uint_as_float(v[2].z) + __uint_as_float(v[3].z);
    }
    CT(13);
#pragma unroll
    for (int o = 1; o < 4; o <<= 1) {
#pragma unroll
      for (int i = 0; i < 6; i++) st[i] += __shfl_xor_sync(0xffffffffu, st[i], o);
    }
    float mb[2], inv[2];
#pragma unroll
    for (int i = 0; i < 2; i++) {
      const float mu = st[3 * i] * (1.f / 1024.f);
      mb[i] = bf16r(mu);
      inv[i] = fast_rcp(ref_sd(fmaxf(st[3 * i + 1] * (1.f / 1024.f) - mu * mu, 0.f)));
    }
    {
      const int srow = key_row(info.z);
      auto put_out = [&](bf16* dst, const float* f, float sc, float of, bool on) {
        auto cvt = [&](int i) { return pack_bf16(fmaf(f[i], sc, of), fmaf(f[i + 1], sc, of)); };
        asm volatile("{\n.reg .pred p;\nsetp.ne.b32 p, %5, 0;\n@p st.global.v4.b32 [%0], {%1, %2, %3, %4};\n}\n"
                     :: "l"(dst), "r"(cvt(0)), "r"(cvt(2)), "r"(cvt(4)), "r"(cvt(6)), "r"((int)on) : "memory");
      };
#pragma unroll
      for (int i = 0; i < 4; i++) {
        put_out(op + i * 32, hf + 8 * i, 1.f + inv[0], -mb[0] * inv[0], row0 != srow);
        put_out(op + 8192 + i * 32, hf + 32 + 8 * i, 1.f + inv[1], -mb[1] * inv[1], row0 + 8 != srow);
      }
    }
    CT(14);
    const uint4 cand = lds128(sb + INFO_CAND);
    uint32_t wkey = zero_here();
#pragma unroll
    for (int i = 0; i < 2; i++) {
      const uint32_t row = row0 + 8 * i, rr = row | (row << 16);
      const bool is_cand = __vcmpeq2(cand.x, rr) | __vcmpeq2(cand.y, rr) | __vcmpeq2(cand.z, rr) | __vcmpeq2(cand.w, rr);
      if (!is_cand) wkey = max(wkey, make_key(bf16r((st[3 * i + 2] - mb[i] * __uint_as_float(info.x)) * inv[i]), row));
    }
    wkey = __reduce_max_sync(0xffffffffu, wkey);
    if (eps == 0 && lane == 0) pkt_st64(&p.sc->key[grp * 8 + warp], wkey, tag);
    const bool beaten = (wkey >> 16) > (info.z >> 16);
    if (__builtin_expect(beaten, 0)) {
      const int br = key_row(wkey);
      if (br == row0 || br == row0 + 8) {
#pragma unroll
        for (int i = 0; i < 4; i++) {
          const uint4 h = br == row0 ? ha[i] : hb[i];
          uint2* dst = &p.sc->hrow[(grp * 8 + warp) * 512 + eps * 64 + i * 16 + q * 4];
          pkt_st128(dst, h.x, tag, h.y, tag); pkt_st128(dst + 2, h.z, tag, h.w, tag);
        }
      }
      __syncwarp();
    }
    uint32_t any;
    asm volatile("{\n.reg .pred p, q;\nsetp.ne.b32 p, %1, 0;\nbarrier.cta.red.or.aligned.pred q, %2, 256, p;\nselp.u32 %0, 1, 0, q;\n}\n" : "=r"(any) : "r"((int)beaten), "n"((int)NB_END) : "memory");
    if (__builtin_expect(any, 0)) slow_path(p, grp, eps, tag, info.z, info.w, SM<float>(INFO_LN), SM<float>(INFO_LN + 4));
  }
}

__global__ void __launch_bounds__(NTHR, 1) occupancy_probe_kernel() {}

typedef CUresult (*EncodeFn)(CUtensorMap*, CUtensorMapDataType, cuuint32_t, void*, const cuuint64_t*, const cuuint64_t*, const cuuint32_t*, const cuuint32_t*,
                             CUtensorMapInterleave, CUtensorMapSwizzle, CUtensorMapL2promotion, CUtensorMapFloatOOBfill);

static void make_tm(EncodeFn enc, CUtensorMap* tm, const void* ptr, uint64_t rows, uint64_t cols, uint32_t brows, uint32_t bcols, bool swz) {
  cuuint64_t dims[2] = {cols, rows};
  cuuint64_t strides[1] = {cols * 2};
  cuuint32_t box[2] = {bcols, brows};
  cuuint32_t es[2] = {1, 1};
  enc(tm, CU_TENSOR_MAP_DATA_TYPE_BFLOAT16, 2, const_cast<void*>(ptr), dims, strides, box, es, CU_TENSOR_MAP_INTERLEAVE_NONE,
      swz ? CU_TENSOR_MAP_SWIZZLE_128B : CU_TENSOR_MAP_SWIZZLE_NONE, CU_TENSOR_MAP_L2_PROMOTION_L2_128B, CU_TENSOR_MAP_FLOAT_OOB_FILL_NONE);
}

extern "C" void kernel_launch(void* const* d_in, const int* in_sizes, int n_in, void* d_out, int out_size) {
  (void)in_sizes; (void)n_in; (void)out_size;
  static EncodeFn enc = nullptr;
  static void* abT = nullptr;
  static void* sc = nullptr;
  static int map = 0;
  if (!enc) {
    void* fn = nullptr; cudaDriverEntryPointQueryResult st;
    cudaGetDriverEntryPoint("cuTensorMapEncodeTiled", &fn, cudaEnableDefault, &st);
    enc = (EncodeFn)fn;
    cudaGetSymbolAddress(&abT, g_abT);
    cudaGetSymbolAddress(&sc, g_sc);
    cudaFuncSetAttribute(fnet_moe_kernel<0>, cudaFuncAttributeMaxDynamicSharedMemorySize, SMEM_TOTAL);
    cudaFuncSetAttribute(fnet_moe_kernel<1>, cudaFuncAttributeMaxDynamicSharedMemorySize, SMEM_TOTAL);
    cudaFuncSetAttribute(occupancy_probe_kernel, cudaFuncAttributeMaxDynamicSharedMemorySize, SMEM_TOTAL);
    cudaFuncSetAttribute(occupancy_probe_kernel, cudaFuncAttributeNonPortableClusterSizeAllowed, 1);
    cudaLaunchConfig_t cfg = {};
    cfg.gridDim = dim3(128); cfg.blockDim = dim3(NTHR); cfg.dynamicSmemBytes = SMEM_TOTAL;
    cudaLaunchAttribute at[1];
    at[0].id = cudaLaunchAttributeClusterDimension; at[0].val.clusterDim.x = 16; at[0].val.clusterDim.y = 1; at[0].val.clusterDim.z = 1;
    cfg.attrs = at; cfg.numAttrs = 1;
    int ncl = 0;
    if (cudaOccupancyMaxActiveClusters(&ncl, occupancy_probe_kernel, &cfg) == cudaSuccess && ncl >= 8) map = 1;
    (void)cudaGetLastError();
  }
  Params p;
  const bf16* x = (const bf16*)d_in[0];
  make_tm(enc, &p.tmD0, d_in[3], 1024, 1024, 128, 64, true);
  make_tm(enc, &p.tmD1, d_in[4], 1024, 1024, 128, 64, true);
  make_tm(enc, &p.tmX, x, 2048, 1024, 256, 64, true);
  make_tm(enc, &p.tmAbS, abT, 2048, 2048, 64, 64, true);
  make_tm(enc, &p.tmAbL, abT, 2048, 2048, 128, 64, true);
  make_tm(enc, &p.tmW0, d_in[1], 2048, 2048, 128, 64, true);
  make_tm(enc, &p.tmW1, d_in[2], 2048, 2048, 128, 64, true);
  make_tm(enc, &p.tmG, d_in[7], 1024, 3584, 16, 64, false);
  make_tm(enc, &p.tmU, d_in[8], 1024, 3584, 16, 64, false);
  make_tm(enc, &p.tmDn, d_in[9], 3584, 1024, 8, 256, false);
  make_tm(enc, &p.tmY, (char*)sc + offsetof(Scratch, ypart), 8 * NSRC, 256, 2 * NSRC, 8, false);
  p.x = x; p.Dre = (const bf16*)d_in[3]; p.Dim = (const bf16*)d_in[4];
  p.wr = (const bf16*)d_in[6]; p.wdown = (const bf16*)d_in[9]; p.wgate = (const bf16*)d_in[7]; p.wup = (const bf16*)d_in[8]; p.Wre = (const bf16*)d_in[1]; p.Wim = (const bf16*)d_in[2];
  p.out = (bf16*)d_out; p.sc = (Scratch*)sc;
  if (map == 1) fnet_moe_kernel<1><<<NGRID, NTHR, SMEM_TOTAL>>>(p);
  else fnet_moe_kernel<0><<<NGRID, NTHR, SMEM_TOTAL>>>(p);
}
```
